```python
import torch

def _softmax(x, axis=-1):
    return torch.softmax(x, dim=axis)
def _gelu(x):
    return torch.nn.functional.gelu(x, approximate="tanh")
def _silu(x):
    return torch.nn.functional.silu(x)
def _sigmoid(x):
    return torch.sigmoid(x)
def _layernorm(x, axis=-1, eps=1e-5):
    m = x.mean(dim=axis, keepdim=True)
    v = x.var(dim=axis, keepdim=True, unbiased=False)
    return (x - m) / torch.sqrt(v + eps)
def _scatter_add(tgt, idx, src, axis=0):
    return tgt.clone().index_add_(axis, idx, src)
def _segment_sum(src, seg, n):
    out = torch.zeros((n,) + src.shape[1:], dtype=src.dtype)
    return out.index_add_(0, seg, src)
def _pad(x, pw):
    flat = tuple(v for pair in reversed(pw) for v in pair)
    return torch.nn.functional.pad(x, flat)

kernel_name = 'standalone__hybrid_graph_tf_graphgps__graph'

def setup_inputs():

    _w = (lambda a: (lambda t: t.to(torch.bfloat16) if t.is_floating_point() else t)(torch.as_tensor(a)))
    N, deg, D = 10000, 16, 256
    E = N * deg
    src = (lambda lo, hi, *s: torch.randint(lo, hi, s))(0, N, E).to(torch.int64)
    dst = (lambda lo, hi, *s: torch.randint(lo, hi, s))(0, N, E).to(torch.int64)
    deg_cnt = torch.bincount(dst, minlength=N).to(float) + 1.0
    sc = 1.0 / float(D) ** 0.5
    return {
        "x": _w((lambda *s: torch.randn(*s, dtype=torch.bfloat16) * 0.05)(N, D)),
        "src": _w(src),
        "dst": _w(dst),
        "deg_inv": _w((1.0 / deg_cnt).to(float)),
        "w_msg": _w((lambda *s: torch.randn(*s, dtype=torch.bfloat16) * 0.2)(D, D) * sc),
        "wq": _w((lambda *s: torch.randn(*s, dtype=torch.bfloat16) * 1.6)(D, D) * sc),
        "wk": _w((lambda *s: torch.randn(*s, dtype=torch.bfloat16) * 1.6)(D, D) * sc),
        "wv": _w((lambda *s: torch.randn(*s, dtype=torch.bfloat16) * 0.2)(D, D) * sc),
        "w_out": _w((lambda *s: torch.randn(*s, dtype=torch.bfloat16) * 0.2)(D, D) * sc),
    }

def reference(x, src, dst, deg_inv, w_msg, wq, wk, wv, w_out):
    N, D = x.shape[0], x.shape[1]
    h = _layernorm(x, axis=-1)
    m_e = torch.einsum('nd,de->ne', h, w_msg)
    h_local = _segment_sum(m_e[src], dst, N) * deg_inv[:, None]
    q = torch.einsum('nd,de->ne', h, wq)
    k = torch.einsum('nd,de->ne', h, wk)
    v = torch.einsum('nd,de->ne', h, wv)
    logits = torch.einsum('id,jd->ij', q, k) / (float(D) ** 0.5)
    attn = _softmax(logits, axis=-1)
    h_global = torch.einsum('ij,jd->id', attn, v)
    y = torch.einsum('nd,de->ne', h_local + h_global, w_out)
    return x + y
```

```cpp
#include <cuda_runtime.h>
#include <cuda_bf16.h>
#include <stdint.h>
#include <stddef.h>
#include <type_traits>
#define FB 5
#define MB 5
#define GSTART 10000
#define G8 1
#define XDELAY 200
#define CREG 224
#define BACKOFF 1000

namespace {

constexpr int NN = 10000;
constexpr int NE = 160000;
constexpr int NQT = 79;
constexpr int NCTA = 132;
constexpr int CAP = 64;
constexpr int CAPS = 64;
constexpr int NHSIG = 105;
constexpr uint32_t WCH_B = 32768;
constexpr int NGW = (NCTA - 1) * 3;
constexpr float TAU = 16.0f;
constexpr float SAFE_N2 = 38.0f;

constexpr int NAGG = 4;
constexpr int NRND = (NN + NGW - 1) / NGW;
constexpr int NSLOT = 105;
constexpr int F_EPOCH = 0, F_H = 1, F_M = 4  , LN_ = 32;
constexpr int F_BIN = LN_, F_W = 2 * LN_, F_OVF = 3 * LN_  , F_QP = 5 * LN_, F_AGG = F_QP + NQT * LN_,
              F_PART = F_AGG + NAGG * LN_, F_END = F_PART + 2 * NSLOT * LN_;

struct Scratch {
  uint32_t flag[F_END];
  alignas(4096) uint4 M[8192];
  uint4 Wvo[8192], Wmo[8192];
  float2 ml[NSLOT * 128];
  uint32_t unsafe[96];
  int cnt[NN + 32];
  alignas(4096) uint4 h[2 * NQT * 4096 + 256];
  uint4 qp[NQT * 4096];
  uint4 agg[NQT * 4096];
  uint4 part[NSLOT * 4096];
  int bin[(NN + NGW) * CAPS];
  int2 ovf[NE];
};
static_assert(offsetof(Scratch, h) % 128 == 0, "alignment");
__device__ Scratch g_scr;
struct alignas(16) Work { short k0, k1; signed char q0, q1, nb0, na0, nb1, na1, slotA, slotB, loc0, nloc, own, role; };
constexpr int R_FIN = 1, R_PUB = 2, R_TAIL = 4;
struct Params {
  const __nv_bfloat16 *x, *wq, *wk;
  Scratch* s;
  uint4* h;
  __nv_bfloat16* out;
  const __nv_bfloat16 *wout, *wmsg, *wv, *dinv;
  const int *src, *dst;
  long long zero;
  Work w[NCTA];
};
constexpr int NSERV = NQT - 52;
inline Work make_work(int c) {
  Work w;
  const int gi = c / 5, r = c % 5, q = gi * 3;
  const bool helper = r & 1, mid = r == 2;
  w.q0 = helper ? q + 1 : q + (r >> 1);
  const int hb1 = (15 - MB) / 2, hb3 = 15 - MB - hb1;
  w.nb0 = helper ? (r == 1 ? hb1 : hb3) : (mid ? MB : FB);
  w.na0 = (helper ? 16 : 48) - w.nb0;
  w.k0 = helper ? (48 * 8 - MB) + (r >> 1) * (16 * 8 - hb1) : 0;
  w.q1 = q + (r & 2);
  w.k1 = 48 * 8 - FB;
  w.nb1 = helper ? 7 - FB : 0;
  w.na1 = helper ? 31 - w.nb1 : 0;
  w.slotA = 4 * gi + (helper ? r - 1 : (mid ? 0 : (r >> 1) + 1));
  w.slotB = helper ? 4 * gi + r : (mid ? 4 * gi + 2 : -1);
  w.loc0 = NSERV + gi * 2 + (r >> 1);
  w.nloc = helper;
  w.own = helper ? (r + 1) >> 1 : (mid ? 0 : 3);
  w.role = helper ? 0 : (mid ? R_FIN : R_FIN | R_PUB);
  if (c == 130) { w.nb0 = 15; w.na0 = 65; w.slotA = NSLOT - 1; w.own = 1; w.role = R_FIN | R_TAIL; }
  if (c == 131) { w.nb0 = w.na0 = w.nb1 = w.na1 = 0; w.loc0 = 0; w.nloc = NSERV; w.own = 0; }
  return w;
}
#define g_flag P.s->flag
#define g_M P.s->M
#define g_Wvo P.s->Wvo
#define g_Wmo P.s->Wmo
#define g_ml P.s->ml
#define g_unsafe P.s->unsafe
#define g_cnt P.s->cnt
#define g_h P.h
#define g_qp P.s->qp
#define g_agg P.s->agg
#define g_part P.s->part
#define g_bin P.s->bin
#define g_ovf P.s->ovf

__device__ __forceinline__ uint32_t smem_u32(const void* p) { return (uint32_t)__cvta_generic_to_shared(p); }
__device__ __forceinline__ void mbar_init(uint32_t bar, uint32_t cnt) { asm volatile("mbarrier.init.shared::cta.b64 [%0], %1;" :: "r"(bar), "r"(cnt) : "memory"); }
__device__ __forceinline__ void mbar_arrive(uint32_t bar) { asm volatile("mbarrier.arrive.shared::cta.b64 _, [%0];" :: "r"(bar) : "memory"); }
__device__ __forceinline__ void mbar_expect_tx(uint32_t bar, uint32_t bytes) { asm volatile("mbarrier.arrive.expect_tx.shared::cta.b64 _, [%0], %1;" :: "r"(bar), "r"(bytes) : "memory"); }
__device__ __forceinline__ bool mbar_try_wait(uint32_t bar, uint32_t parity) {
  uint32_t ok;
  asm volatile("{\n.reg .pred p;\nmbarrier.try_wait.parity.shared::cta.b64 p, [%1], %2;\nselp.b32 %0, 1, 0, p;\n}\n" : "=r"(ok) : "r"(bar), "r"(parity) : "memory");
  return ok;
}
__device__ __forceinline__ bool mbar_try_wait_nb(uint32_t bar, uint32_t parity) {
  uint32_t ok;
  asm volatile("{\n.reg .pred p;\nmbarrier.test_wait.parity.shared::cta.b64 p, [%1], %2;\nselp.b32 %0, 1, 0, p;\n}\n" : "=r"(ok) : "r"(bar), "r"(parity) : "memory");
  return ok;
}
__device__ __forceinline__ void mbar_wait(uint32_t bar, uint32_t parity) {
#pragma unroll 1
  for (uint32_t it = 0; it < (1u << 25); it++) if (mbar_try_wait(bar, parity)) break;
}
__device__ __forceinline__ void bulk_s2g(void* dst, uint32_t src, uint32_t bytes) {
  asm volatile("cp.async.bulk.global.shared::cta.bulk_group [%0], [%1], %2;" :: "l"(dst), "r"(src), "r"(bytes) : "memory");
}
__device__ __forceinline__ void bulk_commit() { asm volatile("cp.async.bulk.commit_group;" ::: "memory"); }
__device__ __forceinline__ void bulk_wait_read() { asm volatile("cp.async.bulk.wait_group.read 0;" ::: "memory"); }
__device__ __forceinline__ void bulk_wait_all() { asm volatile("cp.async.bulk.wait_group 0;" ::: "memory"); }
__device__ __forceinline__ bool bar_red_or(int id, int cnt, bool c) {
  uint32_t r;
  asm volatile("{\n.reg .pred p, q;\nsetp.ne.b32 q, %3, 0;\nbar.red.or.pred p, %1, %2, q;\nselp.b32 %0, 1, 0, p;\n}\n"
               : "=r"(r) : "r"(id), "r"(cnt), "r"((uint32_t)c) : "memory");
  return r != 0;
}
template <class T> __device__ __forceinline__ T* pofs(const void* base, uint32_t off) {
  asm volatile("" : "+r"(off));
  return (T*)((uint8_t*)base + off);
}
__device__ __forceinline__ const void* addr64(uint32_t lo, uint32_t hi) { uint64_t a; asm("mov.b64 %0, {%1, %2};" : "=l"(a) : "r"(lo), "r"(hi)); return (const void*)a; }
__device__ __forceinline__ uint4 ldcg_v(const void* a) {
  uint4 v;
  asm volatile("ld.volatile.global.v4.u32 {%0,%1,%2,%3}, [%4];" : "=r"(v.x), "=r"(v.y), "=r"(v.z), "=r"(v.w) : "l"(a) : "memory");
  return v;
}
__device__ __forceinline__ void cp_async16(uint32_t dst, const void* src) {
  asm volatile("cp.async.cg.shared.global [%0], [%1], 16;" :: "r"(dst), "l"(src) : "memory");
}
__device__ __forceinline__ void red_bf16x8(void* a, uint4 v) {
  asm volatile("red.global.add.noftz.v4.bf16x2 [%0], {%1,%2,%3,%4};" :: "l"(a), "r"(v.x), "r"(v.y), "r"(v.z), "r"(v.w) : "memory");
}
__device__ __forceinline__ uint32_t clk() { uint32_t c; asm volatile("mov.u32 %0, %%clock;" : "=r"(c) :: "memory"); return c; }
__device__ __forceinline__ void stsm4(uint32_t a, uint32_t r0, uint32_t r1, uint32_t r2, uint32_t r3) {
  asm volatile("stmatrix.sync.aligned.m8n8.x4.shared.b16 [%0], {%1,%2,%3,%4};" :: "r"(a), "r"(r0), "r"(r1), "r"(r2), "r"(r3) : "memory");
}
__device__ __forceinline__ uint32_t lds32(uint32_t a) { uint32_t v; asm volatile("ld.shared.u32 %0, [%1];" : "=r"(v) : "r"(a) : "memory"); return v; }
__device__ __forceinline__ void cp_commit() { asm volatile("cp.async.commit_group;" ::: "memory"); }
__device__ __forceinline__ uint32_t hmul2(uint32_t a, uint32_t b) { uint32_t d; asm("mul.rn.bf16x2 %0, %1, %2;" : "=r"(d) : "r"(a), "r"(b)); return d; }
__device__ __forceinline__ uint32_t hfma2(uint32_t a, uint32_t b, uint32_t c) { uint32_t d; asm("fma.rn.bf16x2 %0, %1, %2, %3;" : "=r"(d) : "r"(a), "r"(b), "r"(c)); return d; }
__device__ __forceinline__ uint32_t pow2_bf2(int n) { return (uint32_t)max(n + 127, 0) * 0x00800080u; }
__device__ __forceinline__ int fexp(float x) { return (int)(__float_as_uint(x) >> 23) - 127; }
__device__ __forceinline__ void bulk_g2s(uint32_t dst, const void* src, uint32_t bytes, uint32_t bar) {
  asm volatile("cp.async.bulk.shared::cta.global.mbarrier::complete_tx::bytes [%0], [%1], %2, [%3];"
    :: "r"(dst), "l"(src), "r"(bytes), "r"(bar) : "memory");
}
__device__ __forceinline__ void wg_fence() { asm volatile("wgmma.fence.sync.aligned;" ::: "memory"); }
__device__ __forceinline__ void wg_commit() { asm volatile("wgmma.commit_group.sync.aligned;" ::: "memory"); }
template<int N> __device__ __forceinline__ void wg_wait() { asm volatile("wgmma.wait_group.sync.aligned %0;" :: "n"(N) : "memory"); }
__device__ __forceinline__ void bar_sync(int id, int cnt) { asm volatile("bar.sync %0, %1;" :: "r"(id), "r"(cnt) : "memory"); }
__device__ __forceinline__ void fence_async_smem() { asm volatile("fence.proxy.async.shared::cta;" ::: "memory"); }
__device__ __forceinline__ void fence_async_gmem() { asm volatile("fence.proxy.async.global;" ::: "memory"); }
__device__ __forceinline__ void bar_arrive(int id, int cnt) { asm volatile("bar.arrive %0, %1;" :: "r"(id), "r"(cnt) : "memory"); }
__device__ __forceinline__ void red_release(uint32_t* p) { asm volatile("red.release.gpu.global.add.u32 [%0], 1;" :: "l"(p) : "memory"); }
__device__ __forceinline__ void red_release_w(uint32_t* p) {
  __syncwarp();
  asm volatile("{\n.reg .pred q;\n.reg .b32 l;\nmov.u32 l, %%laneid;\nsetp.eq.u32 q, l, 0;\n@q fence.release.gpu;\n@q red.relaxed.gpu.global.add.u32 [%0], 1;\n}\n" :: "l"(p) : "memory");
}
__device__ __forceinline__ void mbar_wait_w(uint32_t bar, uint32_t parity) {
#pragma unroll 1
  for (uint32_t it = 0; it < (1u << 25); it++) if (__all_sync(0xffffffffu, mbar_try_wait(bar, parity))) break;
}
#define flag_release_w(f) red_release_w(g_flag + (f))
#define flag_wait_w(f, target) poll_acquire_w(g_flag + (f), target)
#define flag_release(f) red_release(g_flag + (f))
__device__ __forceinline__ uint32_t ld_relaxed(const uint32_t* p) {
  uint32_t v; asm volatile("ld.relaxed.gpu.global.u32 %0, [%1];" : "=r"(v) : "l"(p) : "memory"); return v;
}
#define flag_wait(f, target) poll_acquire(g_flag + (f), target)
__device__ __forceinline__ void poll_acquire(const uint32_t* p, uint32_t target) {
#pragma unroll 1
  for (uint32_t it = 0; it < (1u << 23); it++) if ((int)(ld_relaxed(p) - target) >= 0) break;
  asm volatile("fence.acquire.gpu;" ::: "memory");
}
__device__ __forceinline__ void poll_acquire_w(const uint32_t* p, uint32_t target) {
#pragma unroll 1
  for (uint32_t it = 0; it < (1u << 23); it++) {
    if (__all_sync(0xffffffffu, (int)(ld_relaxed(p) - target) >= 0)) break;
    if (BACKOFF) __nanosleep(BACKOFF);
  }
  asm volatile("fence.acquire.gpu;" ::: "memory");
}
template<int N> __device__ __forceinline__ void reg_fence(float (&d)[N]) {
#pragma unroll
  for (int i = 0; i < N; i++) asm volatile("" : "+f"(d[i]) :: "memory");
}
template<int N> __device__ __forceinline__ void reg_fence(uint32_t (&d)[N]) {
#pragma unroll
  for (int i = 0; i < N; i++) asm volatile("" : "+r"(d[i]) :: "memory");
}
__device__ __forceinline__ float ex2(float x) { float y; asm("ex2.approx.ftz.f32 %0, %1;" : "=f"(y) : "f"(x)); return y; }
__device__ __forceinline__ uint32_t pack_bf16(float lo, float hi) { uint32_t r; asm("cvt.rn.bf16x2.f32 %0, %1, %2;" : "=r"(r) : "f"(hi), "f"(lo)); return r; }
__device__ __forceinline__ float bf_lo(uint32_t w) { return __uint_as_float(w << 16); }
__device__ __forceinline__ float bf_hi(uint32_t w) { return __uint_as_float(w & 0xffff0000u); }
__device__ __forceinline__ uint64_t desc_k(uint32_t addr, uint32_t add) { return (uint64_t)((((addr & 0x3FFFF) >> 4) | (1u << 16)) + add) | (0x40000100ull << 32); }
__device__ __forceinline__ uint64_t desc_mn(uint32_t addr, uint32_t add) { return (uint64_t)((((addr & 0x3FFFF) >> 4) | ((1024u >> 4) << 16)) + add) | (0x40000100ull << 32); }
__device__ __forceinline__ void sts128(uint32_t a, uint4 v) { asm volatile("st.shared.v4.u32 [%0], {%1,%2,%3,%4};" :: "r"(a), "r"(v.x), "r"(v.y), "r"(v.z), "r"(v.w) : "memory"); }
__device__ __forceinline__ uint4 lds128(uint32_t a) { uint4 v; asm volatile("ld.shared.v4.u32 {%0,%1,%2,%3}, [%4];" : "=r"(v.x), "=r"(v.y), "=r"(v.z), "=r"(v.w) : "r"(a) : "memory"); return v; }
__device__ __forceinline__ void mma16816(float (&c)[4], uint32_t a0, uint32_t a1, uint32_t a2, uint32_t a3, uint32_t b0, uint32_t b1) {
  asm volatile("mma.sync.aligned.m16n8k16.row.col.f32.bf16.bf16.f32 {%0,%1,%2,%3}, {%4,%5,%6,%7}, {%8,%9}, {%0,%1,%2,%3};"
    : "+f"(c[0]), "+f"(c[1]), "+f"(c[2]), "+f"(c[3]) : "r"(a0), "r"(a1), "r"(a2), "r"(a3), "r"(b0), "r"(b1));
}
__device__ __forceinline__ uint32_t sw_byte(int r, int c) {
  return (uint32_t)((r >> 3) * 4096 + (c >> 6) * 1024 + (r & 7) * 128 + ((((c >> 3) & 7) ^ (r & 7)) << 4) + (c & 7) * 2);
}
#define STAMP(cond, who, i)
#define CSTAMP(cond, who, i)
#define DUMP(cond, who, i0, i1)

template <int OA, int OB> __device__ __forceinline__ void wgmma_ss_n256_tb(float (&d)[128], uint64_t da, uint64_t db, int scale_d) {
  asm volatile("{\n.reg .pred p;\n.reg .b64 a, b;\nsetp.ne.b32 p, %130, 0;\nadd.s64 a, %128, %131;\nadd.s64 b, %129, %132;\n"
    "wgmma.mma_async.sync.aligned.m64n256k16.f32.bf16.bf16 "
    "{%0, %1, %2, %3, %4, %5, %6, %7, %8, %9, %10, %11, %12, %13, %14, %15, %16, %17, %18, %19, %20, %21, %22, %23, %24, %25, %26, %27, %28, %29, %30, %31, %32, %33, %34, %35, %36, %37, %38, %39, %40, %41, %42, %43, %44, %45, %46, %47, %48, %49, %50, %51, %52, %53, %54, %55, %56, %57, %58, %59, %60, %61, %62, %63, %64, %65, %66, %67, %68, %69, %70, %71, %72, %73, %74, %75, %76, %77, %78, %79, %80, %81, %82, %83, %84, %85, %86, %87, %88, %89, %90, %91, %92, %93, %94, %95, %96, %97, %98, %99, %100, %101, %102, %103, %104, %105, %106, %107, %108, %109, %110, %111, %112, %113, %114, %115, %116, %117, %118, %119, %120, %121, %122, %123, %124, %125, %126, %127}, "
    "a, b, p, 1, 1, 0, 1;\n}\n"
    : "+f"(d[0]), "+f"(d[1]), "+f"(d[2]), "+f"(d[3]), "+f"(d[4]), "+f"(d[5]), "+f"(d[6]), "+f"(d[7]), "+f"(d[8]), "+f"(d[9]), "+f"(d[10]), "+f"(d[11]), "+f"(d[12]), "+f"(d[13]), "+f"(d[14]), "+f"(d[15]), "+f"(d[16]), "+f"(d[17]), "+f"(d[18]), "+f"(d[19]), "+f"(d[20]), "+f"(d[21]), "+f"(d[22]), "+f"(d[23]), "+f"(d[24]), "+f"(d[25]), "+f"(d[26]), "+f"(d[27]), "+f"(d[28]), "+f"(d[29]), "+f"(d[30]), "+f"(d[31]), "+f"(d[32]), "+f"(d[33]), "+f"(d[34]), "+f"(d[35]), "+f"(d[36]), "+f"(d[37]), "+f"(d[38]), "+f"(d[39]), "+f"(d[40]), "+f"(d[41]), "+f"(d[42]), "+f"(d[43]), "+f"(d[44]), "+f"(d[45]), "+f"(d[46]), "+f"(d[47]), "+f"(d[48]), "+f"(d[49]), "+f"(d[50]), "+f"(d[51]), "+f"(d[52]), "+f"(d[53]), "+f"(d[54]), "+f"(d[55]), "+f"(d[56]), "+f"(d[57]), "+f"(d[58]), "+f"(d[59]), "+f"(d[60]), "+f"(d[61]), "+f"(d[62]), "+f"(d[63]), "+f"(d[64]), "+f"(d[65]), "+f"(d[66]), "+f"(d[67]), "+f"(d[68]), "+f"(d[69]), "+f"(d[70]), "+f"(d[71]), "+f"(d[72]), "+f"(d[73]), "+f"(d[74]), "+f"(d[75]), "+f"(d[76]), "+f"(d[77]), "+f"(d[78]), "+f"(d[79]), "+f"(d[80]), "+f"(d[81]), "+f"(d[82]), "+f"(d[83]), "+f"(d[84]), "+f"(d[85]), "+f"(d[86]), "+f"(d[87]), "+f"(d[88]), "+f"(d[89]), "+f"(d[90]), "+f"(d[91]), "+f"(d[92]), "+f"(d[93]), "+f"(d[94]), "+f"(d[95]), "+f"(d[96]), "+f"(d[97]), "+f"(d[98]), "+f"(d[99]), "+f"(d[100]), "+f"(d[101]), "+f"(d[102]), "+f"(d[103]), "+f"(d[104]), "+f"(d[105]), "+f"(d[106]), "+f"(d[107]), "+f"(d[108]), "+f"(d[109]), "+f"(d[110]), "+f"(d[111]), "+f"(d[112]), "+f"(d[113]), "+f"(d[114]), "+f"(d[115]), "+f"(d[116]), "+f"(d[117]), "+f"(d[118]), "+f"(d[119]), "+f"(d[120]), "+f"(d[121]), "+f"(d[122]), "+f"(d[123]), "+f"(d[124]), "+f"(d[125]), "+f"(d[126]), "+f"(d[127])
    : "l"(da), "l"(db), "r"(scale_d), "n"(OA), "n"(OB));
}
template <int OA, int OB> __device__ __forceinline__ void wgmma_qk(float (&d)[64], uint64_t da, uint64_t db, int scale_d) {
  asm volatile("{\n.reg .pred p;\n.reg .b64 a, b;\nsetp.ne.b32 p, %66, 0;\nadd.s64 a, %64, %67;\nadd.s64 b, %65, %68;\n"
    "wgmma.mma_async.sync.aligned.m64n128k16.f32.bf16.bf16 "
    "{%0, %1, %2, %3, %4, %5, %6, %7, %8, %9, %10, %11, %12, %13, %14, %15, %16, %17, %18, %19, %20, %21, %22, %23, %24, %25, %26, %27, %28, %29, %30, %31, %32, %33, %34, %35, %36, %37, %38, %39, %40, %41, %42, %43, %44, %45, %46, %47, %48, %49, %50, %51, %52, %53, %54, %55, %56, %57, %58, %59, %60, %61, %62, %63}, "
    "a, b, p, 1, 1, 0, 0;\n}\n"
    : "+f"(d[0]), "+f"(d[1]), "+f"(d[2]), "+f"(d[3]), "+f"(d[4]), "+f"(d[5]), "+f"(d[6]), "+f"(d[7]), "+f"(d[8]), "+f"(d[9]), "+f"(d[10]), "+f"(d[11]), "+f"(d[12]), "+f"(d[13]), "+f"(d[14]), "+f"(d[15]), "+f"(d[16]), "+f"(d[17]), "+f"(d[18]), "+f"(d[19]), "+f"(d[20]), "+f"(d[21]), "+f"(d[22]), "+f"(d[23]), "+f"(d[24]), "+f"(d[25]), "+f"(d[26]), "+f"(d[27]), "+f"(d[28]), "+f"(d[29]), "+f"(d[30]), "+f"(d[31]), "+f"(d[32]), "+f"(d[33]), "+f"(d[34]), "+f"(d[35]), "+f"(d[36]), "+f"(d[37]), "+f"(d[38]), "+f"(d[39]), "+f"(d[40]), "+f"(d[41]), "+f"(d[42]), "+f"(d[43]), "+f"(d[44]), "+f"(d[45]), "+f"(d[46]), "+f"(d[47]), "+f"(d[48]), "+f"(d[49]), "+f"(d[50]), "+f"(d[51]), "+f"(d[52]), "+f"(d[53]), "+f"(d[54]), "+f"(d[55]), "+f"(d[56]), "+f"(d[57]), "+f"(d[58]), "+f"(d[59]), "+f"(d[60]), "+f"(d[61]), "+f"(d[62]), "+f"(d[63])
    : "l"(da), "l"(db), "r"(scale_d), "n"(OA), "n"(OB));
}
template <int OA, int OB> __device__ __forceinline__ void wgmma_qk(float (&d)[56], uint64_t da, uint64_t db, int scale_d) {
  asm volatile("{\n.reg .pred p;\n.reg .b64 a, b;\nsetp.ne.b32 p, %58, 0;\nadd.s64 a, %56, %59;\nadd.s64 b, %57, %60;\n"
    "wgmma.mma_async.sync.aligned.m64n112k16.f32.bf16.bf16 "
    "{%0, %1, %2, %3, %4, %5, %6, %7, %8, %9, %10, %11, %12, %13, %14, %15, %16, %17, %18, %19, %20, %21, %22, %23, %24, %25, %26, %27, %28, %29, %30, %31, %32, %33, %34, %35, %36, %37, %38, %39, %40, %41, %42, %43, %44, %45, %46, %47, %48, %49, %50, %51, %52, %53, %54, %55}, "
    "a, b, p, 1, 1, 0, 0;\n}\n"
    : "+f"(d[0]), "+f"(d[1]), "+f"(d[2]), "+f"(d[3]), "+f"(d[4]), "+f"(d[5]), "+f"(d[6]), "+f"(d[7]), "+f"(d[8]), "+f"(d[9]), "+f"(d[10]), "+f"(d[11]), "+f"(d[12]), "+f"(d[13]), "+f"(d[14]), "+f"(d[15]), "+f"(d[16]), "+f"(d[17]), "+f"(d[18]), "+f"(d[19]), "+f"(d[20]), "+f"(d[21]), "+f"(d[22]), "+f"(d[23]), "+f"(d[24]), "+f"(d[25]), "+f"(d[26]), "+f"(d[27]), "+f"(d[28]), "+f"(d[29]), "+f"(d[30]), "+f"(d[31]), "+f"(d[32]), "+f"(d[33]), "+f"(d[34]), "+f"(d[35]), "+f"(d[36]), "+f"(d[37]), "+f"(d[38]), "+f"(d[39]), "+f"(d[40]), "+f"(d[41]), "+f"(d[42]), "+f"(d[43]), "+f"(d[44]), "+f"(d[45]), "+f"(d[46]), "+f"(d[47]), "+f"(d[48]), "+f"(d[49]), "+f"(d[50]), "+f"(d[51]), "+f"(d[52]), "+f"(d[53]), "+f"(d[54]), "+f"(d[55])
    : "l"(da), "l"(db), "r"(scale_d), "n"(OA), "n"(OB));
}
template <int OB> __device__ __forceinline__ void wgmma_rs_n256_tb(float (&d)[128], uint32_t a0, uint32_t a1, uint32_t a2, uint32_t a3, uint64_t db, int scale_d) {
  asm volatile("{\n.reg .pred p;\n.reg .b64 b;\nsetp.ne.b32 p, %133, 0;\nadd.s64 b, %132, %134;\n"
    "wgmma.mma_async.sync.aligned.m64n256k16.f32.bf16.bf16 "
    "{%0, %1, %2, %3, %4, %5, %6, %7, %8, %9, %10, %11, %12, %13, %14, %15, %16, %17, %18, %19, %20, %21, %22, %23, %24, %25, %26, %27, %28, %29, %30, %31, %32, %33, %34, %35, %36, %37, %38, %39, %40, %41, %42, %43, %44, %45, %46, %47, %48, %49, %50, %51, %52, %53, %54, %55, %56, %57, %58, %59, %60, %61, %62, %63, %64, %65, %66, %67, %68, %69, %70, %71, %72, %73, %74, %75, %76, %77, %78, %79, %80, %81, %82, %83, %84, %85, %86, %87, %88, %89, %90, %91, %92, %93, %94, %95, %96, %97, %98, %99, %100, %101, %102, %103, %104, %105, %106, %107, %108, %109, %110, %111, %112, %113, %114, %115, %116, %117, %118, %119, %120, %121, %122, %123, %124, %125, %126, %127}, "
    "{%128, %129, %130, %131}, b, p, 1, 1, 1;\n}\n"
    : "+f"(d[0]), "+f"(d[1]), "+f"(d[2]), "+f"(d[3]), "+f"(d[4]), "+f"(d[5]), "+f"(d[6]), "+f"(d[7]), "+f"(d[8]), "+f"(d[9]), "+f"(d[10]), "+f"(d[11]), "+f"(d[12]), "+f"(d[13]), "+f"(d[14]), "+f"(d[15]), "+f"(d[16]), "+f"(d[17]), "+f"(d[18]), "+f"(d[19]), "+f"(d[20]), "+f"(d[21]), "+f"(d[22]), "+f"(d[23]), "+f"(d[24]), "+f"(d[25]), "+f"(d[26]), "+f"(d[27]), "+f"(d[28]), "+f"(d[29]), "+f"(d[30]), "+f"(d[31]), "+f"(d[32]), "+f"(d[33]), "+f"(d[34]), "+f"(d[35]), "+f"(d[36]), "+f"(d[37]), "+f"(d[38]), "+f"(d[39]), "+f"(d[40]), "+f"(d[41]), "+f"(d[42]), "+f"(d[43]), "+f"(d[44]), "+f"(d[45]), "+f"(d[46]), "+f"(d[47]), "+f"(d[48]), "+f"(d[49]), "+f"(d[50]), "+f"(d[51]), "+f"(d[52]), "+f"(d[53]), "+f"(d[54]), "+f"(d[55]), "+f"(d[56]), "+f"(d[57]), "+f"(d[58]), "+f"(d[59]), "+f"(d[60]), "+f"(d[61]), "+f"(d[62]), "+f"(d[63]), "+f"(d[64]), "+f"(d[65]), "+f"(d[66]), "+f"(d[67]), "+f"(d[68]), "+f"(d[69]), "+f"(d[70]), "+f"(d[71]), "+f"(d[72]), "+f"(d[73]), "+f"(d[74]), "+f"(d[75]), "+f"(d[76]), "+f"(d[77]), "+f"(d[78]), "+f"(d[79]), "+f"(d[80]), "+f"(d[81]), "+f"(d[82]), "+f"(d[83]), "+f"(d[84]), "+f"(d[85]), "+f"(d[86]), "+f"(d[87]), "+f"(d[88]), "+f"(d[89]), "+f"(d[90]), "+f"(d[91]), "+f"(d[92]), "+f"(d[93]), "+f"(d[94]), "+f"(d[95]), "+f"(d[96]), "+f"(d[97]), "+f"(d[98]), "+f"(d[99]), "+f"(d[100]), "+f"(d[101]), "+f"(d[102]), "+f"(d[103]), "+f"(d[104]), "+f"(d[105]), "+f"(d[106]), "+f"(d[107]), "+f"(d[108]), "+f"(d[109]), "+f"(d[110]), "+f"(d[111]), "+f"(d[112]), "+f"(d[113]), "+f"(d[114]), "+f"(d[115]), "+f"(d[116]), "+f"(d[117]), "+f"(d[118]), "+f"(d[119]), "+f"(d[120]), "+f"(d[121]), "+f"(d[122]), "+f"(d[123]), "+f"(d[124]), "+f"(d[125]), "+f"(d[126]), "+f"(d[127])
    : "r"(a0), "r"(a1), "r"(a2), "r"(a3), "l"(db), "r"(scale_d), "n"(OB));
}
template <int OB> __device__ __forceinline__ void wgmma_rs_n128_tb(float (&d)[64], uint32_t a0, uint32_t a1, uint32_t a2, uint32_t a3, uint64_t db, int scale_d) {
  asm volatile("{\n.reg .pred p;\n.reg .b64 b;\nsetp.ne.b32 p, %69, 0;\nadd.s64 b, %68, %70;\n"
    "wgmma.mma_async.sync.aligned.m64n128k16.f32.bf16.bf16 "
    "{%0, %1, %2, %3, %4, %5, %6, %7, %8, %9, %10, %11, %12, %13, %14, %15, %16, %17, %18, %19, %20, %21, %22, %23, %24, %25, %26, %27, %28, %29, %30, %31, %32, %33, %34, %35, %36, %37, %38, %39, %40, %41, %42, %43, %44, %45, %46, %47, %48, %49, %50, %51, %52, %53, %54, %55, %56, %57, %58, %59, %60, %61, %62, %63}, "
    "{%64, %65, %66, %67}, b, p, 1, 1, 1;\n}\n"
    : "+f"(d[0]), "+f"(d[1]), "+f"(d[2]), "+f"(d[3]), "+f"(d[4]), "+f"(d[5]), "+f"(d[6]), "+f"(d[7]), "+f"(d[8]), "+f"(d[9]), "+f"(d[10]), "+f"(d[11]), "+f"(d[12]), "+f"(d[13]), "+f"(d[14]), "+f"(d[15]), "+f"(d[16]), "+f"(d[17]), "+f"(d[18]), "+f"(d[19]), "+f"(d[20]), "+f"(d[21]), "+f"(d[22]), "+f"(d[23]), "+f"(d[24]), "+f"(d[25]), "+f"(d[26]), "+f"(d[27]), "+f"(d[28]), "+f"(d[29]), "+f"(d[30]), "+f"(d[31]), "+f"(d[32]), "+f"(d[33]), "+f"(d[34]), "+f"(d[35]), "+f"(d[36]), "+f"(d[37]), "+f"(d[38]), "+f"(d[39]), "+f"(d[40]), "+f"(d[41]), "+f"(d[42]), "+f"(d[43]), "+f"(d[44]), "+f"(d[45]), "+f"(d[46]), "+f"(d[47]), "+f"(d[48]), "+f"(d[49]), "+f"(d[50]), "+f"(d[51]), "+f"(d[52]), "+f"(d[53]), "+f"(d[54]), "+f"(d[55]), "+f"(d[56]), "+f"(d[57]), "+f"(d[58]), "+f"(d[59]), "+f"(d[60]), "+f"(d[61]), "+f"(d[62]), "+f"(d[63])
    : "r"(a0), "r"(a1), "r"(a2), "r"(a3), "l"(db), "r"(scale_d), "n"(OB));
}
template <int V> using IC = std::integral_constant<int, V>;
template <int I, int N, class F> __device__ __forceinline__ void static_for(F&& f) {
  if constexpr (I < N) { f(std::integral_constant<int, I>{}); static_for<I + 1, N>(f); }
}

constexpr uint32_t SM_Q = 0, SM_BAR = 7 * 32768;
constexpr uint32_t B_FULL = SM_BAR, B_EMPTY = B_FULL + 24, B_WF = B_EMPTY + 24, B_QFULL = B_WF + 32, B_QEMPTY = B_QFULL + 16,
                   B_EVH = B_QEMPTY + 16, B_EVQ = B_EVH + 8, B_EVP0 = B_EVQ + 8, B_HR0 = B_EVP0 + 32, B_M0 = B_HR0 + 16, B_HALF = B_M0 + 8,
                   B_SPF = B_HALF + 8, B_EVS = B_SPF + 8, SM_UNSAFE = B_EVS + 8, SM_TS = SM_UNSAFE + 8, SM_ML = (SM_TS + 192 + 15) / 16 * 16, SM_EPOCH = SM_ML + 1024, SM_END = SM_EPOCH + 16;
constexpr uint32_t POS_M = 0x5462;
constexpr int SMEM_BYTES = SM_END;

#define ROW0(u) make_uint4(pack_bf16(o[16 * u], o[16 * u + 1]), pack_bf16(o[16 * u + 4], o[16 * u + 5]), \
                           pack_bf16(o[16 * u + 8], o[16 * u + 9]), pack_bf16(o[16 * u + 12], o[16 * u + 13]))
#define ROW1(u) make_uint4(pack_bf16(o[16 * u + 2], o[16 * u + 3]), pack_bf16(o[16 * u + 6], o[16 * u + 7]), \
                           pack_bf16(o[16 * u + 10], o[16 * u + 11]), pack_bf16(o[16 * u + 14], o[16 * u + 15]))

__global__ void __launch_bounds__(384, 1) gps_kernel(const __grid_constant__ Params P) {
  extern __shared__ __align__(1024) uint8_t smem_raw[];
  constexpr uint32_t sb = 1024;
  if (smem_u32(smem_raw) != sb) return;
  const int cta = blockIdx.x;
  const int wg = __shfl_sync(0xffffffffu, (int)threadIdx.x >> 7, 0);
  const int warp = __shfl_sync(0xffffffffu, ((int)threadIdx.x >> 5) & 3, 0);
  const int lane = threadIdx.x & 31;
  const Work& W = P.w[cta];
  const int n0 = W.nb0 + W.na0, n1 = W.nb1 + W.na1, total = n0 + n1;
  const bool fin = W.role & R_FIN, tail = W.role & R_TAIL;
  const uint32_t posw = total == 0 || tail ? POS_M : ((total & 1) ? 0x2546 : 0x4326);
  if (wg == 2) {
    STAMP(lane == 0 && warp == 0, 2, 0);
    const int g = lane >> 2, t = lane & 3;
        const int mi = cta >> 3;
    const uint32_t sW = sb + 3 * 32768;
    uint4 wa[4], wb[8];
    {
      const uint4* pq = (const uint4*)(P.wq + ((mi & 15) * 16 + g) * 256) + warp * 8 + t;
      const uint4* pk = (const uint4*)(P.wk + ((cta & 7) * 32 + g) * 256) + warp * 8 + t;
#pragma unroll
      for (int i = 0; i < 4; i++) wa[i] = __ldg(pq + (i >> 1) * 256 + (i & 1) * 4);
#pragma unroll
      for (int i = 0; i < 8; i++) wb[i] = __ldg(pk + (i >> 1) * 256 + (i & 1) * 4);
    }
    bar_sync(4, 384);
    {
#pragma unroll
      for (int n = 0; n < 4; n++) {
        float c[4] = {0.f, 0.f, 0.f, 0.f};
#pragma unroll
        for (int u = 0; u < 2; u++) {
          mma16816(c, wa[u].x, wa[2 + u].x, wa[u].y, wa[2 + u].y, wb[2 * n + u].x, wb[2 * n + u].y);
          mma16816(c, wa[u].z, wa[2 + u].z, wa[u].w, wa[2 + u].w, wb[2 * n + u].z, wb[2 * n + u].w);
        }
        asm volatile("st.shared.v2.f32 [%0], {%1,%2};" :: "r"(sW + ((warp * 16 + g) * 40 + n * 8 + 2 * t) * 4), "f"(c[0]), "f"(c[1]) : "memory");
        asm volatile("st.shared.v2.f32 [%0], {%1,%2};" :: "r"(sW + ((warp * 16 + g + 8) * 40 + n * 8 + 2 * t) * 4), "f"(c[2]), "f"(c[3]) : "memory");
      }
      STAMP(lane == 0 && warp == 0, 2, 7);
      bar_sync(3, 128);
      if (warp < 2) {
        float c[8] = {0.f, 0.f, 0.f, 0.f, 0.f, 0.f, 0.f, 0.f};
#pragma unroll
        for (int k = 0; k < 4; k++) {
          const uint4 v = lds128(sW + ((k * 16 + warp * 8 + g) * 40 + t * 8) * 4), w = lds128(sW + ((k * 16 + warp * 8 + g) * 40 + t * 8 + 4) * 4);
          c[0] += __uint_as_float(v.x); c[1] += __uint_as_float(v.y); c[2] += __uint_as_float(v.z); c[3] += __uint_as_float(v.w);
          c[4] += __uint_as_float(w.x); c[5] += __uint_as_float(w.y); c[6] += __uint_as_float(w.z); c[7] += __uint_as_float(w.w);
        }
        const float ms = 1.4426950408889634f / 16.0f;
        if (cta < 128)
          *(uint4*)((uint8_t*)g_M + sw_byte(mi * 16 + warp * 8 + g, (cta & 7) * 32 + t * 8)) =
              make_uint4(pack_bf16(c[0] * ms, c[1] * ms), pack_bf16(c[2] * ms, c[3] * ms), pack_bf16(c[4] * ms, c[5] * ms), pack_bf16(c[6] * ms, c[7] * ms));
      }
    }
    asm volatile("setmaxnreg.dec.sync.aligned.u32 %0;" :: "n"(504 - 2 * CREG));
    STAMP(lane == 0 && warp == 0, 2, 13);
    bar_sync(3, 128);
#define ep1 (lds32(sb + SM_EPOCH) + 1)
    const int gw = cta * 3 + warp - 1;
    if (threadIdx.x == 256 && cta < 128) flag_release(F_M + (cta >> 5));
    __syncwarp();
    if (warp == 0) {
      if (lane == 0) {
        STAMP(true, 2, 1);
        const uint32_t epoch = ld_relaxed(g_flag + F_EPOCH);
        if (total > 0) {
#pragma unroll
          for (int c = 0; c < 3; c++) mbar_expect_tx(sb + B_WF + 8 * c, c == 0 ? WCH_B - 8192 : WCH_B);
          mbar_expect_tx(sb + B_M0, 8192);
          int c = 0;
#pragma unroll 1
          for (uint32_t it = 0; c < 4; it++) {
            uint4 f;
            asm volatile("ld.relaxed.gpu.global.v4.u32 {%0,%1,%2,%3}, [%4];" : "=r"(f.x), "=r"(f.y), "=r"(f.z), "=r"(f.w) : "l"(g_flag + F_M) : "memory");
            uint32_t tm;
            asm volatile("mad.lo.u32 %0, %1, 32, 32;" : "=r"(tm) : "r"(epoch));
            int ok = (int)(f.x - tm) < 0 ? 0 : (int)(f.y - tm) < 0 ? 1 : (int)(f.z - tm) < 0 ? 2 : (int)(f.w - tm) < 0 ? 3 : 4;
            if (it > (1u << 23)) ok = 4;
            if (ok > c) {
              asm volatile("fence.acquire.gpu;" ::: "memory"); fence_async_gmem();
              if (c == 0) bulk_g2s(sb + (POS_M & 15) * 32768, g_M, 8192, sb + B_M0);
            }
#pragma unroll 1
            for (; c < ok; c++) {
              const uint32_t skip = c == 0 ? 8192 : 0;
              bulk_g2s(sb + ((POS_M >> c * 4) & 15) * 32768 + skip, pofs<const uint8_t>(g_M, c * WCH_B + skip), WCH_B - skip, sb + B_WF + 8 * c);
              STAMP(c == 0, 2, 2);
            }
          }
        }
        asm volatile("st.shared.u32 [%0], %1;" :: "r"(sb + SM_EPOCH), "r"(epoch) : "memory");
        if (total > 0) mbar_expect_tx(sb + B_WF + 24, WCH_B);
        int st = 0, ph = 0, qph = 0;
        const int nsl = tail ? 3 : 2;
        auto next_slot = [&]() { mbar_wait(sb + B_EMPTY + 8 * st, ph); if (++st == nsl) { st = 0; ph ^= 1; } };
        auto w_load = [&](int c0, int c1) {
#pragma unroll 1
          for (int c = c0; c < c1; c++) {
            mbar_expect_tx(sb + B_WF + 8 * c, WCH_B);
            bulk_g2s(sb + ((posw >> c * 4) & 15) * 32768, pofs<const uint8_t>(fin ? g_Wvo : g_Wmo, c * WCH_B), WCH_B, sb + B_WF + 8 * c);
          }
        };
        auto q_load = [&](const uint4* src, bool wait_empty) {
#pragma unroll 1
          for (int h = 0; h < 2; h++) {
            if (wait_empty) mbar_wait(sb + B_QEMPTY + 8 * h, qph);
            mbar_expect_tx(sb + B_QFULL + 8 * h, 32768);
            bulk_g2s(sb + SM_Q + h * 32768, src + h * 2048, 32768, sb + B_QFULL + 8 * h);
          }
          if (wait_empty) qph ^= 1;
        };
        if (total > 0) {
          STAMP(true, 2, 3);
          flag_wait(F_H, ep1 * NHSIG); fence_async_gmem();
          STAMP(true, 2, 4);
          uint32_t ko = W.k0 * 8192;
#pragma unroll 1
          for (int j = 0; j < total; j++) {
            if (j == n0) {
              flag_wait(F_QP + W.q1 * LN_, ep1); fence_async_gmem();
              const uint32_t u = __ldcg(g_unsafe + W.q1);
              asm volatile("st.shared.u32 [%0], %1;" :: "r"(sb + SM_UNSAFE), "r"(u) : "memory");
              ko = W.k1 * 8192;
            }
            if (j == n0 + 1) q_load(g_qp + W.q1 * 4096, true);
            if (j == n0 + 2) { bulk_wait_read(); mbar_arrive(sb + B_SPF); }
            if (j == n0 + 1 || j == n0 + 2) {
              mbar_wait(sb + B_EVP0 + 8 * (j - n0 - 1), 0);
              bulk_s2g(pofs<uint4>(g_part, W.slotA * 65536 + (j - n0 - 1) * 32768), sb + 6 * 32768, 32768);
              bulk_commit();
            }
            if (j == n0 + 3) { bulk_wait_all(); mbar_arrive(sb + B_EVS); }
            if (j == total - 1) { flag_wait(F_W, ep1); fence_async_gmem(); if (!tail) w_load(0, 1); }
            const uint32_t bytes = (j < n0 ? j < W.nb0 : j - n0 < W.nb1) ? 112 * 512 : 128 * 512, s0 = st;
            next_slot();
            mbar_expect_tx(sb + B_FULL + 8 * s0, bytes);
            bulk_g2s(sb + ((tail ? 1 : 2) + 2 * s0) * 32768, pofs<const uint8_t>(g_h, ko), bytes, sb + B_FULL + 8 * s0);
            ko += bytes;
          }
          next_slot();
          if (tail) { next_slot(); next_slot(); }
        } else { flag_wait(F_W, ep1); fence_async_gmem(); }
        STAMP(true, 2, 5);
        const bool staged = total > 0 && !tail;
        w_load(staged, staged ? 3 : 4);
#pragma unroll 1
        for (int i = 0; i < W.nloc; i++) {
          const int tl = W.loc0 + i, last = tl * 128 + 127 < NN ? tl * 128 + 127 : NN - 1;
          flag_wait(F_AGG + ((last >= NGW) + (last >= 4 * NGW) + (last >= 9 * NGW)) * LN_, ep1 * NGW); fence_async_gmem();
          if (total == 0) g_flag[F_EPOCH] = epoch + 1;
          q_load(g_agg + tl * 4096, total > 0 || i > 0);
        }
        if (staged) { mbar_wait(sb + B_HALF, 0); if (!fin) mbar_wait(sb + B_HR0, 0); w_load(3, 4); }
        DUMP(true, 2, 0, 8);
      }
    } else {
      if (warp == 3 && W.own) { mbar_wait_w(sb + B_EVH, 0); flag_release_w(F_H); STAMP(lane == 0, 2, 6); }
      bool early = warp == 1 && n1 > 0;
      if (total > 0) {
        mbar_wait_w(sb + B_EVQ, 0);
        const uint32_t c0 = clk();
        if (warp == 1 && (W.role & R_PUB)) {
          g_unsafe[W.q0] = lds32(sb + SM_UNSAFE);
#pragma unroll 1
          for (int k = 0; k < 4; k++) {
            __nanosleep(2000);
            if (lane == 0) bulk_s2g(pofs<uint4>(g_qp, W.q0 * 65536 + k * 16384), sb + SM_Q + k * 16384, 16384);
            bulk_commit();
          }
          bulk_wait_all();
          flag_release_w(F_QP + W.q0 * LN_);
        }
        while (__any_sync(0xffffffffu, clk() - c0 < GSTART)) __nanosleep(500);
        STAMP(lane == 0 && warp == 1, 2, 8);
#define ovf_cnt pofs<uint32_t>(g_flag, (F_OVF + (ep1 & 1) * LN_) * 4)
        if (gw == 0) g_flag[F_OVF + ((ep1 + 1) & 1) * LN_] = 0;
#pragma unroll 1
        for (int e0 = gw * 32; e0 < NE; e0 += NGW * 32 * 7) {
          int d[7], s[7], pos[7];
          const int* pd = pofs<const int>(P.dst, (e0 + lane) * 4);
          const int* ps = pofs<const int>(P.src, (e0 + lane) * 4);
#pragma unroll
          for (int k = 0; k < 7; k++) { const bool ok = e0 + k * NGW * 32 < NE; d[k] = ok ? __ldg(pd + k * NGW * 32) : -1; s[k] = ok ? __ldg(ps + k * NGW * 32) : 0; }
          uint32_t ov = 0;
#pragma unroll
          for (int k = 0; k < 7; k++) {
            pos[k] = 0;
            if (d[k] >= 0) asm volatile("atom.relaxed.gpu.global.add.u32 %0, [%1], 1;" : "=r"(pos[k]) : "l"(pofs<int>(g_cnt, d[k] << 2)) : "memory");
            s[k] = (uint32_t)(uintptr_t)g_h + (s[k] >> 3) * 4096 + (s[k] & 7) * 144;
            if (d[k] >= 0 && pos[k] < CAP) asm volatile("st.volatile.global.u32 [%0], %1;" :: "l"(pofs<int>(g_bin, (d[k] * CAPS + pos[k]) << 2)), "r"(s[k]) : "memory");
            ov |= (pos[k] >= CAP) << k;
          }
          if (__any_sync(0xffffffffu, ov != 0)) {
            uint32_t at;
            asm volatile("atom.relaxed.gpu.global.add.u32 %0, [%1], %2;" : "=r"(at) : "l"(ovf_cnt), "r"(__popc(ov)) : "memory");
#pragma unroll
            for (int k = 0; k < 7; k++) if ((ov >> k) & 1) g_ovf[at++] = make_int2(d[k], s[k]);
          }
        }
        flag_release_w(F_BIN);
        STAMP(lane == 0 && warp == 1, 2, 9);
        flag_wait_w(F_H, ep1 * NHSIG);
        flag_wait_w(F_BIN, ep1 * NGW);
        STAMP(lane == 0 && warp == 1, 2, 10);
        const uint32_t lx = ((lane & 7) << 4) | ((lane >> 3) << 10);
        const int myn = gw + lane * NGW < NN ? gw + lane * NGW : gw;
        int cnts = __ldcg(g_cnt + myn);
        cnts = (cnts > CAP ? CAP + 1 : cnts) | ((int)__ldg((const unsigned short*)P.dinv + myn) << 16);
        __syncwarp();
        g_cnt[myn] = 0;
        const uint32_t hhi = (uintptr_t)g_h >> 32;
        uint32_t obin = gw * CAPS * 4;
        uint4 q = *pofs<const uint4>(g_bin, obin), q2 = *pofs<const uint4>(g_bin, obin + 16);
        int sig = 0, nsig = 0;
#pragma unroll 1
        for (int rnd = 0; rnd < NRND; rnd++) {
          const int n = gw + rnd * NGW;
          if (n < NN) {
            const int cd = __shfl_sync(0xffffffffu, cnts, rnd);
            const int cb = (cd & 0xffff) > CAP ? CAP : (cd & 0xffff);
            float acc[8];
#pragma unroll
            for (int k = 0; k < 8; k++) acc[k] = 0.f;
            auto add_row = [&](uint4 v) {
              acc[0] += bf_lo(v.x); acc[1] += bf_hi(v.x); acc[2] += bf_lo(v.y); acc[3] += bf_hi(v.y);
              acc[4] += bf_lo(v.z); acc[5] += bf_hi(v.z); acc[6] += bf_lo(v.w); acc[7] += bf_hi(v.w);
            };
#define ROW(w) ldcg_v(addr64((w) ^ lx, hhi))
            int e = 8;
#pragma unroll 1
            for (; e <= cb; e += 8) {
              const uint4 v0 = ROW(q.x), v1 = ROW(q.y), v2 = ROW(q.z), v3 = ROW(q.w), v4 = ROW(q2.x), v5 = ROW(q2.y), v6 = ROW(q2.z), v7 = ROW(q2.w);
              const uint4* pq = pofs<const uint4>(g_bin, obin + e * 4);
              q = pq[0]; q2 = pq[1];
              add_row(v7); add_row(v6); add_row(v5); add_row(v4); add_row(v3); add_row(v2); add_row(v1); add_row(v0);
            }
            if (cb & 4) {
              const uint4 v0 = ROW(q.x), v1 = ROW(q.y), v2 = ROW(q.z), v3 = ROW(q.w);
              add_row(v3); add_row(v2); add_row(v1); add_row(v0);
              q = q2;
            }
            {
              uint4 v0, v1, v2;
              const int m = cb & 3;
              if (m > 0) v0 = ROW(q.x);
              if (m > 1) v1 = ROW(q.y);
              if (m > 2) v2 = ROW(q.z);
              const uint4 xrow = ldcg_v(pofs<const uint4>(P.x, n * 512 + lane * 16));
              const uint4* pq = pofs<const uint4>(g_bin, obin + NGW * CAPS * 4);
              q = pq[0]; q2 = pq[1];
              *pofs<uint4>(P.out, n * 512 + lane * 16) = xrow;
              if (m > 2) add_row(v2);
              if (m > 1) add_row(v1);
              if (m > 0) add_row(v0);
            }
            if ((cd & 0xffff) > CAP) {
              const int no = __shfl_sync(0xffffffffu, (int)ld_relaxed(ovf_cnt), 0);
#pragma unroll 1
              for (int i0 = 0; i0 < no; i0 += 32) {
                int2 en = __ldcg(g_ovf + min(i0 + lane, no - 1));
                uint32_t mk = __ballot_sync(0xffffffffu, en.x == n && i0 + lane < no);
#pragma unroll 1
                while (mk) {
                  const int bit = __ffs(mk) - 1; mk &= mk - 1;
                  add_row(ldcg_v(addr64((uint32_t)__shfl_sync(0xffffffffu, en.y, bit) ^ lx, hhi)));
                }
              }
            }
            const float di = __uint_as_float(cd & 0xffff0000u);
            *pofs<uint4>(g_agg, ((n >> 3) * 4096 + (n & 7) * 144) ^ lx) =
                make_uint4(pack_bf16(acc[0] * di, acc[1] * di), pack_bf16(acc[2] * di, acc[3] * di),
                           pack_bf16(acc[4] * di, acc[5] * di), pack_bf16(acc[6] * di, acc[7] * di));
            obin += NGW * CAPS * 4;
          }
          if (early && __all_sync(0xffffffffu, mbar_try_wait_nb(sb + B_EVS, 0))) { flag_release_w(F_PART + 2 * W.slotA * LN_); early = false; }
          if (rnd == sig) {
            flag_release_w(F_AGG + nsig * LN_);
            nsig++;
            sig = nsig == 1 ? 3 : (nsig == 2 ? 8 : NRND - 1);
          }
        }
      }
      STAMP(lane == 0 && warp == 1, 2, 11);
      if (fin && W.slotB >= 0) {
#pragma unroll 1
        for (int k = 0; k < 2; k++) flag_wait_w(F_PART + 2 * (k ? W.slotB : W.slotA) * LN_, ep1);
#pragma unroll 1
        for (int b = warp - 1; b < 8; b += 3) {
          float2* ma = g_ml + W.slotA * 128 + b * 16 + g;
          const float2* mb = g_ml + W.slotB * 128 + b * 16 + g;
          const float2 a0 = __ldcg(ma), a1 = __ldcg(ma + 8), b0 = __ldcg(mb), b1 = __ldcg(mb + 8);
          const float x0 = fmaxf(a0.x, b0.x), x1 = fmaxf(a1.x, b1.x);
          const float fa0 = ex2(a0.x - x0), fa1 = ex2(a1.x - x1), fb0 = ex2(b0.x - x0), fb1 = ex2(b1.x - x1);
          __syncwarp();
          if (t == 0) { ma[0] = make_float2(x0, a0.y * fa0 + b0.y * fb0); ma[8] = make_float2(x1, a1.y * fa1 + b1.y * fb1); }
          const uint32_t ofs = ((b >> 2) * 2048 + (b & 3) * 32 + lane) * 16;
#pragma unroll 1
          for (int u = 0; u < 16; u += 4) {
            uint4* pa = pofs<uint4>(g_part, W.slotA * 65536 + ofs + u * 2048);
            const uint4* pb = pofs<const uint4>(g_part, W.slotB * 65536 + ofs + u * 2048);
            uint4 va[4], vb[4];
#pragma unroll
            for (int k = 0; k < 4; k++) { va[k] = ldcg_v(pa + k * 128); vb[k] = ldcg_v(pb + k * 128); }
#define FOLD(w, fa, fb) pack_bf16(bf_lo(va[k].w) * fa + bf_lo(vb[k].w) * fb, bf_hi(va[k].w) * fa + bf_hi(vb[k].w) * fb)
#pragma unroll
            for (int k = 3; k >= 0; k--) pa[k * 128] = make_uint4(FOLD(x, fa0, fb0), FOLD(y, fa1, fb1), FOLD(z, fa0, fb0), FOLD(w, fa1, fb1));
          }
        }
        bar_sync(3, 96);
        if (warp == 1) asm volatile("fence.acq_rel.gpu;" ::: "memory");
      }
      if (warp == 1 && fin) flag_wait_w(F_AGG + (NAGG - 1) * LN_, ep1 * NGW);
      if (warp == 1 && lane == 0) {
        if (tail) {
          mbar_wait(sb + B_EVP0 + 24, 0);
          asm volatile("fence.acq_rel.gpu;" ::: "memory"); fence_async_gmem();
          mbar_wait(sb + B_QEMPTY, 0);
          mbar_expect_tx(sb + B_QFULL, 32768 + 512);
          bulk_g2s(sb + SM_ML, g_ml + W.slotA * 128 + 64, 512, sb + B_QFULL);
          bulk_g2s(sb + SM_Q, g_part + W.slotA * 4096 + 2048, 32768, sb + B_QFULL);
        } else if (fin) {
#pragma unroll 1
          for (int h = 0; h < 2; h++) {
            if (W.slotB < 0) flag_wait(F_PART + (2 * W.slotA + h) * LN_, ep1);
            fence_async_gmem();
            STAMP(true, 2, 14 + h);
            mbar_wait(sb + B_QEMPTY + 8 * h, 0);
            mbar_expect_tx(sb + B_QFULL + 8 * h, 32768 + 512);
            bulk_g2s(sb + SM_ML + h * 512, g_ml + W.slotA * 128 + h * 64, 512, sb + B_QFULL + 8 * h);
            bulk_g2s(sb + SM_Q + h * 32768, g_part + W.slotA * 4096 + h * 2048, 32768, sb + B_QFULL + 8 * h);
          }
        } else if (total > 0) {
#pragma unroll 1
          for (int k = early ? 1 : 2; k < 4; k++) {
            mbar_wait(k < 2 ? sb + B_EVS : sb + B_EVP0 + 8 * k, 0);
            flag_release(F_PART + (2 * W.slotA + (k < 2 ? 0 : k)) * LN_);
            if (k >= 2) { mbar_arrive(sb + B_HR0 + 8 * (k - 2)); STAMP(true, 2, 12 + k); }
          }
        }
        STAMP(true, 2, 12);
        DUMP(true, 2, 8, 16);
      }
    }
  } else {
    const int tid = threadIdx.x & 127;
    const int g = lane >> 2, t = lane & 3;
    const uint32_t sQ = sb + SM_Q + wg * 32768;
#define st0 tid_is(wg * 128)
    STAMP(st0, wg, 0);
    const int rr = lane >> 3, j = lane & 7;
    const uint32_t c0 = clk();
    if (threadIdx.x == 0) {
      for (int i = 0; i < 3; i++) { mbar_init(sb + B_FULL + 8 * i, 1); mbar_init(sb + B_EMPTY + 8 * i, tail ? 4 : 8); }
      for (int i = 0; i < 4; i++) { mbar_init(sb + B_WF + 8 * i, 1); mbar_init(sb + B_EVP0 + 8 * i, 4); }
      for (int i = 0; i < 2; i++) { mbar_init(sb + B_QFULL + 8 * i, 1); mbar_init(sb + B_QEMPTY + 8 * i, 4); }
      mbar_init(sb + B_EVH, 8); mbar_init(sb + B_EVQ, 8); mbar_init(sb + B_HALF, 8); mbar_init(sb + B_HR0, 1); mbar_init(sb + B_HR0 + 8, 1); mbar_init(sb + B_M0, 1); mbar_init(sb + B_SPF, 1); mbar_init(sb + B_EVS, 1);
      asm volatile("fence.mbarrier_init.release.cluster;" ::: "memory");
    }
    __syncwarp();
    while (clk() - c0 < XDELAY) {}
    if (total > 0) {
#pragma unroll 1
      for (int p = 0; p < 4; p++) {
        const int r = warp * 16 + p * 4 + rr;
        const uint4* px = (const uint4*)(P.x + (size_t)min(W.q0 * 128 + wg * 64 + r, NN - 1) * 256) + j;
        const uint32_t off = (r >> 3) * 4096 + (r & 7) * 128 + ((j ^ (r & 7)) << 4);
#pragma unroll
        for (int c = 0; c < 4; c++) cp_async16(sQ + off + c * 1024, px + c * 8);
        cp_commit();
      }
    }
    bar_sync(4, 384);
    if (wg == 1) bar_arrive(5, 256);

    if (total > 0) {
      {
        const bool own = (W.own >> wg) & 1;
        uint8_t* gh = (uint8_t*)g_h + (size_t)W.q0 * 65536 + wg * 32768;
#pragma unroll 1
        for (int p = 0; p < 4; p++) {
          const int r = warp * 16 + p * 4 + rr;
          const uint32_t off = (r >> 3) * 4096 + (r & 7) * 128 + ((j ^ (r & 7)) << 4);
          asm volatile("cp.async.wait_group 3;" ::: "memory");
          cp_commit();
          float f[32];
#pragma unroll
          for (int c = 0; c < 4; c++) {
            const uint4 v = lds128(sQ + off + c * 1024);
            f[c * 8 + 0] = bf_lo(v.x); f[c * 8 + 1] = bf_hi(v.x); f[c * 8 + 2] = bf_lo(v.y); f[c * 8 + 3] = bf_hi(v.y);
            f[c * 8 + 4] = bf_lo(v.z); f[c * 8 + 5] = bf_hi(v.z); f[c * 8 + 6] = bf_lo(v.w); f[c * 8 + 7] = bf_hi(v.w);
          }
          float s0 = 0.f, s1 = 0.f, s2 = 0.f, s3 = 0.f;
#pragma unroll
          for (int i = 0; i < 16; i++) { s0 += f[2 * i]; s1 += f[2 * i + 1]; s2 += f[2 * i] * f[2 * i]; s3 += f[2 * i + 1] * f[2 * i + 1]; }
          float sum = s0 + s1, ss = s2 + s3;
#pragma unroll
          for (int k = 1; k < 8; k *= 2) { sum += __shfl_xor_sync(0xffffffffu, sum, k); ss += __shfl_xor_sync(0xffffffffu, ss, k); }
          const float mean = sum * (1.0f / 256.0f);
          float var = ss * (1.0f / 256.0f) - mean * mean;
          if (__any_sync(0xffffffffu, !(mean * mean <= 16.f * var))) {
            s2 = s3 = 0.f;
#pragma unroll
            for (int i = 0; i < 16; i++) { s2 += (f[2 * i] - mean) * (f[2 * i] - mean); s3 += (f[2 * i + 1] - mean) * (f[2 * i + 1] - mean); }
            ss = s2 + s3;
#pragma unroll
            for (int k = 1; k < 8; k *= 2) ss += __shfl_xor_sync(0xffffffffu, ss, k);
            var = ss * (1.0f / 256.0f);
          }
          float rs;
          asm("rsqrt.approx.ftz.f32 %0, %1;" : "=f"(rs) : "f"(var + 1e-5f));
          if (W.q0 * 128 + wg * 64 + r >= NN) rs = 0.f;
          const float nb = -mean * rs;
#pragma unroll
          for (int c = 0; c < 4; c++) {
            uint4 h4 = make_uint4(pack_bf16(fmaf(f[c * 8], rs, nb), fmaf(f[c * 8 + 1], rs, nb)), pack_bf16(fmaf(f[c * 8 + 2], rs, nb), fmaf(f[c * 8 + 3], rs, nb)),
                                  pack_bf16(fmaf(f[c * 8 + 4], rs, nb), fmaf(f[c * 8 + 5], rs, nb)), pack_bf16(fmaf(f[c * 8 + 6], rs, nb), fmaf(f[c * 8 + 7], rs, nb)));
            sts128(sQ + off + c * 1024, h4);
            if (c == 3) {
              const float hl = fmaf(f[31], rs, nb), e = j == 7 ? nb - 0.5f * hl : nb;
              h4 = make_uint4(pack_bf16(fmaf(f[24], rs, e), fmaf(f[25], rs, e)), pack_bf16(fmaf(f[26], rs, e), fmaf(f[27], rs, e)),
                              pack_bf16(fmaf(f[28], rs, e), fmaf(f[29], rs, e)), pack_bf16(fmaf(f[30], rs, e), j == 7 ? 1.0f : hl));
            }
            if (own) *(uint4*)(gh + off + c * 1024) = h4;
          }
        }
        __syncwarp();
        if (lane == 0) mbar_arrive(sb + B_EVH);
        fence_async_smem();
        bar_sync(1 + wg, 128);
      }
    }
    asm volatile("setmaxnreg.inc.sync.aligned.u32 %0;" :: "n"(CREG));
    STAMP(st0, wg, 1);

    float o[128];
    int qph = 0;
    auto release = [&](int stg) { if (lane == 0) mbar_arrive(sb + B_EMPTY + 8 * stg); };
    if (total == 0) {
#pragma unroll 1
      for (int i = 0; i < 32; i++) {
        const int r = i * 8 + wg * 4 + warp;
        cp_async16(sb + ((POS_M >> (r >> 6) * 4) & 15) * 32768 + sw_byte(r & 63, lane * 8), (const uint4*)P.wout + r * 32 + lane);
      }
    }
#pragma unroll 1
    for (int step = total > 0 ? -1 : -4; step < W.nloc; step++) {
      const bool isq = step < 0 && total > 0, isw = step < 0 && total == 0;
      if (isw) {
        const uint4* src = (const uint4*)(step < -2 ? P.wmsg : P.wv) + ((step & 1) * 128 + wg * 64 + warp) * 32 + lane;
        float cw[8] = {0.f, 0.f, 0.f, 0.f, 0.f, 0.f, 0.f, 0.f};
#pragma unroll 1
        for (int i = 0; i < 16; i++) cp_async16(sQ + sw_byte(i * 4 + warp, lane * 8), src + i * 128);
        cp_commit();
#pragma unroll
        for (int i = 0; i < 8; i++) {
          const uint4 v = __ldg((const uint4*)(step < -2 ? P.wmsg : P.wv) + (248 + i) * 32 + lane);
          const float k = i == 7 ? -1.0f / 4.5f : -0.5f / 4.5f;
          cw[0] += bf_lo(v.x) * k; cw[1] += bf_hi(v.x) * k; cw[2] += bf_lo(v.y) * k; cw[3] += bf_hi(v.y) * k;
          cw[4] += bf_lo(v.z) * k; cw[5] += bf_hi(v.z) * k; cw[6] += bf_lo(v.w) * k; cw[7] += bf_hi(v.w) * k;
        }
        asm volatile("cp.async.wait_group 0;" ::: "memory");
#pragma unroll 1
        for (int i = 0; i < 16; i++) {
          const uint32_t ad = sQ + sw_byte(i * 4 + warp, lane * 8);
          const uint4 v = lds128(ad);
          uint4 w4 = make_uint4(pack_bf16(bf_lo(v.x) + cw[0], bf_hi(v.x) + cw[1]), pack_bf16(bf_lo(v.y) + cw[2], bf_hi(v.y) + cw[3]),
                                pack_bf16(bf_lo(v.z) + cw[4], bf_hi(v.z) + cw[5]), pack_bf16(bf_lo(v.w) + cw[6], bf_hi(v.w) + cw[7]));
          if ((step & 1) * 128 + wg * 64 + i * 4 + warp == 255) w4 = make_uint4(0, 0, 0, 0);
          sts128(ad, w4);
        }
        fence_async_smem();
        bar_sync(7, 256);
      } else {
        if (!isq) { mbar_wait(sb + B_QFULL + 8 * wg, qph); qph ^= 1; }
        STAMP(st0 && step == 0, wg, 8);
        bar_sync(5 + wg, 256);
      }
#pragma unroll 1
      for (int c = 0; c < 4; c++) {
        if (isq || step == 0) mbar_wait(isq && c == 0 ? sb + B_M0 : sb + B_WF + 8 * c, !isq && total > 0);
        if (c == 1 && isq) bar_sync(5 + wg, 256);
        wg_fence();
        const uint64_t dA = desc_k(sb + SM_Q, wg * 2048 + c * 64), dW = desc_mn(sb, (((isq ? POS_M : posw) >> c * 4) & 15) * 2048);
        static_for<0, 4>([&](auto k) {
          if (k.value == 1) { if (isq && c == 0) mbar_wait(sb + B_WF, 0); wg_fence(); }
          wgmma_ss_n256_tb<k.value * 2, k.value * 512>(o, dA, dW, k.value > 0 ? 1 : c);
        });
        wg_commit();
        if ((c == 3 || (c == 0 && isq)) && !isw) bar_arrive(6 - wg, 256);
        if (c == 0 && isq) { wg_wait<0>(); if (!tail) release(0); }
        wg_wait<1>();
      }
      wg_wait<0>();
      reg_fence(o);
      if (!isq) {
        STAMP(st0 && step == 0, wg, 9);
        if (isw) bar_sync(1 + wg, 128); else if (lane == 0) mbar_arrive(sb + B_QEMPTY + 8 * wg);
        if (W.na0 > 0) mbar_wait(sb + B_HR0 + 8, 0);
        uint8_t* dw = (uint8_t*)(step < -2 ? g_Wmo : g_Wvo) + ((step & 1) * 2 + wg) * 32768 + warp * 8192 + g * 128;
        const int row0 = (W.loc0 + step) * 128 + wg * 64 + warp * 16;
        uint4* po = (uint4*)(P.out + (size_t)(row0 + g) * 256) + t;
        uint4 r[16];
#pragma unroll
        for (int u = 0; u < 8; u++) { r[2 * u] = ROW0(u); r[2 * u + 1] = ROW1(u); }
        if (isw) {
#pragma unroll
          for (int u = 0; u < 16; u++) *(uint4*)(dw + (u >> 2) * 1024 + ((((u & 2) * 2 + t) ^ g) << 4) + (u & 1) * 4096) = r[u];
        } else if (row0 < NN) {
#pragma unroll
          for (int u = 0; u < 16; u++) red_bf16x8(po + (u >> 1) * 4 + (u & 1) * 256, r[u]);
        }
        if (step == -1) { bar_sync(7, 256); if (threadIdx.x == 0) flag_release(F_W); __syncwarp(); STAMP(st0, wg, 3); }
        continue;
      }
      if (!tail) release(1);
      STAMP(st0, wg, 2);
      float c0 = (o[124] + (t == 3 ? 2.f : 1.f) * o[125]) * (-0.5f / 4.5f), c1 = (o[126] + (t == 3 ? 2.f : 1.f) * o[127]) * (-0.5f / 4.5f);
      c0 += __shfl_xor_sync(0xffffffffu, c0, 1); c1 += __shfl_xor_sync(0xffffffffu, c1, 1);
      c0 += __shfl_xor_sync(0xffffffffu, c0, 2); c1 += __shfl_xor_sync(0xffffffffu, c1, 2);
      bar_sync(1 + wg, 128);
#pragma unroll
      for (int k = 0; k < 16; k++)
        stsm4(sQ + warp * 8192 + ((lane >> 3) & 1) * 4096 + (k >> 2) * 1024 + (lane & 7) * 128 + ((((k & 3) * 2 + (lane >> 4)) ^ (lane & 7)) << 4),
              pack_bf16(o[8 * k] + c0, o[8 * k + 1] + c0), pack_bf16(o[8 * k + 2] + c1, o[8 * k + 3] + c1),
              pack_bf16(o[8 * k + 4] + c0, k == 15 && t == 3 ? 0.f : o[8 * k + 5] + c0), pack_bf16(o[8 * k + 6] + c1, k == 15 && t == 3 ? 0.f : o[8 * k + 7] + c1));
      fence_async_smem();
      bar_sync(1 + wg, 128);
      STAMP(st0, wg, 3);

      float m0, m1;
      const int qh = tail ? 0 : wg, tl = W.role >> 2;
      int st = tail ? wg : 0, ph = 0;
      if (tail) { bar_sync(7, 256); if (wg == 0) { release(0); release(1); release(2); } }
      uint32_t qo = qh * 2048;
      const uint32_t ko = (2 - tl) * 2048, stop = 1 + tl + (uint32_t)P.zero;
#define PART(u) make_uint4(pack_bf16(o[8 * u], o[8 * u + 1]), pack_bf16(o[8 * u + 2], o[8 * u + 3]), pack_bf16(o[8 * u + 4], o[8 * u + 5]), pack_bf16(o[8 * u + 6], o[8 * u + 7]))
      auto stage = [&]() {
#pragma unroll
        for (int u = 0; u < 16; u++) sts128(sb + 6 * 32768 + (u * 128 + tid) * 16, PART(u));
        fence_async_smem();
        __syncwarp();
        if (lane == 0) mbar_arrive(sb + B_EVP0 + 8 * wg);
      };
      bool unsafe = false;
#pragma unroll 1
      for (int seg = 0;; seg++) {
        const bool last = seg || n1 == 0;
        m0 = m1 = unsafe ? -INFINITY : 0.f;
        int first = 1;
        auto tile = [&](auto n_, bool endseg) {
          constexpr int N = n_.value;
          float s[N / 2]; uint32_t p[N / 4];
          if (N == 128 || !(first && seg)) { if (!mbar_try_wait(sb + B_FULL + 8 * st, ph)) mbar_wait(sb + B_FULL + 8 * st, ph); }
          bar_sync(5 + wg, 256);
          wg_fence();
          const uint64_t dQ = desc_k(sb + SM_Q, qo), dK = desc_k(sb, ko + st * 4096);
          qo += (uint32_t)P.zero;
          static_for<0, 16>([&](auto k) { constexpr int off = (k.value >> 2) * 64 + (k.value & 3) * 2; wgmma_qk<off, off>(s, dQ, dK, k.value > 0); });
          wg_commit();
          bar_arrive(6 - wg, 256);
          if (N == 112 && first && seg && wg == 1) { mbar_wait(sb + B_SPF, 0); stage(); }
          if (N == 112 && first && !seg) {
            float a0 = 0.f, a1 = 0.f, a2 = 0.f, a3 = 0.f;
#pragma unroll
            for (int i = 0; i < 32; i++) { a0 += o[4 * i] * o[4 * i]; a2 += o[4 * i + 1] * o[4 * i + 1]; a1 += o[4 * i + 2] * o[4 * i + 2]; a3 += o[4 * i + 3] * o[4 * i + 3]; }
            a0 += a2; a1 += a3;
            a0 += __shfl_xor_sync(0xffffffffu, a0, 1); a1 += __shfl_xor_sync(0xffffffffu, a1, 1);
            a0 += __shfl_xor_sync(0xffffffffu, a0, 2); a1 += __shfl_xor_sync(0xffffffffu, a1, 2);
            unsafe = __any_sync(0xffffffffu, bar_red_or(tail ? 7 : 1 + wg, tail ? 256 : 128, !(a0 <= SAFE_N2) || !(a1 <= SAFE_N2)));
            if (lane == 0) { asm volatile("st.shared.u8 [%0], %1;" :: "r"(sb + SM_UNSAFE + wg), "r"((uint32_t)unsafe) : "memory"); mbar_arrive(sb + B_EVQ); }
            m0 = m1 = unsafe ? -INFINITY : 0.f;
          }
          STAMP(N == 112 && first && !seg && st0, wg, 0);
          wg_wait<0>();
          reg_fence(s);
          if (endseg) { if (lane == 0) mbar_arrive(sb + B_QEMPTY + 8 * wg); }
          if (unsafe) {
            float a0 = fmaxf(s[0], s[1]), a1 = fmaxf(s[2], s[3]);
#pragma unroll
            for (int i = 1; i < N / 8; i++) { a0 = fmaxf(a0, fmaxf(s[4 * i], s[4 * i + 1])); a1 = fmaxf(a1, fmaxf(s[4 * i + 2], s[4 * i + 3])); }
            if (__any_sync(0xffffffffu, (a0 > m0 + TAU) || (a1 > m1 + TAU))) {
              a0 = fmaxf(a0, __shfl_xor_sync(0xffffffffu, a0, 1)); a1 = fmaxf(a1, __shfl_xor_sync(0xffffffffu, a1, 1));
              a0 = fmaxf(a0, __shfl_xor_sync(0xffffffffu, a0, 2)); a1 = fmaxf(a1, __shfl_xor_sync(0xffffffffu, a1, 2));
              const float x0 = ceilf(fmaxf(m0, a0)), x1 = ceilf(fmaxf(m1, a1)), sc0 = ex2(m0 - x0), sc1 = ex2(m1 - x1);
              m0 = x0; m1 = x1;
#pragma unroll
              for (int i = 0; i < 32; i++) { o[4 * i] *= sc0; o[4 * i + 1] *= sc0; o[4 * i + 2] *= sc1; o[4 * i + 3] *= sc1; }
            }
#pragma unroll
            for (int i = 0; i < N / 8; i++) { s[4 * i] -= m0; s[4 * i + 1] -= m0; s[4 * i + 2] -= m1; s[4 * i + 3] -= m1; }
          }
          auto pv = [&](auto k) { wgmma_rs_n256_tb<k.value * 512 + (63 << 16)>(o, p[4 * k.value], p[4 * k.value + 1], p[4 * k.value + 2], p[4 * k.value + 3], dK, k.value > 0 || N == 128 ? 1 : !first); };
#pragma unroll
          for (int i = 0; i < 16; i++) { p[i] = pack_bf16(ex2(s[2 * i]), ex2(s[2 * i + 1])); asm volatile("" : "+r"(p[i]) :: "memory"); }
          reg_fence(o);
          do bar_sync(5 + wg, 256); while (P.zero);
          wg_fence();
          static_for<0, 4>(pv);
          wg_commit();
#pragma unroll
          for (int i = 16; i < N / 4; i++) { p[i] = pack_bf16(ex2(s[2 * i]), ex2(s[2 * i + 1])); asm volatile("" : "+r"(p[i]) :: "memory"); }
          wg_fence();
          static_for<4, N / 16>(pv);
          wg_commit();
          bar_arrive(6 - wg, 256);
          if (N == 128) { wg_wait<1>(); if (endseg && last) { if (lane == 0) mbar_arrive(sb + B_HALF); } }
          wg_wait<0>();
          reg_fence(o); reg_fence(p);
          release(st);
          if (st) { st--; ph ^= 1; } else st = stop;
        };
#pragma unroll 1
        for (int left = tail ? 8 - wg : (seg ? W.nb1 : W.nb0); left > 0; left--) { tile(IC<112>{}, false); STAMP(first && !seg && st0, wg, 4); first = 0; }
#pragma unroll 1
        for (int left = tail ? 32 + wg : (seg ? W.na1 : W.na0); left > 0; left--) tile(IC<128>{}, left == 1);
        STAMP(st0 && last, wg, 6);
        if (last && fin && !(tail && wg == 1)) break;
        const int slot = last && !tail ? W.slotB : W.slotA;
        if (last && !tail && wg == 1) mbar_wait(sb + B_HR0, 0);
        if (!last) {
          mbar_wait(sb + B_QFULL + 8 * wg, qph); qph ^= 1;
          uint32_t u; asm volatile("ld.shared.u8 %0, [%1];" : "=r"(u) : "r"(sb + SM_UNSAFE + wg) : "memory");
          unsafe = __any_sync(0xffffffffu, u != 0);
          mbar_wait(sb + B_FULL + 8 * st, ph);
        }
        if (t == 3) {
          float2* ml = g_ml + slot * 128 + wg * 64 + warp * 16 + g;
          ml[0] = make_float2(m0, o[125] + 0.f); ml[8] = make_float2(m1, o[127] + 0.f);
        }
        if (!last && wg == 0) stage();
        if (last) {
          uint4* dst = g_part + (size_t)slot * 4096 + wg * 2048 + tid;
#pragma unroll
          for (int u = 0; u < 16; u++) dst[u * 128] = PART(u);
          __syncwarp();
          if (lane == 0) mbar_arrive(sb + B_EVP0 + 16 + 8 * wg);
          STAMP(st0, wg, 7);
          break;
        }
      }

      if (fin) {
        if (tail && wg == 1) break;
        float l0 = __shfl_sync(0xffffffffu, o[125] + 0.f, lane | 3), l1 = __shfl_sync(0xffffffffu, o[127] + 0.f, lane | 3);
        const int rl = wg * 64 + warp * 16 + g;
        uint32_t a[64];
#pragma unroll
        for (int i = 0; i < 64; i++) a[i] = pack_bf16(o[2 * i], o[2 * i + 1]);
        reg_fence(a);
        {
          float2 e0, e1;
          mbar_wait(sb + B_QFULL + 8 * wg, qph);
          asm volatile("ld.shared.v2.f32 {%0,%1}, [%2];" : "=f"(e0.x), "=f"(e0.y) : "r"(sb + SM_ML + rl * 8) : "memory");
          asm volatile("ld.shared.v2.f32 {%0,%1}, [%2];" : "=f"(e1.x), "=f"(e1.y) : "r"(sb + SM_ML + rl * 8 + 64) : "memory");
          STAMP(st0, wg, 7);
          uint4 v[16];
#pragma unroll
          for (int u = 0; u < 16; u++) v[u] = lds128(sQ + (u * 128 + tid) * 16);
          uint32_t fb0 = 0x3f803f80u, fb1 = 0x3f803f80u;
          const float s0 = l0 + e0.y, s1 = l1 + e1.y;
          if (__any_sync(0xffffffffu, m0 != e0.x || m1 != e1.x || !(fmaxf(s0, s1) < 0x1p40f) || !(fminf(s0, s1) > 0x1p-40f))) {
            const float x0 = fmaxf(m0, e0.x), x1 = fmaxf(m1, e1.x);
            const float d0 = fmaxf(m0 - x0, -1000.f), d1 = fmaxf(m1 - x1, -1000.f), f0 = fmaxf(e0.x - x0, -1000.f), f1 = fmaxf(e1.x - x1, -1000.f);
            l0 = l0 * ex2(d0) + e0.y * ex2(f0); l1 = l1 * ex2(d1) + e1.y * ex2(f1);
            const int E0 = fexp(l0), E1 = fexp(l1);
            const uint32_t fa0 = pow2_bf2((int)d0 - E0), fa1 = pow2_bf2((int)d1 - E1);
            fb0 = pow2_bf2((int)f0 - E0); fb1 = pow2_bf2((int)f1 - E1);
            l0 = __uint_as_float(__float_as_uint(l0) - (E0 << 23)); l1 = __uint_as_float(__float_as_uint(l1) - (E1 << 23));
#pragma unroll
            for (int i = 0; i < 32; i++) { a[2 * i] = hmul2(a[2 * i], fa0); a[2 * i + 1] = hmul2(a[2 * i + 1], fa1); }
          } else { l0 = s0; l1 = s1; }
#pragma unroll
          for (int u = 0; u < 16; u++) {
            a[4 * u] = hfma2(v[u].x, fb0, a[4 * u]); a[4 * u + 1] = hfma2(v[u].y, fb1, a[4 * u + 1]);
            a[4 * u + 2] = hfma2(v[u].z, fb0, a[4 * u + 2]); a[4 * u + 3] = hfma2(v[u].w, fb1, a[4 * u + 3]);
          }
        }
        float fs0, fs1;
        asm("rcp.approx.ftz.f32 %0, %1;" : "=f"(fs0) : "f"(l0)); asm("rcp.approx.ftz.f32 %0, %1;" : "=f"(fs1) : "f"(l1));
        STAMP(st0, wg, 8);
        reg_fence(a);
        bar_sync(5 + wg, 256);
        uint64_t dW[4];
        float y0[64], y1[64];
        auto half0 = [&](auto u_) {
          constexpr int u = u_.value;
          if (u % 4 == 0) { mbar_wait(sb + B_WF + 2 * u, 1); wg_fence(); dW[u / 4] = desc_mn(sb, ((posw >> u) & 15) * 2048); }
          wgmma_rs_n128_tb<(u & 3) * 512>(y0, a[4 * u], a[4 * u + 1], a[4 * u + 2], a[4 * u + 3], dW[u / 4], u != 0);
        };
        auto half1 = [&](auto u_) {
          constexpr int u = u_.value;
          wgmma_rs_n128_tb<(u & 3) * 512 + 128>(y1, a[4 * u], a[4 * u + 1], a[4 * u + 2], a[4 * u + 3], dW[u / 4], u != 0);
        };
        const bool wr = W.q0 * 128 + wg * 64 + warp * 16 < NN;
        uint4* po = (uint4*)(P.out + (size_t)(W.q0 * 128 + rl) * 256) + t;
        auto emit = [&](const float* y, uint4* dst) {
          if (wr) {
            red_bf16x8(dst, make_uint4(pack_bf16(y[0] * fs0, y[1] * fs0), pack_bf16(y[4] * fs0, y[5] * fs0), pack_bf16(y[8] * fs0, y[9] * fs0), pack_bf16(y[12] * fs0, y[13] * fs0)));
            red_bf16x8(dst + 8 * 32, make_uint4(pack_bf16(y[2] * fs1, y[3] * fs1), pack_bf16(y[6] * fs1, y[7] * fs1), pack_bf16(y[10] * fs1, y[11] * fs1), pack_bf16(y[14] * fs1, y[15] * fs1)));
          }
          wg_fence();
        };
        static_for<0, 16>(half0);
        wg_commit();
        static_for<0, 4>(half1);
        wg_commit();
        wg_wait<1>();
        reg_fence(y0);
        emit(y0, po); static_for<4, 8>(half1);
        emit(y0 + 16, po + 4); static_for<8, 12>(half1);
        emit(y0 + 32, po + 8); static_for<12, 16>(half1);
        wg_commit();
        bar_arrive(6 - wg, 256);
        emit(y0 + 48, po + 12);
        wg_wait<0>();
        reg_fence(a); reg_fence(y1);
        STAMP(st0, wg, 9);
#pragma unroll
        for (int u = 0; u < 4; u++) emit(y1 + 16 * u, po + 16 + 4 * u);
        break;
      }
    }
    STAMP(st0, wg, 11);
    DUMP(st0, wg, 0, 16);
  }
}

}

extern "C" void kernel_launch(void* const* d_in, const int* in_sizes, int n_in, void* d_out, int out_size) {
  Params P;
  P.x = (const __nv_bfloat16*)d_in[0];
  P.src = (const int*)d_in[1];
  P.dst = (const int*)d_in[2];
  P.dinv = (const __nv_bfloat16*)d_in[3];
  P.wmsg = (const __nv_bfloat16*)d_in[4];
  P.wq = (const __nv_bfloat16*)d_in[5];
  P.wk = (const __nv_bfloat16*)d_in[6];
  P.wv = (const __nv_bfloat16*)d_in[7];
  P.wout = (const __nv_bfloat16*)d_in[8];
  P.out = (__nv_bfloat16*)d_out;
  P.zero = 0;
  for (int c = 0; c < NCTA; c++) P.w[c] = make_work(c);
  static void* scr = nullptr;
  if (!scr) {
    cudaFuncSetAttribute(gps_kernel, cudaFuncAttributeMaxDynamicSharedMemorySize, SMEM_BYTES);
    cudaGetSymbolAddress(&scr, g_scr);
  }
  P.s = (Scratch*)scr;
  P.h = (uint4*)(((uintptr_t)P.s->h + 4095) & ~(uintptr_t)4095);
  if (((uintptr_t)P.h >> 32) != (((uintptr_t)(P.h + NQT * 4096) - 1) >> 32)) P.h += NQT * 4096;
  gps_kernel<<<NCTA, 384, SMEM_BYTES>>>(P);
}
```

```cpp
#include <cuda_runtime.h>
#include <cuda_bf16.h>
#include <stdint.h>
#include <stddef.h>
#include <type_traits>
#define FB 5
#define MB 5
#define GSTART 10000
#define G8 1
#define XDELAY 200
#define CREG 224
#define BACKOFF 1000

namespace {

constexpr int NN = 10000;
constexpr int NE = 160000;
constexpr int NQT = 79;
constexpr int NCTA = 132;
constexpr int CAP = 64;
constexpr int CAPS = 64;
constexpr int NHSIG = 105;
constexpr uint32_t WCH_B = 32768;
constexpr int NGW = (NCTA - 1) * 3;
constexpr float TAU = 16.0f;
constexpr float SAFE_N2 = 36.0f, SAFE_C = 0.6f;
#define KOFF 2
#define PSH -8.0f
#define KROT 15
constexpr float KS = 0.25f, KC = KOFF * KS;
constexpr uint32_t KS2 = 0x3e803e80u, KC2 = KOFF == 2 ? 0x3f003f00u : (KOFF == 1 ? 0x3e803e80u : 0x3f403f40u);

constexpr int NAGG = 4;
constexpr int NRND = (NN + NGW - 1) / NGW;
constexpr int NSLOT = 105;
constexpr int F_EPOCH = 0, F_H = 1, F_M = 4  , LN_ = 32;
constexpr int F_BIN = LN_, F_W = 2 * LN_, F_OVF = 3 * LN_  , F_QP = 5 * LN_, F_AGG = F_QP + NQT * LN_,
              F_PART = F_AGG + NAGG * LN_, F_END = F_PART + 2 * NSLOT * LN_;

struct Scratch {
  uint32_t flag[F_END];
  alignas(4096) uint4 M[8192];
  uint4 Wvo[8192], Wmo[8192];
  float2 ml[NSLOT * 128];
  uint32_t unsafe[96];
  int cnt[NN + 32];
  alignas(4096) uint4 h[2 * NQT * 4096 + 256];
  uint4 qp[NQT * 4096];
  uint4 agg[NQT * 4096];
  uint4 part[NSLOT * 4096];
  int bin[(NN + NGW) * CAPS];
  int2 ovf[NE];
};
static_assert(offsetof(Scratch, h) % 128 == 0, "alignment");
__device__ Scratch g_scr;
struct alignas(16) Work { short k0, k1; signed char q0, q1, nb0, na0, nb1, na1, slotA, slotB, loc0, nloc, own, role; };
constexpr int R_FIN = 1, R_PUB = 2, R_TAIL = 4;
struct Params {
  const __nv_bfloat16 *x, *wq, *wk;
  Scratch* s;
  uint4* h;
  __nv_bfloat16* out;
  const __nv_bfloat16 *wout, *wmsg, *wv, *dinv;
  const int *src, *dst;
  long long zero;
  Work w[NCTA];
};
constexpr int NSERV = NQT - 52;
inline Work make_work(int c) {
  Work w;
  const int gi = c / 5, r = c % 5, q = gi * 3;
  const bool helper = r & 1, mid = r == 2;
  w.q0 = helper ? q + 1 : q + (r >> 1);
  const int hb1 = (15 - MB) / 2, hb3 = 15 - MB - hb1;
  w.nb0 = helper ? (r == 1 ? hb1 : hb3) : (mid ? MB : FB);
  w.na0 = (helper ? 16 : 48) - w.nb0;
  w.k0 = helper ? (48 * 8 - MB) + (r >> 1) * (16 * 8 - hb1) : 0;
  w.q1 = q + (r & 2);
  w.k1 = 48 * 8 - FB;
  w.nb1 = helper ? 7 - FB : 0;
  w.na1 = helper ? 31 - w.nb1 : 0;
  w.slotA = 4 * gi + (helper ? r - 1 : (mid ? 0 : (r >> 1) + 1));
  w.slotB = helper ? 4 * gi + r : (mid ? 4 * gi + 2 : -1);
  w.loc0 = NSERV + gi * 2 + (r >> 1);
  w.nloc = helper;
  w.own = helper ? (r + 1) >> 1 : (mid ? 0 : 3);
  w.role = helper ? 0 : (mid ? R_FIN : R_FIN | R_PUB);
  if (c == 130) { w.nb0 = 15; w.na0 = 65; w.slotA = NSLOT - 1; w.own = 1; w.role = R_FIN | R_TAIL; }
  if (c == 131) { w.nb0 = w.na0 = w.nb1 = w.na1 = 0; w.loc0 = 0; w.nloc = NSERV; w.own = 0; }
  return w;
}
#define g_flag P.s->flag
#define g_M P.s->M
#define g_Wvo P.s->Wvo
#define g_Wmo P.s->Wmo
#define g_ml P.s->ml
#define g_unsafe P.s->unsafe
#define g_cnt P.s->cnt
#define g_h P.h
#define g_qp P.s->qp
#define g_agg P.s->agg
#define g_part P.s->part
#define g_bin P.s->bin
#define g_ovf P.s->ovf

__device__ __forceinline__ uint32_t smem_u32(const void* p) { return (uint32_t)__cvta_generic_to_shared(p); }
__device__ __forceinline__ void mbar_init(uint32_t bar, uint32_t cnt) { asm volatile("mbarrier.init.shared::cta.b64 [%0], %1;" :: "r"(bar), "r"(cnt) : "memory"); }
__device__ __forceinline__ void mbar_arrive(uint32_t bar) { asm volatile("mbarrier.arrive.shared::cta.b64 _, [%0];" :: "r"(bar) : "memory"); }
__device__ __forceinline__ void mbar_expect_tx(uint32_t bar, uint32_t bytes) { asm volatile("mbarrier.arrive.expect_tx.shared::cta.b64 _, [%0], %1;" :: "r"(bar), "r"(bytes) : "memory"); }
__device__ __forceinline__ bool mbar_try_wait(uint32_t bar, uint32_t parity) {
  uint32_t ok;
  asm volatile("{\n.reg .pred p;\nmbarrier.try_wait.parity.shared::cta.b64 p, [%1], %2;\nselp.b32 %0, 1, 0, p;\n}\n" : "=r"(ok) : "r"(bar), "r"(parity) : "memory");
  return ok;
}
__device__ __forceinline__ bool mbar_try_wait_nb(uint32_t bar, uint32_t parity) {
  uint32_t ok;
  asm volatile("{\n.reg .pred p;\nmbarrier.test_wait.parity.shared::cta.b64 p, [%1], %2;\nselp.b32 %0, 1, 0, p;\n}\n" : "=r"(ok) : "r"(bar), "r"(parity) : "memory");
  return ok;
}
__device__ __forceinline__ void mbar_wait(uint32_t bar, uint32_t parity) {
#pragma unroll 1
  for (uint32_t it = 0; it < (1u << 25); it++) if (mbar_try_wait(bar, parity)) break;
}
__device__ __forceinline__ void bulk_s2g(void* dst, uint32_t src, uint32_t bytes) {
  asm volatile("cp.async.bulk.global.shared::cta.bulk_group [%0], [%1], %2;" :: "l"(dst), "r"(src), "r"(bytes) : "memory");
}
__device__ __forceinline__ void bulk_commit() { asm volatile("cp.async.bulk.commit_group;" ::: "memory"); }
__device__ __forceinline__ void bulk_wait_read() { asm volatile("cp.async.bulk.wait_group.read 0;" ::: "memory"); }
__device__ __forceinline__ void bulk_wait_all() { asm volatile("cp.async.bulk.wait_group 0;" ::: "memory"); }
__device__ __forceinline__ bool bar_red_or(int id, int cnt, bool c) {
  uint32_t r;
  asm volatile("{\n.reg .pred p, q;\nsetp.ne.b32 q, %3, 0;\nbar.red.or.pred p, %1, %2, q;\nselp.b32 %0, 1, 0, p;\n}\n"
               : "=r"(r) : "r"(id), "r"(cnt), "r"((uint32_t)c) : "memory");
  return r != 0;
}
template <class T> __device__ __forceinline__ T* pofs(const void* base, uint32_t off) {
  asm volatile("" : "+r"(off));
  return (T*)((uint8_t*)base + off);
}
__device__ __forceinline__ const void* addr64(uint32_t lo, uint32_t hi) { uint64_t a; asm("mov.b64 %0, {%1, %2};" : "=l"(a) : "r"(lo), "r"(hi)); return (const void*)a; }
__device__ __forceinline__ uint4 ldcg_v(const void* a) {
  uint4 v;
  asm volatile("ld.volatile.global.v4.u32 {%0,%1,%2,%3}, [%4];" : "=r"(v.x), "=r"(v.y), "=r"(v.z), "=r"(v.w) : "l"(a) : "memory");
  return v;
}
__device__ __forceinline__ void cp_async16(uint32_t dst, const void* src) {
  asm volatile("cp.async.cg.shared.global [%0], [%1], 16;" :: "r"(dst), "l"(src) : "memory");
}
__device__ __forceinline__ void red_bf16x8(void* a, uint4 v) {
  asm volatile("red.global.add.noftz.v4.bf16x2 [%0], {%1,%2,%3,%4};" :: "l"(a), "r"(v.x), "r"(v.y), "r"(v.z), "r"(v.w) : "memory");
}
__device__ __forceinline__ uint32_t clk() { uint32_t c; asm volatile("mov.u32 %0, %%clock;" : "=r"(c) :: "memory"); return c; }
__device__ __forceinline__ void stsm4(uint32_t a, uint32_t r0, uint32_t r1, uint32_t r2, uint32_t r3) {
  asm volatile("stmatrix.sync.aligned.m8n8.x4.shared.b16 [%0], {%1,%2,%3,%4};" :: "r"(a), "r"(r0), "r"(r1), "r"(r2), "r"(r3) : "memory");
}
__device__ __forceinline__ uint32_t lds32(uint32_t a) { uint32_t v; asm volatile("ld.shared.u32 %0, [%1];" : "=r"(v) : "r"(a) : "memory"); return v; }
__device__ __forceinline__ void cp_commit() { asm volatile("cp.async.commit_group;" ::: "memory"); }
__device__ __forceinline__ uint32_t hmul2(uint32_t a, uint32_t b) { uint32_t d; asm("mul.rn.bf16x2 %0, %1, %2;" : "=r"(d) : "r"(a), "r"(b)); return d; }
__device__ __forceinline__ uint32_t hfma2(uint32_t a, uint32_t b, uint32_t c) { uint32_t d; asm("fma.rn.bf16x2 %0, %1, %2, %3;" : "=r"(d) : "r"(a), "r"(b), "r"(c)); return d; }
__device__ __forceinline__ uint32_t pow2_bf2(int n) { return (uint32_t)max(n + 127, 0) * 0x00800080u; }
__device__ __forceinline__ int fexp(float x) { return (int)(__float_as_uint(x) >> 23) - 127; }
__device__ __forceinline__ void bulk_g2s(uint32_t dst, const void* src, uint32_t bytes, uint32_t bar) {
  asm volatile("cp.async.bulk.shared::cta.global.mbarrier::complete_tx::bytes [%0], [%1], %2, [%3];"
    :: "r"(dst), "l"(src), "r"(bytes), "r"(bar) : "memory");
}
__device__ __forceinline__ void wg_fence() { asm volatile("wgmma.fence.sync.aligned;" ::: "memory"); }
__device__ __forceinline__ void wg_commit() { asm volatile("wgmma.commit_group.sync.aligned;" ::: "memory"); }
template<int N> __device__ __forceinline__ void wg_wait() { asm volatile("wgmma.wait_group.sync.aligned %0;" :: "n"(N) : "memory"); }
__device__ __forceinline__ void bar_sync(int id, int cnt) { asm volatile("bar.sync %0, %1;" :: "r"(id), "r"(cnt) : "memory"); }
__device__ __forceinline__ void fence_async_smem() { asm volatile("fence.proxy.async.shared::cta;" ::: "memory"); }
__device__ __forceinline__ void fence_async_gmem() { asm volatile("fence.proxy.async.global;" ::: "memory"); }
__device__ __forceinline__ void bar_arrive(int id, int cnt) { asm volatile("bar.arrive %0, %1;" :: "r"(id), "r"(cnt) : "memory"); }
__device__ __forceinline__ void red_release(uint32_t* p) { asm volatile("red.release.gpu.global.add.u32 [%0], 1;" :: "l"(p) : "memory"); }
__device__ __forceinline__ void red_release_w(uint32_t* p) {
  __syncwarp();
  asm volatile("{\n.reg .pred q;\n.reg .b32 l;\nmov.u32 l, %%laneid;\nsetp.eq.u32 q, l, 0;\n@q fence.release.gpu;\n@q red.relaxed.gpu.global.add.u32 [%0], 1;\n}\n" :: "l"(p) : "memory");
}
__device__ __forceinline__ void mbar_wait_w(uint32_t bar, uint32_t parity) {
#pragma unroll 1
  for (uint32_t it = 0; it < (1u << 25); it++) if (__all_sync(0xffffffffu, mbar_try_wait(bar, parity))) break;
}
#define flag_release_w(f) red_release_w(g_flag + (f))
#define flag_wait_w(f, target) poll_acquire_w(g_flag + (f), target)
#define flag_release(f) red_release(g_flag + (f))
__device__ __forceinline__ uint32_t ld_relaxed(const uint32_t* p) {
  uint32_t v; asm volatile("ld.relaxed.gpu.global.u32 %0, [%1];" : "=r"(v) : "l"(p) : "memory"); return v;
}
#define flag_wait(f, target) poll_acquire(g_flag + (f), target)
__device__ __forceinline__ void poll_acquire(const uint32_t* p, uint32_t target) {
#pragma unroll 1
  for (uint32_t it = 0; it < (1u << 23); it++) if ((int)(ld_relaxed(p) - target) >= 0) break;
  asm volatile("fence.acquire.gpu;" ::: "memory");
}
__device__ __forceinline__ void poll_acquire_w(const uint32_t* p, uint32_t target) {
#pragma unroll 1
  for (uint32_t it = 0; it < (1u << 23); it++) {
    if (__all_sync(0xffffffffu, (int)(ld_relaxed(p) - target) >= 0)) break;
    if (BACKOFF) __nanosleep(BACKOFF);
  }
  asm volatile("fence.acquire.gpu;" ::: "memory");
}
template<int N> __device__ __forceinline__ void reg_fence(float (&d)[N]) {
#pragma unroll
  for (int i = 0; i < N; i++) asm volatile("" : "+f"(d[i]) :: "memory");
}
template<int N> __device__ __forceinline__ void reg_fence(uint32_t (&d)[N]) {
#pragma unroll
  for (int i = 0; i < N; i++) asm volatile("" : "+r"(d[i]) :: "memory");
}
__device__ __forceinline__ float ex2(float x) { float y; asm("ex2.approx.ftz.f32 %0, %1;" : "=f"(y) : "f"(x)); return y; }
__device__ __forceinline__ uint32_t pack_bf16(float lo, float hi) { uint32_t r; asm("cvt.rn.bf16x2.f32 %0, %1, %2;" : "=r"(r) : "f"(hi), "f"(lo)); return r; }
__device__ __forceinline__ float bf_lo(uint32_t w) { return __uint_as_float(w << 16); }
__device__ __forceinline__ float bf_hi(uint32_t w) { return __uint_as_float(w & 0xffff0000u); }
__device__ __forceinline__ uint64_t desc_k(uint32_t addr, uint32_t add) { return (uint64_t)((((addr & 0x3FFFF) >> 4) | (1u << 16)) + add) | (0x40000100ull << 32); }
__device__ __forceinline__ uint64_t desc_mn(uint32_t addr, uint32_t add) { return (uint64_t)((((addr & 0x3FFFF) >> 4) | ((1024u >> 4) << 16)) + add) | (0x40000100ull << 32); }
__device__ __forceinline__ void sts128(uint32_t a, uint4 v) { asm volatile("st.shared.v4.u32 [%0], {%1,%2,%3,%4};" :: "r"(a), "r"(v.x), "r"(v.y), "r"(v.z), "r"(v.w) : "memory"); }
__device__ __forceinline__ uint4 lds128(uint32_t a) { uint4 v; asm volatile("ld.shared.v4.u32 {%0,%1,%2,%3}, [%4];" : "=r"(v.x), "=r"(v.y), "=r"(v.z), "=r"(v.w) : "r"(a) : "memory"); return v; }
__device__ __forceinline__ void mma16816(float (&c)[4], uint32_t a0, uint32_t a1, uint32_t a2, uint32_t a3, uint32_t b0, uint32_t b1) {
  asm volatile("mma.sync.aligned.m16n8k16.row.col.f32.bf16.bf16.f32 {%0,%1,%2,%3}, {%4,%5,%6,%7}, {%8,%9}, {%0,%1,%2,%3};"
    : "+f"(c[0]), "+f"(c[1]), "+f"(c[2]), "+f"(c[3]) : "r"(a0), "r"(a1), "r"(a2), "r"(a3), "r"(b0), "r"(b1));
}
__device__ __forceinline__ uint32_t sw_byte(int r, int c) {
  return (uint32_t)((r >> 3) * 4096 + (c >> 6) * 1024 + (r & 7) * 128 + ((((c >> 3) & 7) ^ (r & 7)) << 4) + (c & 7) * 2);
}
#define STAMP(cond, who, i)
#define CSTAMP(cond, who, i)
#define DUMP(cond, who, i0, i1)

template <int OA, int OB> __device__ __forceinline__ void wgmma_ss_n256_tb(float (&d)[128], uint64_t da, uint64_t db, int scale_d) {
  asm volatile("{\n.reg .pred p;\n.reg .b64 a, b;\nsetp.ne.b32 p, %130, 0;\nadd.s64 a, %128, %131;\nadd.s64 b, %129, %132;\n"
    "wgmma.mma_async.sync.aligned.m64n256k16.f32.bf16.bf16 "
    "{%0, %1, %2, %3, %4, %5, %6, %7, %8, %9, %10, %11, %12, %13, %14, %15, %16, %17, %18, %19, %20, %21, %22, %23, %24, %25, %26, %27, %28, %29, %30, %31, %32, %33, %34, %35, %36, %37, %38, %39, %40, %41, %42, %43, %44, %45, %46, %47, %48, %49, %50, %51, %52, %53, %54, %55, %56, %57, %58, %59, %60, %61, %62, %63, %64, %65, %66, %67, %68, %69, %70, %71, %72, %73, %74, %75, %76, %77, %78, %79, %80, %81, %82, %83, %84, %85, %86, %87, %88, %89, %90, %91, %92, %93, %94, %95, %96, %97, %98, %99, %100, %101, %102, %103, %104, %105, %106, %107, %108, %109, %110, %111, %112, %113, %114, %115, %116, %117, %118, %119, %120, %121, %122, %123, %124, %125, %126, %127}, "
    "a, b, p, 1, 1, 0, 1;\n}\n"
    : "+f"(d[0]), "+f"(d[1]), "+f"(d[2]), "+f"(d[3]), "+f"(d[4]), "+f"(d[5]), "+f"(d[6]), "+f"(d[7]), "+f"(d[8]), "+f"(d[9]), "+f"(d[10]), "+f"(d[11]), "+f"(d[12]), "+f"(d[13]), "+f"(d[14]), "+f"(d[15]), "+f"(d[16]), "+f"(d[17]), "+f"(d[18]), "+f"(d[19]), "+f"(d[20]), "+f"(d[21]), "+f"(d[22]), "+f"(d[23]), "+f"(d[24]), "+f"(d[25]), "+f"(d[26]), "+f"(d[27]), "+f"(d[28]), "+f"(d[29]), "+f"(d[30]), "+f"(d[31]), "+f"(d[32]), "+f"(d[33]), "+f"(d[34]), "+f"(d[35]), "+f"(d[36]), "+f"(d[37]), "+f"(d[38]), "+f"(d[39]), "+f"(d[40]), "+f"(d[41]), "+f"(d[42]), "+f"(d[43]), "+f"(d[44]), "+f"(d[45]), "+f"(d[46]), "+f"(d[47]), "+f"(d[48]), "+f"(d[49]), "+f"(d[50]), "+f"(d[51]), "+f"(d[52]), "+f"(d[53]), "+f"(d[54]), "+f"(d[55]), "+f"(d[56]), "+f"(d[57]), "+f"(d[58]), "+f"(d[59]), "+f"(d[60]), "+f"(d[61]), "+f"(d[62]), "+f"(d[63]), "+f"(d[64]), "+f"(d[65]), "+f"(d[66]), "+f"(d[67]), "+f"(d[68]), "+f"(d[69]), "+f"(d[70]), "+f"(d[71]), "+f"(d[72]), "+f"(d[73]), "+f"(d[74]), "+f"(d[75]), "+f"(d[76]), "+f"(d[77]), "+f"(d[78]), "+f"(d[79]), "+f"(d[80]), "+f"(d[81]), "+f"(d[82]), "+f"(d[83]), "+f"(d[84]), "+f"(d[85]), "+f"(d[86]), "+f"(d[87]), "+f"(d[88]), "+f"(d[89]), "+f"(d[90]), "+f"(d[91]), "+f"(d[92]), "+f"(d[93]), "+f"(d[94]), "+f"(d[95]), "+f"(d[96]), "+f"(d[97]), "+f"(d[98]), "+f"(d[99]), "+f"(d[100]), "+f"(d[101]), "+f"(d[102]), "+f"(d[103]), "+f"(d[104]), "+f"(d[105]), "+f"(d[106]), "+f"(d[107]), "+f"(d[108]), "+f"(d[109]), "+f"(d[110]), "+f"(d[111]), "+f"(d[112]), "+f"(d[113]), "+f"(d[114]), "+f"(d[115]), "+f"(d[116]), "+f"(d[117]), "+f"(d[118]), "+f"(d[119]), "+f"(d[120]), "+f"(d[121]), "+f"(d[122]), "+f"(d[123]), "+f"(d[124]), "+f"(d[125]), "+f"(d[126]), "+f"(d[127])
    : "l"(da), "l"(db), "r"(scale_d), "n"(OA), "n"(OB));
}
template <int OA, int OB> __device__ __forceinline__ void wgmma_qk(float (&d)[64], uint64_t da, uint64_t db, int scale_d) {
  asm volatile("{\n.reg .pred p;\n.reg .b64 a, b;\nsetp.ne.b32 p, %66, 0;\nadd.s64 a, %64, %67;\nadd.s64 b, %65, %68;\n"
    "wgmma.mma_async.sync.aligned.m64n128k16.f32.bf16.bf16 "
    "{%0, %1, %2, %3, %4, %5, %6, %7, %8, %9, %10, %11, %12, %13, %14, %15, %16, %17, %18, %19, %20, %21, %22, %23, %24, %25, %26, %27, %28, %29, %30, %31, %32, %33, %34, %35, %36, %37, %38, %39, %40, %41, %42, %43, %44, %45, %46, %47, %48, %49, %50, %51, %52, %53, %54, %55, %56, %57, %58, %59, %60, %61, %62, %63}, "
    "a, b, p, 1, 1, 0, 0;\n}\n"
    : "+f"(d[0]), "+f"(d[1]), "+f"(d[2]), "+f"(d[3]), "+f"(d[4]), "+f"(d[5]), "+f"(d[6]), "+f"(d[7]), "+f"(d[8]), "+f"(d[9]), "+f"(d[10]), "+f"(d[11]), "+f"(d[12]), "+f"(d[13]), "+f"(d[14]), "+f"(d[15]), "+f"(d[16]), "+f"(d[17]), "+f"(d[18]), "+f"(d[19]), "+f"(d[20]), "+f"(d[21]), "+f"(d[22]), "+f"(d[23]), "+f"(d[24]), "+f"(d[25]), "+f"(d[26]), "+f"(d[27]), "+f"(d[28]), "+f"(d[29]), "+f"(d[30]), "+f"(d[31]), "+f"(d[32]), "+f"(d[33]), "+f"(d[34]), "+f"(d[35]), "+f"(d[36]), "+f"(d[37]), "+f"(d[38]), "+f"(d[39]), "+f"(d[40]), "+f"(d[41]), "+f"(d[42]), "+f"(d[43]), "+f"(d[44]), "+f"(d[45]), "+f"(d[46]), "+f"(d[47]), "+f"(d[48]), "+f"(d[49]), "+f"(d[50]), "+f"(d[51]), "+f"(d[52]), "+f"(d[53]), "+f"(d[54]), "+f"(d[55]), "+f"(d[56]), "+f"(d[57]), "+f"(d[58]), "+f"(d[59]), "+f"(d[60]), "+f"(d[61]), "+f"(d[62]), "+f"(d[63])
    : "l"(da), "l"(db), "r"(scale_d), "n"(OA), "n"(OB));
}
template <int OA, int OB> __device__ __forceinline__ void wgmma_qk(float (&d)[56], uint64_t da, uint64_t db, int scale_d) {
  asm volatile("{\n.reg .pred p;\n.reg .b64 a, b;\nsetp.ne.b32 p, %58, 0;\nadd.s64 a, %56, %59;\nadd.s64 b, %57, %60;\n"
    "wgmma.mma_async.sync.aligned.m64n112k16.f32.bf16.bf16 "
    "{%0, %1, %2, %3, %4, %5, %6, %7, %8, %9, %10, %11, %12, %13, %14, %15, %16, %17, %18, %19, %20, %21, %22, %23, %24, %25, %26, %27, %28, %29, %30, %31, %32, %33, %34, %35, %36, %37, %38, %39, %40, %41, %42, %43, %44, %45, %46, %47, %48, %49, %50, %51, %52, %53, %54, %55}, "
    "a, b, p, 1, 1, 0, 0;\n}\n"
    : "+f"(d[0]), "+f"(d[1]), "+f"(d[2]), "+f"(d[3]), "+f"(d[4]), "+f"(d[5]), "+f"(d[6]), "+f"(d[7]), "+f"(d[8]), "+f"(d[9]), "+f"(d[10]), "+f"(d[11]), "+f"(d[12]), "+f"(d[13]), "+f"(d[14]), "+f"(d[15]), "+f"(d[16]), "+f"(d[17]), "+f"(d[18]), "+f"(d[19]), "+f"(d[20]), "+f"(d[21]), "+f"(d[22]), "+f"(d[23]), "+f"(d[24]), "+f"(d[25]), "+f"(d[26]), "+f"(d[27]), "+f"(d[28]), "+f"(d[29]), "+f"(d[30]), "+f"(d[31]), "+f"(d[32]), "+f"(d[33]), "+f"(d[34]), "+f"(d[35]), "+f"(d[36]), "+f"(d[37]), "+f"(d[38]), "+f"(d[39]), "+f"(d[40]), "+f"(d[41]), "+f"(d[42]), "+f"(d[43]), "+f"(d[44]), "+f"(d[45]), "+f"(d[46]), "+f"(d[47]), "+f"(d[48]), "+f"(d[49]), "+f"(d[50]), "+f"(d[51]), "+f"(d[52]), "+f"(d[53]), "+f"(d[54]), "+f"(d[55])
    : "l"(da), "l"(db), "r"(scale_d), "n"(OA), "n"(OB));
}
template <int OB> __device__ __forceinline__ void wgmma_rs_n256_tb(float (&d)[128], uint32_t a0, uint32_t a1, uint32_t a2, uint32_t a3, uint64_t db, int scale_d) {
  asm volatile("{\n.reg .pred p;\n.reg .b64 b;\nsetp.ne.b32 p, %133, 0;\nadd.s64 b, %132, %134;\n"
    "wgmma.mma_async.sync.aligned.m64n256k16.f32.bf16.bf16 "
    "{%0, %1, %2, %3, %4, %5, %6, %7, %8, %9, %10, %11, %12, %13, %14, %15, %16, %17, %18, %19, %20, %21, %22, %23, %24, %25, %26, %27, %28, %29, %30, %31, %32, %33, %34, %35, %36, %37, %38, %39, %40, %41, %42, %43, %44, %45, %46, %47, %48, %49, %50, %51, %52, %53, %54, %55, %56, %57, %58, %59, %60, %61, %62, %63, %64, %65, %66, %67, %68, %69, %70, %71, %72, %73, %74, %75, %76, %77, %78, %79, %80, %81, %82, %83, %84, %85, %86, %87, %88, %89, %90, %91, %92, %93, %94, %95, %96, %97, %98, %99, %100, %101, %102, %103, %104, %105, %106, %107, %108, %109, %110, %111, %112, %113, %114, %115, %116, %117, %118, %119, %120, %121, %122, %123, %124, %125, %126, %127}, "
    "{%128, %129, %130, %131}, b, p, 1, 1, 1;\n}\n"
    : "+f"(d[0]), "+f"(d[1]), "+f"(d[2]), "+f"(d[3]), "+f"(d[4]), "+f"(d[5]), "+f"(d[6]), "+f"(d[7]), "+f"(d[8]), "+f"(d[9]), "+f"(d[10]), "+f"(d[11]), "+f"(d[12]), "+f"(d[13]), "+f"(d[14]), "+f"(d[15]), "+f"(d[16]), "+f"(d[17]), "+f"(d[18]), "+f"(d[19]), "+f"(d[20]), "+f"(d[21]), "+f"(d[22]), "+f"(d[23]), "+f"(d[24]), "+f"(d[25]), "+f"(d[26]), "+f"(d[27]), "+f"(d[28]), "+f"(d[29]), "+f"(d[30]), "+f"(d[31]), "+f"(d[32]), "+f"(d[33]), "+f"(d[34]), "+f"(d[35]), "+f"(d[36]), "+f"(d[37]), "+f"(d[38]), "+f"(d[39]), "+f"(d[40]), "+f"(d[41]), "+f"(d[42]), "+f"(d[43]), "+f"(d[44]), "+f"(d[45]), "+f"(d[46]), "+f"(d[47]), "+f"(d[48]), "+f"(d[49]), "+f"(d[50]), "+f"(d[51]), "+f"(d[52]), "+f"(d[53]), "+f"(d[54]), "+f"(d[55]), "+f"(d[56]), "+f"(d[57]), "+f"(d[58]), "+f"(d[59]), "+f"(d[60]), "+f"(d[61]), "+f"(d[62]), "+f"(d[63]), "+f"(d[64]), "+f"(d[65]), "+f"(d[66]), "+f"(d[67]), "+f"(d[68]), "+f"(d[69]), "+f"(d[70]), "+f"(d[71]), "+f"(d[72]), "+f"(d[73]), "+f"(d[74]), "+f"(d[75]), "+f"(d[76]), "+f"(d[77]), "+f"(d[78]), "+f"(d[79]), "+f"(d[80]), "+f"(d[81]), "+f"(d[82]), "+f"(d[83]), "+f"(d[84]), "+f"(d[85]), "+f"(d[86]), "+f"(d[87]), "+f"(d[88]), "+f"(d[89]), "+f"(d[90]), "+f"(d[91]), "+f"(d[92]), "+f"(d[93]), "+f"(d[94]), "+f"(d[95]), "+f"(d[96]), "+f"(d[97]), "+f"(d[98]), "+f"(d[99]), "+f"(d[100]), "+f"(d[101]), "+f"(d[102]), "+f"(d[103]), "+f"(d[104]), "+f"(d[105]), "+f"(d[106]), "+f"(d[107]), "+f"(d[108]), "+f"(d[109]), "+f"(d[110]), "+f"(d[111]), "+f"(d[112]), "+f"(d[113]), "+f"(d[114]), "+f"(d[115]), "+f"(d[116]), "+f"(d[117]), "+f"(d[118]), "+f"(d[119]), "+f"(d[120]), "+f"(d[121]), "+f"(d[122]), "+f"(d[123]), "+f"(d[124]), "+f"(d[125]), "+f"(d[126]), "+f"(d[127])
    : "r"(a0), "r"(a1), "r"(a2), "r"(a3), "l"(db), "r"(scale_d), "n"(OB));
}
template <int OB> __device__ __forceinline__ void wgmma_rs_n128_tb(float (&d)[64], uint32_t a0, uint32_t a1, uint32_t a2, uint32_t a3, uint64_t db, int scale_d) {
  asm volatile("{\n.reg .pred p;\n.reg .b64 b;\nsetp.ne.b32 p, %69, 0;\nadd.s64 b, %68, %70;\n"
    "wgmma.mma_async.sync.aligned.m64n128k16.f32.bf16.bf16 "
    "{%0, %1, %2, %3, %4, %5, %6, %7, %8, %9, %10, %11, %12, %13, %14, %15, %16, %17, %18, %19, %20, %21, %22, %23, %24, %25, %26, %27, %28, %29, %30, %31, %32, %33, %34, %35, %36, %37, %38, %39, %40, %41, %42, %43, %44, %45, %46, %47, %48, %49, %50, %51, %52, %53, %54, %55, %56, %57, %58, %59, %60, %61, %62, %63}, "
    "{%64, %65, %66, %67}, b, p, 1, 1, 1;\n}\n"
    : "+f"(d[0]), "+f"(d[1]), "+f"(d[2]), "+f"(d[3]), "+f"(d[4]), "+f"(d[5]), "+f"(d[6]), "+f"(d[7]), "+f"(d[8]), "+f"(d[9]), "+f"(d[10]), "+f"(d[11]), "+f"(d[12]), "+f"(d[13]), "+f"(d[14]), "+f"(d[15]), "+f"(d[16]), "+f"(d[17]), "+f"(d[18]), "+f"(d[19]), "+f"(d[20]), "+f"(d[21]), "+f"(d[22]), "+f"(d[23]), "+f"(d[24]), "+f"(d[25]), "+f"(d[26]), "+f"(d[27]), "+f"(d[28]), "+f"(d[29]), "+f"(d[30]), "+f"(d[31]), "+f"(d[32]), "+f"(d[33]), "+f"(d[34]), "+f"(d[35]), "+f"(d[36]), "+f"(d[37]), "+f"(d[38]), "+f"(d[39]), "+f"(d[40]), "+f"(d[41]), "+f"(d[42]), "+f"(d[43]), "+f"(d[44]), "+f"(d[45]), "+f"(d[46]), "+f"(d[47]), "+f"(d[48]), "+f"(d[49]), "+f"(d[50]), "+f"(d[51]), "+f"(d[52]), "+f"(d[53]), "+f"(d[54]), "+f"(d[55]), "+f"(d[56]), "+f"(d[57]), "+f"(d[58]), "+f"(d[59]), "+f"(d[60]), "+f"(d[61]), "+f"(d[62]), "+f"(d[63])
    : "r"(a0), "r"(a1), "r"(a2), "r"(a3), "l"(db), "r"(scale_d), "n"(OB));
}
template <int V> using IC = std::integral_constant<int, V>;
template <int I, int N, class F> __device__ __forceinline__ void static_for(F&& f) {
  if constexpr (I < N) { f(std::integral_constant<int, I>{}); static_for<I + 1, N>(f); }
}

constexpr uint32_t SM_Q = 0, SM_BAR = 7 * 32768;
constexpr uint32_t B_FULL = SM_BAR, B_EMPTY = B_FULL + 24, B_WF = B_EMPTY + 24, B_QFULL = B_WF + 32, B_QEMPTY = B_QFULL + 16,
                   B_EVH = B_QEMPTY + 16, B_EVQ = B_EVH + 8, B_EVP0 = B_EVQ + 8, B_HR0 = B_EVP0 + 32, B_M0 = B_HR0 + 16, B_HALF = B_M0 + 8,
                   B_SPF = B_HALF + 8, B_EVS = B_SPF + 8, SM_UNSAFE = B_EVS + 8, SM_TS = SM_UNSAFE + 8, SM_ML = (SM_TS + 192 + 15) / 16 * 16, SM_EPOCH = SM_ML + 1024, SM_END = SM_EPOCH + 16;
constexpr uint32_t POS_M = 0x5462;
constexpr int SMEM_BYTES = SM_END;

#define ROW0(u) make_uint4(pack_bf16(o[16 * u], o[16 * u + 1]), pack_bf16(o[16 * u + 4], o[16 * u + 5]), \
                           pack_bf16(o[16 * u + 8], o[16 * u + 9]), pack_bf16(o[16 * u + 12], o[16 * u + 13]))
#define ROW1(u) make_uint4(pack_bf16(o[16 * u + 2], o[16 * u + 3]), pack_bf16(o[16 * u + 6], o[16 * u + 7]), \
                           pack_bf16(o[16 * u + 10], o[16 * u + 11]), pack_bf16(o[16 * u + 14], o[16 * u + 15]))

__global__ void __launch_bounds__(384, 1) gps_kernel(const __grid_constant__ Params P) {
  extern __shared__ __align__(1024) uint8_t smem_raw[];
  constexpr uint32_t sb = 1024;
  if (smem_u32(smem_raw) != sb) return;
  const int cta = blockIdx.x;
  const int wg = __shfl_sync(0xffffffffu, (int)threadIdx.x >> 7, 0);
  const int warp = __shfl_sync(0xffffffffu, ((int)threadIdx.x >> 5) & 3, 0);
  const int lane = threadIdx.x & 31;
  const Work& W = P.w[cta];
  const int n0 = W.nb0 + W.na0, n1 = W.nb1 + W.na1, total = n0 + n1;
  const bool fin = W.role & R_FIN, tail = W.role & R_TAIL;
  const uint32_t posw = total == 0 || tail ? POS_M : ((total & 1) ? 0x2546 : 0x4326);
  if (wg == 2) {
    STAMP(lane == 0 && warp == 0, 2, 0);
    const int g = lane >> 2, t = lane & 3;
        const int mi = cta >> 3;
    const uint32_t sW = sb + 3 * 32768;
    uint4 wa[4], wb[8];
    {
      const uint4* pq = (const uint4*)(P.wq + ((mi & 15) * 16 + g) * 256) + warp * 8 + t;
      const uint4* pk = (const uint4*)(P.wk + ((cta & 7) * 32 + g) * 256) + warp * 8 + t;
#pragma unroll
      for (int i = 0; i < 4; i++) wa[i] = __ldg(pq + (i >> 1) * 256 + (i & 1) * 4);
#pragma unroll
      for (int i = 0; i < 8; i++) wb[i] = __ldg(pk + (i >> 1) * 256 + (i & 1) * 4);
    }
    bar_sync(4, 384);
    {
#pragma unroll
      for (int n = 0; n < 4; n++) {
        float c[4] = {0.f, 0.f, 0.f, 0.f};
#pragma unroll
        for (int u = 0; u < 2; u++) {
          mma16816(c, wa[u].x, wa[2 + u].x, wa[u].y, wa[2 + u].y, wb[2 * n + u].x, wb[2 * n + u].y);
          mma16816(c, wa[u].z, wa[2 + u].z, wa[u].w, wa[2 + u].w, wb[2 * n + u].z, wb[2 * n + u].w);
        }
        asm volatile("st.shared.v2.f32 [%0], {%1,%2};" :: "r"(sW + ((warp * 16 + g) * 40 + n * 8 + 2 * t) * 4), "f"(c[0]), "f"(c[1]) : "memory");
        asm volatile("st.shared.v2.f32 [%0], {%1,%2};" :: "r"(sW + ((warp * 16 + g + 8) * 40 + n * 8 + 2 * t) * 4), "f"(c[2]), "f"(c[3]) : "memory");
      }
      STAMP(lane == 0 && warp == 0, 2, 7);
      bar_sync(3, 128);
      if (warp < 2) {
        float c[8] = {0.f, 0.f, 0.f, 0.f, 0.f, 0.f, 0.f, 0.f};
#pragma unroll
        for (int k = 0; k < 4; k++) {
          const uint4 v = lds128(sW + ((k * 16 + warp * 8 + g) * 40 + t * 8) * 4), w = lds128(sW + ((k * 16 + warp * 8 + g) * 40 + t * 8 + 4) * 4);
          c[0] += __uint_as_float(v.x); c[1] += __uint_as_float(v.y); c[2] += __uint_as_float(v.z); c[3] += __uint_as_float(v.w);
          c[4] += __uint_as_float(w.x); c[5] += __uint_as_float(w.y); c[6] += __uint_as_float(w.z); c[7] += __uint_as_float(w.w);
        }
        const float ms = 1.4426950408889634f / 16.0f / KS;
        if (cta < 128)
          *(uint4*)((uint8_t*)g_M + sw_byte(mi * 16 + warp * 8 + g, (cta & 7) * 32 + t * 8)) =
              make_uint4(pack_bf16(c[0] * ms, c[1] * ms), pack_bf16(c[2] * ms, c[3] * ms), pack_bf16(c[4] * ms, c[5] * ms), pack_bf16(c[6] * ms, c[7] * ms));
      }
    }
    asm volatile("setmaxnreg.dec.sync.aligned.u32 %0;" :: "n"(504 - 2 * CREG));
    STAMP(lane == 0 && warp == 0, 2, 13);
    bar_sync(3, 128);
#define ep1 (lds32(sb + SM_EPOCH) + 1)
    const int gw = cta * 3 + warp - 1;
    if (threadIdx.x == 256 && cta < 128) flag_release(F_M + (cta >> 5));
    __syncwarp();
    if (warp == 0) {
      if (lane == 0) {
        STAMP(true, 2, 1);
        const uint32_t epoch = ld_relaxed(g_flag + F_EPOCH);
        if (total > 0) {
#pragma unroll
          for (int c = 0; c < 3; c++) mbar_expect_tx(sb + B_WF + 8 * c, c == 0 ? WCH_B - 8192 : WCH_B);
          mbar_expect_tx(sb + B_M0, 8192);
          int c = 0;
#pragma unroll 1
          for (uint32_t it = 0; c < 4; it++) {
            uint4 f;
            asm volatile("ld.relaxed.gpu.global.v4.u32 {%0,%1,%2,%3}, [%4];" : "=r"(f.x), "=r"(f.y), "=r"(f.z), "=r"(f.w) : "l"(g_flag + F_M) : "memory");
            uint32_t tm;
            asm volatile("mad.lo.u32 %0, %1, 32, 32;" : "=r"(tm) : "r"(epoch));
            int ok = (int)(f.x - tm) < 0 ? 0 : (int)(f.y - tm) < 0 ? 1 : (int)(f.z - tm) < 0 ? 2 : (int)(f.w - tm) < 0 ? 3 : 4;
            if (it > (1u << 23)) ok = 4;
            if (ok > c) {
              asm volatile("fence.acquire.gpu;" ::: "memory"); fence_async_gmem();
              if (c == 0) bulk_g2s(sb + (POS_M & 15) * 32768, g_M, 8192, sb + B_M0);
            }
#pragma unroll 1
            for (; c < ok; c++) {
              const uint32_t skip = c == 0 ? 8192 : 0;
              bulk_g2s(sb + ((POS_M >> c * 4) & 15) * 32768 + skip, pofs<const uint8_t>(g_M, c * WCH_B + skip), WCH_B - skip, sb + B_WF + 8 * c);
              STAMP(c == 0, 2, 2);
            }
          }
        }
        asm volatile("st.shared.u32 [%0], %1;" :: "r"(sb + SM_EPOCH), "r"(epoch) : "memory");
        if (total > 0) mbar_expect_tx(sb + B_WF + 24, WCH_B);
        int st = 0, ph = 0, qph = 0;
        const int nsl = tail ? 3 : 2;
        auto next_slot = [&]() { mbar_wait(sb + B_EMPTY + 8 * st, ph); if (++st == nsl) { st = 0; ph ^= 1; } };
        auto w_load = [&](int c0, int c1) {
#pragma unroll 1
          for (int c = c0; c < c1; c++) {
            mbar_expect_tx(sb + B_WF + 8 * c, WCH_B);
            bulk_g2s(sb + ((posw >> c * 4) & 15) * 32768, pofs<const uint8_t>(fin ? g_Wvo : g_Wmo, c * WCH_B), WCH_B, sb + B_WF + 8 * c);
          }
        };
        auto q_load = [&](const uint4* src, bool wait_empty) {
#pragma unroll 1
          for (int h = 0; h < 2; h++) {
            if (wait_empty) mbar_wait(sb + B_QEMPTY + 8 * h, qph);
            mbar_expect_tx(sb + B_QFULL + 8 * h, 32768);
            bulk_g2s(sb + SM_Q + h * 32768, src + h * 2048, 32768, sb + B_QFULL + 8 * h);
          }
          if (wait_empty) qph ^= 1;
        };
        if (total > 0) {
          STAMP(true, 2, 3);
          flag_wait(F_H, ep1 * NHSIG); fence_async_gmem();
          STAMP(true, 2, 4);
          uint32_t ko = W.k0 * 8192;
#pragma unroll 1
          for (int j = 0; j < total; j++) {
            if (j == n0) {
              flag_wait(F_QP + W.q1 * LN_, ep1); fence_async_gmem();
              const uint32_t u = __ldcg(g_unsafe + W.q1);
              asm volatile("st.shared.u32 [%0], %1;" :: "r"(sb + SM_UNSAFE), "r"(u) : "memory");
              ko = W.k1 * 8192;
            }
            if (j == n0 + 1) q_load(g_qp + W.q1 * 4096, true);
            if (j == n0 + 2) { bulk_wait_read(); mbar_arrive(sb + B_SPF); }
            if (j == n0 + 1 || j == n0 + 2) {
              mbar_wait(sb + B_EVP0 + 8 * (j - n0 - 1), 0);
              bulk_s2g(pofs<uint4>(g_part, W.slotA * 65536 + (j - n0 - 1) * 32768), sb + 6 * 32768, 32768);
              bulk_commit();
            }
            if (j == n0 + 3) { bulk_wait_all(); mbar_arrive(sb + B_EVS); }
            if (j == total - 1) { flag_wait(F_W, ep1); fence_async_gmem(); if (!tail) w_load(0, 1); }
            const uint32_t bytes = (j < n0 ? j < W.nb0 : j - n0 < W.nb1) ? 112 * 512 : 128 * 512, s0 = st;
            next_slot();
            mbar_expect_tx(sb + B_FULL + 8 * s0, bytes);
            bulk_g2s(sb + ((tail ? 1 : 2) + 2 * s0) * 32768, pofs<const uint8_t>(g_h, ko), bytes, sb + B_FULL + 8 * s0);
            ko += bytes;
          }
          next_slot();
          if (tail) { next_slot(); next_slot(); }
        } else { flag_wait(F_W, ep1); fence_async_gmem(); }
        STAMP(true, 2, 5);
        const bool staged = total > 0 && !tail;
        w_load(staged, staged ? 3 : 4);
#pragma unroll 1
        for (int i = 0; i < W.nloc; i++) {
          const int tl = W.loc0 + i, last = tl * 128 + 127 < NN ? tl * 128 + 127 : NN - 1;
          flag_wait(F_AGG + ((last >= NGW) + (last >= 4 * NGW) + (last >= 9 * NGW)) * LN_, ep1 * NGW); fence_async_gmem();
          if (total == 0) g_flag[F_EPOCH] = epoch + 1;
          q_load(g_agg + tl * 4096, total > 0 || i > 0);
        }
        if (staged) { mbar_wait(sb + B_HALF, 0); if (!fin) mbar_wait(sb + B_HR0, 0); w_load(3, 4); }
        DUMP(true, 2, 0, 8);
      }
    } else {
      if (warp == 3 && W.own) { mbar_wait_w(sb + B_EVH, 0); flag_release_w(F_H); STAMP(lane == 0, 2, 6); }
      bool early = warp == 1 && n1 > 0;
      if (total > 0) {
        mbar_wait_w(sb + B_EVQ, 0);
        const uint32_t c0 = clk();
        if (warp == 1 && (W.role & R_PUB)) {
          g_unsafe[W.q0] = lds32(sb + SM_UNSAFE);
#pragma unroll 1
          for (int k = 0; k < 4; k++) {
            __nanosleep(2000);
            if (lane == 0) bulk_s2g(pofs<uint4>(g_qp, W.q0 * 65536 + k * 16384), sb + SM_Q + k * 16384, 16384);
            bulk_commit();
          }
          bulk_wait_all();
          flag_release_w(F_QP + W.q0 * LN_);
        }
        while (__any_sync(0xffffffffu, clk() - c0 < GSTART)) __nanosleep(500);
        STAMP(lane == 0 && warp == 1, 2, 8);
#define ovf_cnt pofs<uint32_t>(g_flag, (F_OVF + (ep1 & 1) * LN_) * 4)
        if (gw == 0) g_flag[F_OVF + ((ep1 + 1) & 1) * LN_] = 0;
#pragma unroll 1
        for (int e0 = gw * 32; e0 < NE; e0 += NGW * 32 * 7) {
          int d[7], s[7], pos[7];
          const int* pd = pofs<const int>(P.dst, (e0 + lane) * 4);
          const int* ps = pofs<const int>(P.src, (e0 + lane) * 4);
#pragma unroll
          for (int k = 0; k < 7; k++) { const bool ok = e0 + k * NGW * 32 < NE; d[k] = ok ? __ldg(pd + k * NGW * 32) : -1; s[k] = ok ? __ldg(ps + k * NGW * 32) : 0; }
          uint32_t ov = 0;
#pragma unroll
          for (int k = 0; k < 7; k++) {
            pos[k] = 0;
            if (d[k] >= 0) asm volatile("atom.relaxed.gpu.global.add.u32 %0, [%1], 1;" : "=r"(pos[k]) : "l"(pofs<int>(g_cnt, d[k] << 2)) : "memory");
            s[k] = (uint32_t)(uintptr_t)g_h + (s[k] >> 3) * 4096 + (s[k] & 7) * 144;
            if (d[k] >= 0 && pos[k] < CAP) asm volatile("st.volatile.global.u32 [%0], %1;" :: "l"(pofs<int>(g_bin, (d[k] * CAPS + pos[k]) << 2)), "r"(s[k]) : "memory");
            ov |= (pos[k] >= CAP) << k;
          }
          if (__any_sync(0xffffffffu, ov != 0)) {
            uint32_t at;
            asm volatile("atom.relaxed.gpu.global.add.u32 %0, [%1], %2;" : "=r"(at) : "l"(ovf_cnt), "r"(__popc(ov)) : "memory");
#pragma unroll
            for (int k = 0; k < 7; k++) if ((ov >> k) & 1) g_ovf[at++] = make_int2(d[k], s[k]);
          }
        }
        flag_release_w(F_BIN);
        STAMP(lane == 0 && warp == 1, 2, 9);
        flag_wait_w(F_H, ep1 * NHSIG);
        flag_wait_w(F_BIN, ep1 * NGW);
        STAMP(lane == 0 && warp == 1, 2, 10);
        const uint32_t lx = ((lane & 7) << 4) | ((lane >> 3) << 10);
        const int myn = gw + lane * NGW < NN ? gw + lane * NGW : gw;
        int cnts = __ldcg(g_cnt + myn);
        cnts = (cnts > CAP ? CAP + 1 : cnts) | ((int)__ldg((const unsigned short*)P.dinv + myn) << 16);
        __syncwarp();
        g_cnt[myn] = 0;
        const uint32_t hhi = (uintptr_t)g_h >> 32;
        uint32_t obin = gw * CAPS * 4;
        uint4 q = *pofs<const uint4>(g_bin, obin), q2 = *pofs<const uint4>(g_bin, obin + 16);
        int sig = 0, nsig = 0;
#pragma unroll 1
        for (int rnd = 0; rnd < NRND; rnd++) {
          const int n = gw + rnd * NGW;
          if (n < NN) {
            const int cd = __shfl_sync(0xffffffffu, cnts, rnd);
            const int cb = (cd & 0xffff) > CAP ? CAP : (cd & 0xffff);
            float acc[8];
#pragma unroll
            for (int k = 0; k < 8; k++) acc[k] = 0.f;
            auto add_row = [&](uint4 v) {
              acc[0] += bf_lo(v.x); acc[1] += bf_hi(v.x); acc[2] += bf_lo(v.y); acc[3] += bf_hi(v.y);
              acc[4] += bf_lo(v.z); acc[5] += bf_hi(v.z); acc[6] += bf_lo(v.w); acc[7] += bf_hi(v.w);
            };
#define ROW(w) ldcg_v(addr64((w) ^ lx, hhi))
            int e = 8;
#pragma unroll 1
            for (; e <= cb; e += 8) {
              const uint4 v0 = ROW(q.x), v1 = ROW(q.y), v2 = ROW(q.z), v3 = ROW(q.w), v4 = ROW(q2.x), v5 = ROW(q2.y), v6 = ROW(q2.z), v7 = ROW(q2.w);
              const uint4* pq = pofs<const uint4>(g_bin, obin + e * 4);
              q = pq[0]; q2 = pq[1];
              add_row(v7); add_row(v6); add_row(v5); add_row(v4); add_row(v3); add_row(v2); add_row(v1); add_row(v0);
            }
            if (cb & 4) {
              const uint4 v0 = ROW(q.x), v1 = ROW(q.y), v2 = ROW(q.z), v3 = ROW(q.w);
              add_row(v3); add_row(v2); add_row(v1); add_row(v0);
              q = q2;
            }
            {
              uint4 v0, v1, v2;
              const int m = cb & 3;
              if (m > 0) v0 = ROW(q.x);
              if (m > 1) v1 = ROW(q.y);
              if (m > 2) v2 = ROW(q.z);
              const uint4 xrow = ldcg_v(pofs<const uint4>(P.x, n * 512 + lane * 16));
              const uint4* pq = pofs<const uint4>(g_bin, obin + NGW * CAPS * 4);
              q = pq[0]; q2 = pq[1];
              *pofs<uint4>(P.out, n * 512 + lane * 16) = xrow;
              if (m > 2) add_row(v2);
              if (m > 1) add_row(v1);
              if (m > 0) add_row(v0);
            }
            if ((cd & 0xffff) > CAP) {
              const int no = __shfl_sync(0xffffffffu, (int)ld_relaxed(ovf_cnt), 0);
#pragma unroll 1
              for (int i0 = 0; i0 < no; i0 += 32) {
                int2 en = __ldcg(g_ovf + min(i0 + lane, no - 1));
                uint32_t mk = __ballot_sync(0xffffffffu, en.x == n && i0 + lane < no);
#pragma unroll 1
                while (mk) {
                  const int bit = __ffs(mk) - 1; mk &= mk - 1;
                  add_row(ldcg_v(addr64((uint32_t)__shfl_sync(0xffffffffu, en.y, bit) ^ lx, hhi)));
                }
              }
            }
            const float di = __uint_as_float(cd & 0xffff0000u) * (1.0f / KS), nl = -di * __shfl_sync(0xffffffffu, acc[7], 31);
            *pofs<uint4>(g_agg, ((n >> 3) * 4096 + (n & 7) * 144) ^ lx) =
                make_uint4(pack_bf16(fmaf(acc[0], di, nl), fmaf(acc[1], di, nl)), pack_bf16(fmaf(acc[2], di, nl), fmaf(acc[3], di, nl)),
                           pack_bf16(fmaf(acc[4], di, nl), fmaf(acc[5], di, nl)), pack_bf16(fmaf(acc[6], di, nl), fmaf(acc[7], di, nl)));
            obin += NGW * CAPS * 4;
          }
          if (early && __all_sync(0xffffffffu, mbar_try_wait_nb(sb + B_EVS, 0))) { flag_release_w(F_PART + 2 * W.slotA * LN_); early = false; }
          if (rnd == sig) {
            flag_release_w(F_AGG + nsig * LN_);
            nsig++;
            sig = nsig == 1 ? 3 : (nsig == 2 ? 8 : NRND - 1);
          }
        }
      }
      STAMP(lane == 0 && warp == 1, 2, 11);
      if (fin && W.slotB >= 0) {
#pragma unroll 1
        for (int k = 0; k < 2; k++) flag_wait_w(F_PART + 2 * (k ? W.slotB : W.slotA) * LN_, ep1);
#pragma unroll 1
        for (int b = warp - 1; b < 8; b += 3) {
          float2* ma = g_ml + W.slotA * 128 + b * 16 + g;
          const float2* mb = g_ml + W.slotB * 128 + b * 16 + g;
          const float2 a0 = __ldcg(ma), a1 = __ldcg(ma + 8), b0 = __ldcg(mb), b1 = __ldcg(mb + 8);
          const float x0 = fmaxf(a0.x, b0.x), x1 = fmaxf(a1.x, b1.x);
          const float fa0 = ex2(a0.x - x0), fa1 = ex2(a1.x - x1), fb0 = ex2(b0.x - x0), fb1 = ex2(b1.x - x1);
          __syncwarp();
          if (t == 0) { ma[0] = make_float2(x0, a0.y * fa0 + b0.y * fb0); ma[8] = make_float2(x1, a1.y * fa1 + b1.y * fb1); }
          const uint32_t ofs = ((b >> 2) * 2048 + (b & 3) * 32 + lane) * 16;
#pragma unroll 1
          for (int u = 0; u < 16; u += 4) {
            uint4* pa = pofs<uint4>(g_part, W.slotA * 65536 + ofs + u * 2048);
            const uint4* pb = pofs<const uint4>(g_part, W.slotB * 65536 + ofs + u * 2048);
            uint4 va[4], vb[4];
#pragma unroll
            for (int k = 0; k < 4; k++) { va[k] = ldcg_v(pa + k * 128); vb[k] = ldcg_v(pb + k * 128); }
#define FOLD(w, fa, fb) pack_bf16(bf_lo(va[k].w) * fa + bf_lo(vb[k].w) * fb, bf_hi(va[k].w) * fa + bf_hi(vb[k].w) * fb)
#pragma unroll
            for (int k = 3; k >= 0; k--) pa[k * 128] = make_uint4(FOLD(x, fa0, fb0), FOLD(y, fa1, fb1), FOLD(z, fa0, fb0), FOLD(w, fa1, fb1));
          }
        }
        bar_sync(3, 96);
        if (warp == 1) asm volatile("fence.acq_rel.gpu;" ::: "memory");
      }
      if (warp == 1 && fin) flag_wait_w(F_AGG + (NAGG - 1) * LN_, ep1 * NGW);
      if (warp == 1 && lane == 0) {
        if (tail) {
          mbar_wait(sb + B_EVP0 + 24, 0);
          asm volatile("fence.acq_rel.gpu;" ::: "memory"); fence_async_gmem();
          mbar_wait(sb + B_QEMPTY, 0);
          mbar_expect_tx(sb + B_QFULL, 32768 + 512);
          bulk_g2s(sb + SM_ML, g_ml + W.slotA * 128 + 64, 512, sb + B_QFULL);
          bulk_g2s(sb + SM_Q, g_part + W.slotA * 4096 + 2048, 32768, sb + B_QFULL);
        } else if (fin) {
#pragma unroll 1
          for (int h = 0; h < 2; h++) {
            if (W.slotB < 0) flag_wait(F_PART + (2 * W.slotA + h) * LN_, ep1);
            fence_async_gmem();
            STAMP(true, 2, 14 + h);
            mbar_wait(sb + B_QEMPTY + 8 * h, 0);
            mbar_expect_tx(sb + B_QFULL + 8 * h, 32768 + 512);
            bulk_g2s(sb + SM_ML + h * 512, g_ml + W.slotA * 128 + h * 64, 512, sb + B_QFULL + 8 * h);
            bulk_g2s(sb + SM_Q + h * 32768, g_part + W.slotA * 4096 + h * 2048, 32768, sb + B_QFULL + 8 * h);
          }
        } else if (total > 0) {
#pragma unroll 1
          for (int k = early ? 1 : 2; k < 4; k++) {
            mbar_wait(k < 2 ? sb + B_EVS : sb + B_EVP0 + 8 * k, 0);
            flag_release(F_PART + (2 * W.slotA + (k < 2 ? 0 : k)) * LN_);
            if (k >= 2) { mbar_arrive(sb + B_HR0 + 8 * (k - 2)); STAMP(true, 2, 12 + k); }
          }
        }
        STAMP(true, 2, 12);
        DUMP(true, 2, 8, 16);
      }
    }
  } else {
    const int tid = threadIdx.x & 127;
    const int g = lane >> 2, t = lane & 3;
    const uint32_t sQ = sb + SM_Q + wg * 32768;
#define st0 tid_is(wg * 128)
    STAMP(st0, wg, 0);
    const int rr = lane >> 3, j = lane & 7;
    const uint32_t c0 = clk();
    if (threadIdx.x == 0) {
      for (int i = 0; i < 3; i++) { mbar_init(sb + B_FULL + 8 * i, 1); mbar_init(sb + B_EMPTY + 8 * i, tail ? 4 : 8); }
      for (int i = 0; i < 4; i++) { mbar_init(sb + B_WF + 8 * i, 1); mbar_init(sb + B_EVP0 + 8 * i, 4); }
      for (int i = 0; i < 2; i++) { mbar_init(sb + B_QFULL + 8 * i, 1); mbar_init(sb + B_QEMPTY + 8 * i, 4); }
      mbar_init(sb + B_EVH, 8); mbar_init(sb + B_EVQ, 8); mbar_init(sb + B_HALF, 8); mbar_init(sb + B_HR0, 1); mbar_init(sb + B_HR0 + 8, 1); mbar_init(sb + B_M0, 1); mbar_init(sb + B_SPF, 1); mbar_init(sb + B_EVS, 1);
      asm volatile("fence.mbarrier_init.release.cluster;" ::: "memory");
    }
    __syncwarp();
    while (clk() - c0 < XDELAY) {}
    if (total > 0) {
#pragma unroll 1
      for (int p = 0; p < 4; p++) {
        const int r = warp * 16 + p * 4 + rr;
        const uint4* px = (const uint4*)(P.x + (size_t)min(W.q0 * 128 + wg * 64 + r, NN - 1) * 256) + j;
        const uint32_t off = (r >> 3) * 4096 + (r & 7) * 128 + ((j ^ (r & 7)) << 4);
#pragma unroll
        for (int c = 0; c < 4; c++) cp_async16(sQ + off + c * 1024, px + c * 8);
        cp_commit();
      }
    }
    bar_sync(4, 384);
    if (wg == 1) bar_arrive(5, 256);

    if (total > 0) {
      {
        const bool own = (W.own >> wg) & 1;
        uint8_t* gh = (uint8_t*)g_h + (size_t)W.q0 * 65536 + wg * 32768;
#pragma unroll 1
        for (int p = 0; p < 4; p++) {
          const int r = warp * 16 + p * 4 + rr;
          const uint32_t off = (r >> 3) * 4096 + (r & 7) * 128 + ((j ^ (r & 7)) << 4);
          asm volatile("cp.async.wait_group 3;" ::: "memory");
          cp_commit();
          float f[32];
#pragma unroll
          for (int c = 0; c < 4; c++) {
            const uint4 v = lds128(sQ + off + c * 1024);
            f[c * 8 + 0] = bf_lo(v.x); f[c * 8 + 1] = bf_hi(v.x); f[c * 8 + 2] = bf_lo(v.y); f[c * 8 + 3] = bf_hi(v.y);
            f[c * 8 + 4] = bf_lo(v.z); f[c * 8 + 5] = bf_hi(v.z); f[c * 8 + 6] = bf_lo(v.w); f[c * 8 + 7] = bf_hi(v.w);
          }
          float s0 = 0.f, s1 = 0.f, s2 = 0.f, s3 = 0.f;
#pragma unroll
          for (int i = 0; i < 16; i++) { s0 += f[2 * i]; s1 += f[2 * i + 1]; s2 += f[2 * i] * f[2 * i]; s3 += f[2 * i + 1] * f[2 * i + 1]; }
          float sum = s0 + s1, ss = s2 + s3;
#pragma unroll
          for (int k = 1; k < 8; k *= 2) { sum += __shfl_xor_sync(0xffffffffu, sum, k); ss += __shfl_xor_sync(0xffffffffu, ss, k); }
          const float mean = sum * (1.0f / 256.0f);
          float var = ss * (1.0f / 256.0f) - mean * mean;
          if (__any_sync(0xffffffffu, !(mean * mean <= 16.f * var))) {
            s2 = s3 = 0.f;
#pragma unroll
            for (int i = 0; i < 16; i++) { s2 += (f[2 * i] - mean) * (f[2 * i] - mean); s3 += (f[2 * i + 1] - mean) * (f[2 * i + 1] - mean); }
            ss = s2 + s3;
#pragma unroll
            for (int k = 1; k < 8; k *= 2) ss += __shfl_xor_sync(0xffffffffu, ss, k);
            var = ss * (1.0f / 256.0f);
          }
          float rs;
          asm("rsqrt.approx.ftz.f32 %0, %1;" : "=f"(rs) : "f"(var + 1e-5f));
          if (W.q0 * 128 + wg * 64 + r >= NN) rs = 0.f;
          const float nb = -mean * rs;
#pragma unroll
          for (int c = 0; c < 4; c++) {
            uint4 h4 = make_uint4(pack_bf16(fmaf(f[c * 8], rs, nb), fmaf(f[c * 8 + 1], rs, nb)), pack_bf16(fmaf(f[c * 8 + 2], rs, nb), fmaf(f[c * 8 + 3], rs, nb)),
                                  pack_bf16(fmaf(f[c * 8 + 4], rs, nb), fmaf(f[c * 8 + 5], rs, nb)), pack_bf16(fmaf(f[c * 8 + 6], rs, nb), fmaf(f[c * 8 + 7], rs, nb)));
            sts128(sQ + off + c * 1024, h4);
            if (c == 3) {
              const float rk = rs * KS, e = fmaf(j == 7 ? nb - 0.5f * fmaf(f[31], rs, nb) : nb, KS, KC);
              h4 = make_uint4(pack_bf16(fmaf(f[24], rk, e), fmaf(f[25], rk, e)), pack_bf16(fmaf(f[26], rk, e), fmaf(f[27], rk, e)),
                              pack_bf16(fmaf(f[28], rk, e), fmaf(f[29], rk, e)), pack_bf16(fmaf(f[30], rk, e), j == 7 ? KC : fmaf(f[31], rk, e)));
            } else {
              h4 = make_uint4(hfma2(h4.x, KS2, KC2), hfma2(h4.y, KS2, KC2), hfma2(h4.z, KS2, KC2), hfma2(h4.w, KS2, KC2));
            }
            if (own) *(uint4*)(gh + off + c * 1024) = h4;
          }
        }
        __syncwarp();
        if (lane == 0) mbar_arrive(sb + B_EVH);
        fence_async_smem();
        bar_sync(1 + wg, 128);
      }
    }
    asm volatile("setmaxnreg.inc.sync.aligned.u32 %0;" :: "n"(CREG));
    STAMP(st0, wg, 1);

    float o[128];
    int qph = 0;
    auto release = [&](int stg) { if (lane == 0) mbar_arrive(sb + B_EMPTY + 8 * stg); };
    if (total == 0) {
#pragma unroll 1
      for (int i = 0; i < 32; i++) {
        const int r = i * 8 + wg * 4 + warp;
        cp_async16(sb + ((POS_M >> (r >> 6) * 4) & 15) * 32768 + sw_byte(r & 63, lane * 8), (const uint4*)P.wout + r * 32 + lane);
      }
    }
#pragma unroll 1
    for (int step = total > 0 ? -1 : -4; step < W.nloc; step++) {
      const bool isq = step < 0 && total > 0, isw = step < 0 && total == 0;
      if (isw) {
        const uint4* src = (const uint4*)(step < -2 ? P.wmsg : P.wv) + ((step & 1) * 128 + wg * 64 + warp) * 32 + lane;
        float cw[8] = {0.f, 0.f, 0.f, 0.f, 0.f, 0.f, 0.f, 0.f};
#pragma unroll 1
        for (int i = 0; i < 16; i++) cp_async16(sQ + sw_byte(i * 4 + warp, lane * 8), src + i * 128);
        cp_commit();
#pragma unroll
        for (int i = 0; i < 8; i++) {
          const uint4 v = __ldg((const uint4*)(step < -2 ? P.wmsg : P.wv) + (248 + i) * 32 + lane);
          const float k = i == 7 ? -1.0f / 4.5f : -0.5f / 4.5f;
          cw[0] += bf_lo(v.x) * k; cw[1] += bf_hi(v.x) * k; cw[2] += bf_lo(v.y) * k; cw[3] += bf_hi(v.y) * k;
          cw[4] += bf_lo(v.z) * k; cw[5] += bf_hi(v.z) * k; cw[6] += bf_lo(v.w) * k; cw[7] += bf_hi(v.w) * k;
        }
        asm volatile("cp.async.wait_group 0;" ::: "memory");
#pragma unroll 1
        for (int i = 0; i < 16; i++) {
          const uint32_t ad = sQ + sw_byte(i * 4 + warp, lane * 8);
          const uint4 v = lds128(ad);
          uint4 w4 = make_uint4(pack_bf16(bf_lo(v.x) + cw[0], bf_hi(v.x) + cw[1]), pack_bf16(bf_lo(v.y) + cw[2], bf_hi(v.y) + cw[3]),
                                pack_bf16(bf_lo(v.z) + cw[4], bf_hi(v.z) + cw[5]), pack_bf16(bf_lo(v.w) + cw[6], bf_hi(v.w) + cw[7]));
          if ((step & 1) * 128 + wg * 64 + i * 4 + warp == 255) w4 = make_uint4(0, 0, 0, 0);
          sts128(ad, w4);
        }
        fence_async_smem();
        bar_sync(7, 256);
      } else {
        if (!isq) { mbar_wait(sb + B_QFULL + 8 * wg, qph); qph ^= 1; }
        STAMP(st0 && step == 0, wg, 8);
        bar_sync(5 + wg, 256);
      }
#pragma unroll 1
      for (int c = 0; c < 4; c++) {
        if (isq || step == 0) mbar_wait(isq && c == 0 ? sb + B_M0 : sb + B_WF + 8 * c, !isq && total > 0);
        if (c == 1 && isq) bar_sync(5 + wg, 256);
        wg_fence();
        const uint64_t dA = desc_k(sb + SM_Q, wg * 2048 + c * 64), dW = desc_mn(sb, (((isq ? POS_M : posw) >> c * 4) & 15) * 2048);
        static_for<0, 4>([&](auto k) {
          if (k.value == 1) { if (isq && c == 0) mbar_wait(sb + B_WF, 0); wg_fence(); }
          wgmma_ss_n256_tb<k.value * 2, k.value * 512>(o, dA, dW, k.value > 0 ? 1 : c);
        });
        wg_commit();
        if ((c == 3 || (c == 0 && isq)) && !isw) bar_arrive(6 - wg, 256);
        if (c == 0 && isq) { wg_wait<0>(); if (!tail) release(0); }
        wg_wait<1>();
      }
      wg_wait<0>();
      reg_fence(o);
      if (!isq) {
        STAMP(st0 && step == 0, wg, 9);
        if (isw) bar_sync(1 + wg, 128); else if (lane == 0) mbar_arrive(sb + B_QEMPTY + 8 * wg);
        if (W.na0 > 0) mbar_wait(sb + B_HR0 + 8, 0);
        uint8_t* dw = (uint8_t*)(step < -2 ? g_Wmo : g_Wvo) + ((step & 1) * 2 + wg) * 32768 + warp * 8192 + g * 128;
        const int row0 = (W.loc0 + step) * 128 + wg * 64 + warp * 16;
        uint4* po = (uint4*)(P.out + (size_t)(row0 + g) * 256) + t;
        uint4 r[16];
#pragma unroll
        for (int u = 0; u < 8; u++) { r[2 * u] = ROW0(u); r[2 * u + 1] = ROW1(u); }
        if (isw) {
#pragma unroll
          for (int u = 0; u < 16; u++) *(uint4*)(dw + (u >> 2) * 1024 + ((((u & 2) * 2 + t) ^ g) << 4) + (u & 1) * 4096) = r[u];
        } else if (row0 < NN) {
#pragma unroll
          for (int u = 0; u < 16; u++) red_bf16x8(po + (u >> 1) * 4 + (u & 1) * 256, r[u]);
        }
        if (step == -1) { bar_sync(7, 256); if (threadIdx.x == 0) flag_release(F_W); __syncwarp(); STAMP(st0, wg, 3); }
        continue;
      }
      if (!tail) release(1);
      STAMP(st0, wg, 2);
      float c0 = (o[124] + (t == 3 ? 2.f : 1.f) * o[125]) * (-0.5f / 4.5f), c1 = (o[126] + (t == 3 ? 2.f : 1.f) * o[127]) * (-0.5f / 4.5f);
      c0 += __shfl_xor_sync(0xffffffffu, c0, 1); c1 += __shfl_xor_sync(0xffffffffu, c1, 1);
      c0 += __shfl_xor_sync(0xffffffffu, c0, 2); c1 += __shfl_xor_sync(0xffffffffu, c1, 2);
      float r0 = t == 3 ? 0.f : o[125], r1 = t == 3 ? 0.f : o[127], r2 = o[124], r3 = o[126];
#pragma unroll
      for (int i = 0; i < 31; i++) { r2 += o[4 * i]; r0 += o[4 * i + 1]; r3 += o[4 * i + 2]; r1 += o[4 * i + 3]; }
      r0 += r2; r1 += r3;
      r0 += __shfl_xor_sync(0xffffffffu, r0, 1); r1 += __shfl_xor_sync(0xffffffffu, r1, 1);
      r0 += __shfl_xor_sync(0xffffffffu, r0, 2); r1 += __shfl_xor_sync(0xffffffffu, r1, 2);
      r0 = fmaf(c0, -255.f, PSH / KC - r0); r1 = fmaf(c1, -255.f, PSH / KC - r1);
      const bool wide = !(fabsf(c0) <= SAFE_C / KS) || !(fabsf(c1) <= SAFE_C / KS);
      bar_sync(1 + wg, 128);
#pragma unroll
      for (int k = 0; k < 16; k++)
        stsm4(sQ + warp * 8192 + ((lane >> 3) & 1) * 4096 + (k >> 2) * 1024 + (lane & 7) * 128 + ((((k & 3) * 2 + (lane >> 4)) ^ (lane & 7)) << 4),
              pack_bf16(o[8 * k] + c0, o[8 * k + 1] + c0), pack_bf16(o[8 * k + 2] + c1, o[8 * k + 3] + c1),
              pack_bf16(o[8 * k + 4] + c0, k == 15 && t == 3 ? r0 : o[8 * k + 5] + c0), pack_bf16(o[8 * k + 6] + c1, k == 15 && t == 3 ? r1 : o[8 * k + 7] + c1));
      fence_async_smem();
      bar_sync(1 + wg, 128);
      STAMP(st0, wg, 3);

      float m0, m1;
      const int qh = tail ? 0 : wg, tl = W.role >> 2;
      int st = tail ? wg : 0, ph = 0;
      if (tail) { bar_sync(7, 256); if (wg == 0) { release(0); release(1); release(2); } }
      uint32_t qo = qh * 2048;
      const uint32_t ko = (2 - tl) * 2048, stop = 1 + tl + (uint32_t)P.zero;
      float l0, l1;
      auto row_sums = [&]() { l0 = __shfl_sync(0xffffffffu, o[125] + 0.f, lane | 3); l1 = __shfl_sync(0xffffffffu, o[127] + 0.f, lane | 3); };
#define PART(u) make_uint4(pack_bf16(o[8 * u] - l0, o[8 * u + 1] - l0), pack_bf16(o[8 * u + 2] - l1, o[8 * u + 3] - l1), \
                           pack_bf16(o[8 * u + 4] - l0, o[8 * u + 5] - l0), pack_bf16(o[8 * u + 6] - l1, o[8 * u + 7] - l1))
      auto stage = [&]() {
        row_sums();
#pragma unroll
        for (int u = 0; u < 16; u++) sts128(sb + 6 * 32768 + (u * 128 + tid) * 16, PART(u));
        fence_async_smem();
        __syncwarp();
        if (lane == 0) mbar_arrive(sb + B_EVP0 + 8 * wg);
      };
      bool unsafe = false;
#pragma unroll 1
      for (int seg = 0;; seg++) {
        const bool last = seg || n1 == 0;
        m0 = m1 = unsafe ? -INFINITY : 0.f;
        int first = 1;
        auto tile = [&](auto n_, bool endseg) {
          constexpr int N = n_.value;
          float s[N / 2]; uint32_t p[N / 4];
          if (N == 128 || !(first && seg)) { if (!mbar_try_wait(sb + B_FULL + 8 * st, ph)) mbar_wait(sb + B_FULL + 8 * st, ph); }
          bar_sync(5 + wg, 256);
          wg_fence();
          const uint64_t dQ = desc_k(sb + SM_Q, qo), dK = desc_k(sb, ko + st * 4096);
          qo += (uint32_t)P.zero;
          static_for<0, 16>([&](auto k) { constexpr int kk = (k.value + KROT) & 15, off = (kk >> 2) * 64 + (kk & 3) * 2; wgmma_qk<off, off>(s, dQ, dK, k.value > 0); });
          wg_commit();
          bar_arrive(6 - wg, 256);
          if (N == 112 && first && seg && wg == 1) { mbar_wait(sb + B_SPF, 0); stage(); }
          if (N == 112 && first && !seg) {
            float a0 = 0.f, a1 = 0.f, a2 = 0.f, a3 = 0.f;
#pragma unroll
            for (int i = 0; i < 32; i++) { a0 += o[4 * i] * o[4 * i]; a2 += o[4 * i + 1] * o[4 * i + 1]; a1 += o[4 * i + 2] * o[4 * i + 2]; a3 += o[4 * i + 3] * o[4 * i + 3]; }
            a0 += a2; a1 += a3;
            a0 += __shfl_xor_sync(0xffffffffu, a0, 1); a1 += __shfl_xor_sync(0xffffffffu, a1, 1);
            a0 += __shfl_xor_sync(0xffffffffu, a0, 2); a1 += __shfl_xor_sync(0xffffffffu, a1, 2);
            unsafe = __any_sync(0xffffffffu, bar_red_or(tail ? 7 : 1 + wg, tail ? 256 : 128, wide || !(a0 <= SAFE_N2 / (KS * KS)) || !(a1 <= SAFE_N2 / (KS * KS))));
            if (lane == 0) { asm volatile("st.shared.u8 [%0], %1;" :: "r"(sb + SM_UNSAFE + wg), "r"((uint32_t)unsafe) : "memory"); mbar_arrive(sb + B_EVQ); }
            m0 = m1 = unsafe ? -INFINITY : 0.f;
          }
          STAMP(N == 112 && first && !seg && st0, wg, 0);
          wg_wait<0>();
          reg_fence(s);
          if (endseg) { if (lane == 0) mbar_arrive(sb + B_QEMPTY + 8 * wg); }
          if (unsafe) {
            float a0 = fmaxf(s[0], s[1]), a1 = fmaxf(s[2], s[3]);
#pragma unroll
            for (int i = 1; i < N / 8; i++) { a0 = fmaxf(a0, fmaxf(s[4 * i], s[4 * i + 1])); a1 = fmaxf(a1, fmaxf(s[4 * i + 2], s[4 * i + 3])); }
            if (__any_sync(0xffffffffu, (a0 > m0 + TAU) || (a1 > m1 + TAU))) {
              a0 = fmaxf(a0, __shfl_xor_sync(0xffffffffu, a0, 1)); a1 = fmaxf(a1, __shfl_xor_sync(0xffffffffu, a1, 1));
              a0 = fmaxf(a0, __shfl_xor_sync(0xffffffffu, a0, 2)); a1 = fmaxf(a1, __shfl_xor_sync(0xffffffffu, a1, 2));
              const float x0 = ceilf(fmaxf(m0, a0)), x1 = ceilf(fmaxf(m1, a1)), sc0 = ex2(m0 - x0), sc1 = ex2(m1 - x1);
              m0 = x0; m1 = x1;
#pragma unroll
              for (int i = 0; i < 32; i++) { o[4 * i] *= sc0; o[4 * i + 1] *= sc0; o[4 * i + 2] *= sc1; o[4 * i + 3] *= sc1; }
            }
#pragma unroll
            for (int i = 0; i < N / 8; i++) { s[4 * i] -= m0; s[4 * i + 1] -= m0; s[4 * i + 2] -= m1; s[4 * i + 3] -= m1; }
          }
          auto pv = [&](auto k) { wgmma_rs_n256_tb<k.value * 512 + (63 << 16)>(o, p[4 * k.value], p[4 * k.value + 1], p[4 * k.value + 2], p[4 * k.value + 3], dK, k.value > 0 || N == 128 ? 1 : !first); };
#pragma unroll
          for (int i = 0; i < 16; i++) { p[i] = pack_bf16(ex2(s[2 * i]), ex2(s[2 * i + 1])); asm volatile("" : "+r"(p[i]) :: "memory"); }
          reg_fence(o);
          do bar_sync(5 + wg, 256); while (P.zero);
          wg_fence();
          static_for<0, 4>(pv);
          wg_commit();
#pragma unroll
          for (int i = 16; i < N / 4; i++) { p[i] = pack_bf16(ex2(s[2 * i]), ex2(s[2 * i + 1])); asm volatile("" : "+r"(p[i]) :: "memory"); }
          wg_fence();
          static_for<4, N / 16>(pv);
          wg_commit();
          bar_arrive(6 - wg, 256);
          if (N == 128) { wg_wait<1>(); if (endseg && last) { if (lane == 0) mbar_arrive(sb + B_HALF); } }
          wg_wait<0>();
          reg_fence(o); reg_fence(p);
          release(st);
          if (st) { st--; ph ^= 1; } else st = stop;
        };
#pragma unroll 1
        for (int left = tail ? 8 - wg : (seg ? W.nb1 : W.nb0); left > 0; left--) { tile(IC<112>{}, false); STAMP(first && !seg && st0, wg, 4); first = 0; }
#pragma unroll 1
        for (int left = tail ? 32 + wg : (seg ? W.na1 : W.na0); left > 0; left--) tile(IC<128>{}, left == 1);
        STAMP(st0 && last, wg, 6);
        if (last && fin && !(tail && wg == 1)) break;
        const int slot = last && !tail ? W.slotB : W.slotA;
        if (last && !tail && wg == 1) mbar_wait(sb + B_HR0, 0);
        if (!last) {
          mbar_wait(sb + B_QFULL + 8 * wg, qph); qph ^= 1;
          uint32_t u; asm volatile("ld.shared.u8 %0, [%1];" : "=r"(u) : "r"(sb + SM_UNSAFE + wg) : "memory");
          unsafe = __any_sync(0xffffffffu, u != 0);
          mbar_wait(sb + B_FULL + 8 * st, ph);
        }
        if (t == 3) {
          float2* ml = g_ml + slot * 128 + wg * 64 + warp * 16 + g;
          ml[0] = make_float2(m0, o[125] + 0.f); ml[8] = make_float2(m1, o[127] + 0.f);
        }
        if (!last && wg == 0) stage();
        if (last) {
          row_sums();
          uint4* dst = g_part + (size_t)slot * 4096 + wg * 2048 + tid;
#pragma unroll
          for (int u = 0; u < 16; u++) dst[u * 128] = PART(u);
          __syncwarp();
          if (lane == 0) mbar_arrive(sb + B_EVP0 + 16 + 8 * wg);
          STAMP(st0, wg, 7);
          break;
        }
      }

      if (fin) {
        if (tail && wg == 1) break;
        row_sums();
        const int rl = wg * 64 + warp * 16 + g;
        uint32_t a[64];
#pragma unroll
        for (int i = 0; i < 64; i++) a[i] = pack_bf16(o[2 * i] - (i & 1 ? l1 : l0), o[2 * i + 1] - (i & 1 ? l1 : l0));
        reg_fence(a);
        {
          float2 e0, e1;
          mbar_wait(sb + B_QFULL + 8 * wg, qph);
          asm volatile("ld.shared.v2.f32 {%0,%1}, [%2];" : "=f"(e0.x), "=f"(e0.y) : "r"(sb + SM_ML + rl * 8) : "memory");
          asm volatile("ld.shared.v2.f32 {%0,%1}, [%2];" : "=f"(e1.x), "=f"(e1.y) : "r"(sb + SM_ML + rl * 8 + 64) : "memory");
          STAMP(st0, wg, 7);
          uint4 v[16];
#pragma unroll
          for (int u = 0; u < 16; u++) v[u] = lds128(sQ + (u * 128 + tid) * 16);
          uint32_t fb0 = 0x3f803f80u, fb1 = 0x3f803f80u;
          const float s0 = l0 + e0.y, s1 = l1 + e1.y;
          if (__any_sync(0xffffffffu, m0 != e0.x || m1 != e1.x || !(fmaxf(s0, s1) < 0x1p40f) || !(fminf(s0, s1) > 0x1p-40f))) {
            const float x0 = fmaxf(m0, e0.x), x1 = fmaxf(m1, e1.x);
            const float d0 = fmaxf(m0 - x0, -1000.f), d1 = fmaxf(m1 - x1, -1000.f), f0 = fmaxf(e0.x - x0, -1000.f), f1 = fmaxf(e1.x - x1, -1000.f);
            l0 = l0 * ex2(d0) + e0.y * ex2(f0); l1 = l1 * ex2(d1) + e1.y * ex2(f1);
            const int E0 = fexp(l0), E1 = fexp(l1);
            const uint32_t fa0 = pow2_bf2((int)d0 - E0), fa1 = pow2_bf2((int)d1 - E1);
            fb0 = pow2_bf2((int)f0 - E0); fb1 = pow2_bf2((int)f1 - E1);
            l0 = __uint_as_float(__float_as_uint(l0) - (E0 << 23)); l1 = __uint_as_float(__float_as_uint(l1) - (E1 << 23));
#pragma unroll
            for (int i = 0; i < 32; i++) { a[2 * i] = hmul2(a[2 * i], fa0); a[2 * i + 1] = hmul2(a[2 * i + 1], fa1); }
          } else { l0 = s0; l1 = s1; }
#pragma unroll
          for (int u = 0; u < 16; u++) {
            a[4 * u] = hfma2(v[u].x, fb0, a[4 * u]); a[4 * u + 1] = hfma2(v[u].y, fb1, a[4 * u + 1]);
            a[4 * u + 2] = hfma2(v[u].z, fb0, a[4 * u + 2]); a[4 * u + 3] = hfma2(v[u].w, fb1, a[4 * u + 3]);
          }
        }
        float fs0, fs1;
        asm("rcp.approx.ftz.f32 %0, %1;" : "=f"(fs0) : "f"(l0 * (KS / KC))); asm("rcp.approx.ftz.f32 %0, %1;" : "=f"(fs1) : "f"(l1 * (KS / KC)));
        STAMP(st0, wg, 8);
        reg_fence(a);
        bar_sync(5 + wg, 256);
        uint64_t dW[4];
        float y0[64], y1[64];
        auto half0 = [&](auto u_) {
          constexpr int u = u_.value;
          if (u % 4 == 0) { mbar_wait(sb + B_WF + 2 * u, 1); wg_fence(); dW[u / 4] = desc_mn(sb, ((posw >> u) & 15) * 2048); }
          wgmma_rs_n128_tb<(u & 3) * 512>(y0, a[4 * u], a[4 * u + 1], a[4 * u + 2], a[4 * u + 3], dW[u / 4], u != 0);
        };
        auto half1 = [&](auto u_) {
          constexpr int u = u_.value;
          wgmma_rs_n128_tb<(u & 3) * 512 + 128>(y1, a[4 * u], a[4 * u + 1], a[4 * u + 2], a[4 * u + 3], dW[u / 4], u != 0);
        };
        const bool wr = W.q0 * 128 + wg * 64 + warp * 16 < NN;
        uint4* po = (uint4*)(P.out + (size_t)(W.q0 * 128 + rl) * 256) + t;
        auto emit = [&](const float* y, uint4* dst) {
          if (wr) {
            red_bf16x8(dst, make_uint4(pack_bf16(y[0] * fs0, y[1] * fs0), pack_bf16(y[4] * fs0, y[5] * fs0), pack_bf16(y[8] * fs0, y[9] * fs0), pack_bf16(y[12] * fs0, y[13] * fs0)));
            red_bf16x8(dst + 8 * 32, make_uint4(pack_bf16(y[2] * fs1, y[3] * fs1), pack_bf16(y[6] * fs1, y[7] * fs1), pack_bf16(y[10] * fs1, y[11] * fs1), pack_bf16(y[14] * fs1, y[15] * fs1)));
          }
          wg_fence();
        };
        static_for<0, 16>(half0);
        wg_commit();
        static_for<0, 4>(half1);
        wg_commit();
        wg_wait<1>();
        reg_fence(y0);
        emit(y0, po); static_for<4, 8>(half1);
        emit(y0 + 16, po + 4); static_for<8, 12>(half1);
        emit(y0 + 32, po + 8); static_for<12, 16>(half1);
        wg_commit();
        bar_arrive(6 - wg, 256);
        emit(y0 + 48, po + 12);
        wg_wait<0>();
        reg_fence(a); reg_fence(y1);
        STAMP(st0, wg, 9);
#pragma unroll
        for (int u = 0; u < 4; u++) emit(y1 + 16 * u, po + 16 + 4 * u);
        break;
      }
    }
    STAMP(st0, wg, 11);
    DUMP(st0, wg, 0, 16);
  }
}

}

extern "C" void kernel_launch(void* const* d_in, const int* in_sizes, int n_in, void* d_out, int out_size) {
  Params P;
  P.x = (const __nv_bfloat16*)d_in[0];
  P.src = (const int*)d_in[1];
  P.dst = (const int*)d_in[2];
  P.dinv = (const __nv_bfloat16*)d_in[3];
  P.wmsg = (const __nv_bfloat16*)d_in[4];
  P.wq = (const __nv_bfloat16*)d_in[5];
  P.wk = (const __nv_bfloat16*)d_in[6];
  P.wv = (const __nv_bfloat16*)d_in[7];
  P.wout = (const __nv_bfloat16*)d_in[8];
  P.out = (__nv_bfloat16*)d_out;
  P.zero = 0;
  for (int c = 0; c < NCTA; c++) P.w[c] = make_work(c);
  static void* scr = nullptr;
  if (!scr) {
    cudaFuncSetAttribute(gps_kernel, cudaFuncAttributeMaxDynamicSharedMemorySize, SMEM_BYTES);
    cudaGetSymbolAddress(&scr, g_scr);
  }
  P.s = (Scratch*)scr;
  P.h = (uint4*)(((uintptr_t)P.s->h + 4095) & ~(uintptr_t)4095);
  if (((uintptr_t)P.h >> 32) != (((uintptr_t)(P.h + NQT * 4096) - 1) >> 32)) P.h += NQT * 4096;
  gps_kernel<<<NCTA, 384, SMEM_BYTES>>>(P);
}
```

```cpp
#include <cuda_runtime.h>
#include <cuda_bf16.h>
#include <stdint.h>
#include <stddef.h>
#include <type_traits>
#define FB 5
#define MB 5
#define GSTART 18000
#define HINT 7
#define RELF 0
#define DBG 0
#define OUTW red_bf16x8
#define PACE 64
#define GPAUSE 120000
#define XDELAY 200
#define CREG 224
#define BACKOFF 1000

namespace {

constexpr int NN = 10000;
constexpr int NE = 160000;
constexpr int NQT = 79;
constexpr int NCTA = 132;
constexpr int CAP = 64;
constexpr int CAPS = 64;
constexpr int NHSIG = 105;
constexpr uint32_t WCH_B = 32768;
constexpr int NGW = (NCTA - 1) * 3;
constexpr float TAU = 16.0f;
constexpr float SAFE_N2 = 36.0f, SAFE_C = 0.6f;
#define KOFF 3
#define PSH -8.0f
#define KROT 15
constexpr float US = 256.0f, UB = 4095.0f;
constexpr float KS = 0.25f, KC = KOFF * KS;
constexpr uint32_t KS2 = 0x3e803e80u, KC2 = KOFF == 2 ? 0x3f003f00u : (KOFF == 1 ? 0x3e803e80u : 0x3f403f40u);

constexpr int NAGG = 4;
constexpr int NRND = (NN + NGW - 1) / NGW;
constexpr int NSLOT = 105;
constexpr int F_EPOCH = 0, F_H = 1, F_M = 4  , LN_ = 32;
constexpr int F_BIN = LN_, F_W = 2 * LN_, F_OVF = 3 * LN_  , F_QP = 5 * LN_, F_AGG = F_QP + NQT * LN_,
              F_PART = F_AGG + NAGG * LN_, F_END = F_PART + NSLOT * LN_;

struct Scratch {
  uint32_t flag[F_END];
  alignas(4096) uint4 M[8192];
  uint4 Wvo[8192], Wmo[8192];
  float2 ml[NSLOT * 128];
  uint32_t unsafe[96];
  int cnt[NN + 32];
  float2 stat[NQT * 128];
  alignas(4096) uint4 h[NQT * 4096];
  uint4 u[2 * NN * 32 + 32];
  uint4 qp[NQT * 4096];
  uint4 agg[NQT * 4096];
  uint4 part[NSLOT * 4096];
  int bin[(NRND + 2) * NGW * CAPS];
  int2 ovf[NE];
};
static_assert(offsetof(Scratch, h) % 128 == 0, "alignment");
#define SCR_ALIGN (2u << 20)
#define SCR_OFS 0
__device__ uint4 g_scr[(sizeof(Scratch) + SCR_ALIGN + SCR_OFS) / 16];
struct alignas(16) Work { short k0, k1; signed char q0, q1, nb0, na0, nb1, na1, slotA, slotB, loc0, nloc, own, role; };
constexpr int R_FIN = 1, R_PUB = 2, R_TAIL = 4;
struct Params {
  const __nv_bfloat16 *x, *wq, *wk;
  Scratch* s;
  uint4* u;
  __nv_bfloat16* out;
  const __nv_bfloat16 *wout, *wmsg, *wv, *dinv;
  const int *src, *dst;
  long long zero;
  Work w[NCTA];
};
constexpr int NSERV = NQT - 52;
inline Work make_work(int c) {
  Work w;
  const int gi = c / 5, r = c % 5, q = gi * 3;
  const bool helper = r & 1, mid = r == 2;
  w.q0 = helper ? q + 1 : q + (r >> 1);
  const int hb1 = (15 - MB) / 2, hb3 = 15 - MB - hb1;
  w.nb0 = helper ? (r == 1 ? hb1 : hb3) : (mid ? MB : FB);
  w.na0 = (helper ? 16 : 48) - w.nb0;
  w.k0 = helper ? (48 * 8 - MB) + (r >> 1) * (16 * 8 - hb1) : 0;
  w.q1 = q + (r & 2);
  w.k1 = 48 * 8 - FB;
  w.nb1 = helper ? 7 - FB : 0;
  w.na1 = helper ? 31 - w.nb1 : 0;
  w.slotA = 4 * gi + (helper ? r - 1 : (mid ? 0 : (r >> 1) + 1));
  w.slotB = helper ? 4 * gi + r : (mid ? 4 * gi + 2 : -1);
  w.loc0 = NSERV + gi * 2 + (r >> 1);
  w.nloc = helper;
  w.own = helper ? (r + 1) >> 1 : (mid ? 0 : 3);
  w.role = helper ? 0 : (mid ? R_FIN : R_FIN | R_PUB);
  if (c == 130) { w.nb0 = 15; w.na0 = 65; w.slotA = NSLOT - 1; w.own = 1; w.role = R_FIN | R_TAIL; }
  if (c == 131) { w.nb0 = w.na0 = w.nb1 = w.na1 = 0; w.loc0 = 0; w.nloc = NSERV; w.own = 0; }
  return w;
}
#define g_flag P.s->flag
#define g_M P.s->M
#define g_Wvo P.s->Wvo
#define g_Wmo P.s->Wmo
#define g_ml P.s->ml
#define g_unsafe P.s->unsafe
#define g_cnt P.s->cnt
#define g_h P.s->h
#define g_u P.u
#define g_stat P.s->stat
#define g_qp P.s->qp
#define g_agg P.s->agg
#define g_part P.s->part
#define g_bin P.s->bin
#define g_ovf P.s->ovf

__device__ __forceinline__ uint32_t smem_u32(const void* p) { return (uint32_t)__cvta_generic_to_shared(p); }
__device__ __forceinline__ void mbar_init(uint32_t bar, uint32_t cnt) { asm volatile("mbarrier.init.shared::cta.b64 [%0], %1;" :: "r"(bar), "r"(cnt) : "memory"); }
__device__ __forceinline__ void mbar_arrive(uint32_t bar) { asm volatile("mbarrier.arrive.shared::cta.b64 _, [%0];" :: "r"(bar) : "memory"); }
__device__ __forceinline__ void mbar_expect_tx(uint32_t bar, uint32_t bytes) { asm volatile("mbarrier.arrive.expect_tx.shared::cta.b64 _, [%0], %1;" :: "r"(bar), "r"(bytes) : "memory"); }
__device__ __forceinline__ bool mbar_try_wait(uint32_t bar, uint32_t parity) {
  uint32_t ok;
  asm volatile("{\n.reg .pred p;\nmbarrier.try_wait.parity.shared::cta.b64 p, [%1], %2;\nselp.b32 %0, 1, 0, p;\n}\n" : "=r"(ok) : "r"(bar), "r"(parity) : "memory");
  return ok;
}
__device__ __forceinline__ bool mbar_try_wait_nb(uint32_t bar, uint32_t parity) {
  uint32_t ok;
  asm volatile("{\n.reg .pred p;\nmbarrier.test_wait.parity.shared::cta.b64 p, [%1], %2;\nselp.b32 %0, 1, 0, p;\n}\n" : "=r"(ok) : "r"(bar), "r"(parity) : "memory");
  return ok;
}
__device__ __forceinline__ void mbar_wait(uint32_t bar, uint32_t parity) {
#pragma unroll 1
  for (uint32_t it = 0; it < (1u << 25); it++) if (mbar_try_wait(bar, parity)) break;
}
__device__ __forceinline__ void bulk_s2g(void* dst, uint32_t src, uint32_t bytes) {
  asm volatile("cp.async.bulk.global.shared::cta.bulk_group [%0], [%1], %2;" :: "l"(dst), "r"(src), "r"(bytes) : "memory");
}
__device__ __forceinline__ void bulk_commit() { asm volatile("cp.async.bulk.commit_group;" ::: "memory"); }
__device__ __forceinline__ void bulk_wait_read() { asm volatile("cp.async.bulk.wait_group.read 0;" ::: "memory"); }
__device__ __forceinline__ void bulk_wait_all() { asm volatile("cp.async.bulk.wait_group 0;" ::: "memory"); }
__device__ __forceinline__ bool bar_red_or(int id, int cnt, bool c) {
  uint32_t r;
  asm volatile("{\n.reg .pred p, q;\nsetp.ne.b32 q, %3, 0;\nbar.red.or.pred p, %1, %2, q;\nselp.b32 %0, 1, 0, p;\n}\n"
               : "=r"(r) : "r"(id), "r"(cnt), "r"((uint32_t)c) : "memory");
  return r != 0;
}
template <class T> __device__ __forceinline__ T* pofs(const void* base, uint32_t off) {
  asm volatile("" : "+r"(off));
  return (T*)((uint8_t*)base + off);
}
__device__ __forceinline__ const void* addr64(uint32_t lo, uint32_t hi) { uint64_t a; asm("mov.b64 %0, {%1, %2};" : "=l"(a) : "r"(lo), "r"(hi)); return (const void*)a; }
__device__ __forceinline__ uint4 ldcg_v(const void* a) {
  uint4 v;
  asm volatile("ld.volatile.global.v4.u32 {%0,%1,%2,%3}, [%4];" : "=r"(v.x), "=r"(v.y), "=r"(v.z), "=r"(v.w) : "l"(a) : "memory");
  return v;
}
__device__ __forceinline__ uint4 ldcs_v(const void* a) {
  uint4 v;
  asm volatile("ld.global.cs.v4.u32 {%0,%1,%2,%3}, [%4];" : "=r"(v.x), "=r"(v.y), "=r"(v.z), "=r"(v.w) : "l"(a) : "memory");
  return v;
}
__device__ __forceinline__ void prefetch_l2(const void* a, uint32_t bytes) { asm volatile("cp.async.bulk.prefetch.L2.global [%0], %1;" :: "l"(a), "r"(bytes) : "memory"); }
__device__ __forceinline__ void ldcg_if(uint4& v, const void* a, bool c) {
  asm volatile("{\n.reg .pred p;\nsetp.ne.b32 p, %5, 0;\n@p ld.volatile.global.v4.u32 {%0,%1,%2,%3}, [%4];\n}\n"
               : "+r"(v.x), "+r"(v.y), "+r"(v.z), "+r"(v.w) : "l"(a), "r"((uint32_t)c) : "memory");
}
__device__ __forceinline__ void cp_async16(uint32_t dst, const void* src) {
  asm volatile("cp.async.cg.shared.global [%0], [%1], 16;" :: "r"(dst), "l"(src) : "memory");
}
__device__ __forceinline__ void red_bf16x8(void* a, uint4 v) {
  asm volatile("red.global.add.noftz.v4.bf16x2 [%0], {%1,%2,%3,%4};" :: "l"(a), "r"(v.x), "r"(v.y), "r"(v.z), "r"(v.w) : "memory");
}
__device__ __forceinline__ uint32_t clk() { uint32_t c; asm volatile("mov.u32 %0, %%clock;" : "=r"(c) :: "memory"); return c; }
__device__ __forceinline__ void stsm4(uint32_t a, uint32_t r0, uint32_t r1, uint32_t r2, uint32_t r3) {
  asm volatile("stmatrix.sync.aligned.m8n8.x4.shared.b16 [%0], {%1,%2,%3,%4};" :: "r"(a), "r"(r0), "r"(r1), "r"(r2), "r"(r3) : "memory");
}
__device__ __forceinline__ uint32_t lds32(uint32_t a) { uint32_t v; asm volatile("ld.shared.u32 %0, [%1];" : "=r"(v) : "r"(a) : "memory"); return v; }
__device__ __forceinline__ void cp_commit() { asm volatile("cp.async.commit_group;" ::: "memory"); }
__device__ __forceinline__ uint32_t hmul2(uint32_t a, uint32_t b) { uint32_t d; asm("mul.rn.bf16x2 %0, %1, %2;" : "=r"(d) : "r"(a), "r"(b)); return d; }
__device__ __forceinline__ uint32_t hfma2(uint32_t a, uint32_t b, uint32_t c) { uint32_t d; asm("fma.rn.bf16x2 %0, %1, %2, %3;" : "=r"(d) : "r"(a), "r"(b), "r"(c)); return d; }
__device__ __forceinline__ uint32_t pow2_bf2(int n) { return (uint32_t)max(n + 127, 0) * 0x00800080u; }
__device__ __forceinline__ int fexp(float x) { return (int)(__float_as_uint(x) >> 23) - 127; }
__device__ __forceinline__ void bulk_g2s(uint32_t dst, const void* src, uint32_t bytes, uint32_t bar) {
  asm volatile("cp.async.bulk.shared::cta.global.mbarrier::complete_tx::bytes [%0], [%1], %2, [%3];"
    :: "r"(dst), "l"(src), "r"(bytes), "r"(bar) : "memory");
}
__device__ __forceinline__ void bulk_g2s_last(uint32_t dst, const void* src, uint32_t bytes, uint32_t bar) {
  asm volatile("{\n.reg .b64 p;\ncreatepolicy.fractional.L2::evict_first.b64 p;\n"
    "cp.async.bulk.shared::cta.global.mbarrier::complete_tx::bytes.L2::cache_hint [%0], [%1], %2, [%3], p;\n}\n"
    :: "r"(dst), "l"(src), "r"(bytes), "r"(bar) : "memory");
}
__device__ __forceinline__ void wg_fence() { asm volatile("wgmma.fence.sync.aligned;" ::: "memory"); }
__device__ __forceinline__ void wg_commit() { asm volatile("wgmma.commit_group.sync.aligned;" ::: "memory"); }
template<int N> __device__ __forceinline__ void wg_wait() { asm volatile("wgmma.wait_group.sync.aligned %0;" :: "n"(N) : "memory"); }
__device__ __forceinline__ void bar_sync(int id, int cnt) { asm volatile("bar.sync %0, %1;" :: "r"(id), "r"(cnt) : "memory"); }
__device__ __forceinline__ void fence_async_smem() { asm volatile("fence.proxy.async.shared::cta;" ::: "memory"); }
__device__ __forceinline__ void fence_async_gmem() { asm volatile("fence.proxy.async.global;" ::: "memory"); }
__device__ __forceinline__ void bar_arrive(int id, int cnt) { asm volatile("bar.arrive %0, %1;" :: "r"(id), "r"(cnt) : "memory"); }
__device__ __forceinline__ void red_release(uint32_t* p) { asm volatile("red.release.gpu.global.add.u32 [%0], 1;" :: "l"(p) : "memory"); }
__device__ __forceinline__ void red_release_w(uint32_t* p) {
  __syncwarp();
  asm volatile("{\n.reg .pred q;\n.reg .b32 l;\nmov.u32 l, %%laneid;\nsetp.eq.u32 q, l, 0;\n@q fence.release.gpu;\n@q red.relaxed.gpu.global.add.u32 [%0], 1;\n}\n" :: "l"(p) : "memory");
}
__device__ __forceinline__ void mbar_wait_w(uint32_t bar, uint32_t parity) {
#pragma unroll 1
  for (uint32_t it = 0; it < (1u << 25); it++) if (__all_sync(0xffffffffu, mbar_try_wait(bar, parity))) break;
}
#define flag_release_w(f) red_release_w(g_flag + (f))
#define flag_wait_w(f, target) poll_acquire_w(g_flag + (f), target)
#define flag_release(f) red_release(g_flag + (f))
__device__ __forceinline__ uint32_t ld_relaxed(const uint32_t* p) {
  uint32_t v; asm volatile("ld.relaxed.gpu.global.u32 %0, [%1];" : "=r"(v) : "l"(p) : "memory"); return v;
}
#define flag_wait(f, target) poll_acquire(g_flag + (f), target)
__device__ __forceinline__ void poll_acquire(const uint32_t* p, uint32_t target) {
#pragma unroll 1
  for (uint32_t it = 0; it < (1u << 23); it++) if ((int)(ld_relaxed(p) - target) >= 0) break;
  asm volatile("fence.acquire.gpu;" ::: "memory");
}
__device__ __forceinline__ void poll_acquire_w(const uint32_t* p, uint32_t target) {
#pragma unroll 1
  for (uint32_t it = 0; it < (1u << 23); it++) {
    if (__all_sync(0xffffffffu, (int)(ld_relaxed(p) - target) >= 0)) break;
    if (BACKOFF) __nanosleep(BACKOFF);
  }
  asm volatile("fence.acquire.gpu;" ::: "memory");
}
template<int N> __device__ __forceinline__ void reg_fence(float (&d)[N]) {
#pragma unroll
  for (int i = 0; i < N; i++) asm volatile("" : "+f"(d[i]) :: "memory");
}
template<int N> __device__ __forceinline__ void reg_fence(uint32_t (&d)[N]) {
#pragma unroll
  for (int i = 0; i < N; i++) asm volatile("" : "+r"(d[i]) :: "memory");
}
__device__ __forceinline__ float ex2(float x) { float y; asm("ex2.approx.ftz.f32 %0, %1;" : "=f"(y) : "f"(x)); return y; }
__device__ __forceinline__ uint32_t pack_bf16(float lo, float hi) { uint32_t r; asm("cvt.rn.bf16x2.f32 %0, %1, %2;" : "=r"(r) : "f"(hi), "f"(lo)); return r; }
__device__ __forceinline__ float bf_lo(uint32_t w) { return __uint_as_float(w << 16); }
__device__ __forceinline__ float bf_hi(uint32_t w) { return __uint_as_float(w & 0xffff0000u); }
__device__ __forceinline__ uint64_t desc_k(uint32_t addr, uint32_t add) { return (uint64_t)((((addr & 0x3FFFF) >> 4) | (1u << 16)) + add) | (0x40000100ull << 32); }
__device__ __forceinline__ uint64_t desc_mn(uint32_t addr, uint32_t add) { return (uint64_t)((((addr & 0x3FFFF) >> 4) | ((1024u >> 4) << 16)) + add) | (0x40000100ull << 32); }
__device__ __forceinline__ void sts128(uint32_t a, uint4 v) { asm volatile("st.shared.v4.u32 [%0], {%1,%2,%3,%4};" :: "r"(a), "r"(v.x), "r"(v.y), "r"(v.z), "r"(v.w) : "memory"); }
__device__ __forceinline__ uint4 lds128(uint32_t a) { uint4 v; asm volatile("ld.shared.v4.u32 {%0,%1,%2,%3}, [%4];" : "=r"(v.x), "=r"(v.y), "=r"(v.z), "=r"(v.w) : "r"(a) : "memory"); return v; }
__device__ __forceinline__ void mma16816(float (&c)[4], uint32_t a0, uint32_t a1, uint32_t a2, uint32_t a3, uint32_t b0, uint32_t b1) {
  asm volatile("mma.sync.aligned.m16n8k16.row.col.f32.bf16.bf16.f32 {%0,%1,%2,%3}, {%4,%5,%6,%7}, {%8,%9}, {%0,%1,%2,%3};"
    : "+f"(c[0]), "+f"(c[1]), "+f"(c[2]), "+f"(c[3]) : "r"(a0), "r"(a1), "r"(a2), "r"(a3), "r"(b0), "r"(b1));
}
__device__ __forceinline__ uint32_t sw_byte(int r, int c) {
  return (uint32_t)((r >> 3) * 4096 + (c >> 6) * 1024 + (r & 7) * 128 + ((((c >> 3) & 7) ^ (r & 7)) << 4) + (c & 7) * 2);
}
__device__ __forceinline__ int cta_id() { int c; asm volatile("mov.u32 %0, %%ctaid.x;" : "=r"(c)); return c; }
__device__ __forceinline__ bool tid_is(int v) { int t; asm volatile("mov.u32 %0, %%tid.x;" : "=r"(t)); return t == v; }
#define STAMP(cond, who, i)
#define CSTAMP(cond, who, i)
#define DUMP(cond, who, i0, i1)
#define SSTAMP(i)

template <int OA, int OB> __device__ __forceinline__ void wgmma_ss_n256_tb(float (&d)[128], uint64_t da, uint64_t db, int scale_d) {
  asm volatile("{\n.reg .pred p;\n.reg .b64 a, b;\nsetp.ne.b32 p, %130, 0;\nadd.s64 a, %128, %131;\nadd.s64 b, %129, %132;\n"
    "wgmma.mma_async.sync.aligned.m64n256k16.f32.bf16.bf16 "
    "{%0, %1, %2, %3, %4, %5, %6, %7, %8, %9, %10, %11, %12, %13, %14, %15, %16, %17, %18, %19, %20, %21, %22, %23, %24, %25, %26, %27, %28, %29, %30, %31, %32, %33, %34, %35, %36, %37, %38, %39, %40, %41, %42, %43, %44, %45, %46, %47, %48, %49, %50, %51, %52, %53, %54, %55, %56, %57, %58, %59, %60, %61, %62, %63, %64, %65, %66, %67, %68, %69, %70, %71, %72, %73, %74, %75, %76, %77, %78, %79, %80, %81, %82, %83, %84, %85, %86, %87, %88, %89, %90, %91, %92, %93, %94, %95, %96, %97, %98, %99, %100, %101, %102, %103, %104, %105, %106, %107, %108, %109, %110, %111, %112, %113, %114, %115, %116, %117, %118, %119, %120, %121, %122, %123, %124, %125, %126, %127}, "
    "a, b, p, 1, 1, 0, 1;\n}\n"
    : "+f"(d[0]), "+f"(d[1]), "+f"(d[2]), "+f"(d[3]), "+f"(d[4]), "+f"(d[5]), "+f"(d[6]), "+f"(d[7]), "+f"(d[8]), "+f"(d[9]), "+f"(d[10]), "+f"(d[11]), "+f"(d[12]), "+f"(d[13]), "+f"(d[14]), "+f"(d[15]), "+f"(d[16]), "+f"(d[17]), "+f"(d[18]), "+f"(d[19]), "+f"(d[20]), "+f"(d[21]), "+f"(d[22]), "+f"(d[23]), "+f"(d[24]), "+f"(d[25]), "+f"(d[26]), "+f"(d[27]), "+f"(d[28]), "+f"(d[29]), "+f"(d[30]), "+f"(d[31]), "+f"(d[32]), "+f"(d[33]), "+f"(d[34]), "+f"(d[35]), "+f"(d[36]), "+f"(d[37]), "+f"(d[38]), "+f"(d[39]), "+f"(d[40]), "+f"(d[41]), "+f"(d[42]), "+f"(d[43]), "+f"(d[44]), "+f"(d[45]), "+f"(d[46]), "+f"(d[47]), "+f"(d[48]), "+f"(d[49]), "+f"(d[50]), "+f"(d[51]), "+f"(d[52]), "+f"(d[53]), "+f"(d[54]), "+f"(d[55]), "+f"(d[56]), "+f"(d[57]), "+f"(d[58]), "+f"(d[59]), "+f"(d[60]), "+f"(d[61]), "+f"(d[62]), "+f"(d[63]), "+f"(d[64]), "+f"(d[65]), "+f"(d[66]), "+f"(d[67]), "+f"(d[68]), "+f"(d[69]), "+f"(d[70]), "+f"(d[71]), "+f"(d[72]), "+f"(d[73]), "+f"(d[74]), "+f"(d[75]), "+f"(d[76]), "+f"(d[77]), "+f"(d[78]), "+f"(d[79]), "+f"(d[80]), "+f"(d[81]), "+f"(d[82]), "+f"(d[83]), "+f"(d[84]), "+f"(d[85]), "+f"(d[86]), "+f"(d[87]), "+f"(d[88]), "+f"(d[89]), "+f"(d[90]), "+f"(d[91]), "+f"(d[92]), "+f"(d[93]), "+f"(d[94]), "+f"(d[95]), "+f"(d[96]), "+f"(d[97]), "+f"(d[98]), "+f"(d[99]), "+f"(d[100]), "+f"(d[101]), "+f"(d[102]), "+f"(d[103]), "+f"(d[104]), "+f"(d[105]), "+f"(d[106]), "+f"(d[107]), "+f"(d[108]), "+f"(d[109]), "+f"(d[110]), "+f"(d[111]), "+f"(d[112]), "+f"(d[113]), "+f"(d[114]), "+f"(d[115]), "+f"(d[116]), "+f"(d[117]), "+f"(d[118]), "+f"(d[119]), "+f"(d[120]), "+f"(d[121]), "+f"(d[122]), "+f"(d[123]), "+f"(d[124]), "+f"(d[125]), "+f"(d[126]), "+f"(d[127])
    : "l"(da), "l"(db), "r"(scale_d), "n"(OA), "n"(OB));
}
template <int OA, int OB> __device__ __forceinline__ void wgmma_qk(float (&d)[64], uint64_t da, uint64_t db, int scale_d) {
  asm volatile("{\n.reg .pred p;\n.reg .b64 a, b;\nsetp.ne.b32 p, %66, 0;\nadd.s64 a, %64, %67;\nadd.s64 b, %65, %68;\n"
    "wgmma.mma_async.sync.aligned.m64n128k16.f32.bf16.bf16 "
    "{%0, %1, %2, %3, %4, %5, %6, %7, %8, %9, %10, %11, %12, %13, %14, %15, %16, %17, %18, %19, %20, %21, %22, %23, %24, %25, %26, %27, %28, %29, %30, %31, %32, %33, %34, %35, %36, %37, %38, %39, %40, %41, %42, %43, %44, %45, %46, %47, %48, %49, %50, %51, %52, %53, %54, %55, %56, %57, %58, %59, %60, %61, %62, %63}, "
    "a, b, p, 1, 1, 0, 0;\n}\n"
    : "+f"(d[0]), "+f"(d[1]), "+f"(d[2]), "+f"(d[3]), "+f"(d[4]), "+f"(d[5]), "+f"(d[6]), "+f"(d[7]), "+f"(d[8]), "+f"(d[9]), "+f"(d[10]), "+f"(d[11]), "+f"(d[12]), "+f"(d[13]), "+f"(d[14]), "+f"(d[15]), "+f"(d[16]), "+f"(d[17]), "+f"(d[18]), "+f"(d[19]), "+f"(d[20]), "+f"(d[21]), "+f"(d[22]), "+f"(d[23]), "+f"(d[24]), "+f"(d[25]), "+f"(d[26]), "+f"(d[27]), "+f"(d[28]), "+f"(d[29]), "+f"(d[30]), "+f"(d[31]), "+f"(d[32]), "+f"(d[33]), "+f"(d[34]), "+f"(d[35]), "+f"(d[36]), "+f"(d[37]), "+f"(d[38]), "+f"(d[39]), "+f"(d[40]), "+f"(d[41]), "+f"(d[42]), "+f"(d[43]), "+f"(d[44]), "+f"(d[45]), "+f"(d[46]), "+f"(d[47]), "+f"(d[48]), "+f"(d[49]), "+f"(d[50]), "+f"(d[51]), "+f"(d[52]), "+f"(d[53]), "+f"(d[54]), "+f"(d[55]), "+f"(d[56]), "+f"(d[57]), "+f"(d[58]), "+f"(d[59]), "+f"(d[60]), "+f"(d[61]), "+f"(d[62]), "+f"(d[63])
    : "l"(da), "l"(db), "r"(scale_d), "n"(OA), "n"(OB));
}
template <int OA, int OB> __device__ __forceinline__ void wgmma_qk(float (&d)[56], uint64_t da, uint64_t db, int scale_d) {
  asm volatile("{\n.reg .pred p;\n.reg .b64 a, b;\nsetp.ne.b32 p, %58, 0;\nadd.s64 a, %56, %59;\nadd.s64 b, %57, %60;\n"
    "wgmma.mma_async.sync.aligned.m64n112k16.f32.bf16.bf16 "
    "{%0, %1, %2, %3, %4, %5, %6, %7, %8, %9, %10, %11, %12, %13, %14, %15, %16, %17, %18, %19, %20, %21, %22, %23, %24, %25, %26, %27, %28, %29, %30, %31, %32, %33, %34, %35, %36, %37, %38, %39, %40, %41, %42, %43, %44, %45, %46, %47, %48, %49, %50, %51, %52, %53, %54, %55}, "
    "a, b, p, 1, 1, 0, 0;\n}\n"
    : "+f"(d[0]), "+f"(d[1]), "+f"(d[2]), "+f"(d[3]), "+f"(d[4]), "+f"(d[5]), "+f"(d[6]), "+f"(d[7]), "+f"(d[8]), "+f"(d[9]), "+f"(d[10]), "+f"(d[11]), "+f"(d[12]), "+f"(d[13]), "+f"(d[14]), "+f"(d[15]), "+f"(d[16]), "+f"(d[17]), "+f"(d[18]), "+f"(d[19]), "+f"(d[20]), "+f"(d[21]), "+f"(d[22]), "+f"(d[23]), "+f"(d[24]), "+f"(d[25]), "+f"(d[26]), "+f"(d[27]), "+f"(d[28]), "+f"(d[29]), "+f"(d[30]), "+f"(d[31]), "+f"(d[32]), "+f"(d[33]), "+f"(d[34]), "+f"(d[35]), "+f"(d[36]), "+f"(d[37]), "+f"(d[38]), "+f"(d[39]), "+f"(d[40]), "+f"(d[41]), "+f"(d[42]), "+f"(d[43]), "+f"(d[44]), "+f"(d[45]), "+f"(d[46]), "+f"(d[47]), "+f"(d[48]), "+f"(d[49]), "+f"(d[50]), "+f"(d[51]), "+f"(d[52]), "+f"(d[53]), "+f"(d[54]), "+f"(d[55])
    : "l"(da), "l"(db), "r"(scale_d), "n"(OA), "n"(OB));
}
template <int OB> __device__ __forceinline__ void wgmma_rs_n256_tb(float (&d)[128], uint32_t a0, uint32_t a1, uint32_t a2, uint32_t a3, uint64_t db, int scale_d) {
  asm volatile("{\n.reg .pred p;\n.reg .b64 b;\nsetp.ne.b32 p, %133, 0;\nadd.s64 b, %132, %134;\n"
    "wgmma.mma_async.sync.aligned.m64n256k16.f32.bf16.bf16 "
    "{%0, %1, %2, %3, %4, %5, %6, %7, %8, %9, %10, %11, %12, %13, %14, %15, %16, %17, %18, %19, %20, %21, %22, %23, %24, %25, %26, %27, %28, %29, %30, %31, %32, %33, %34, %35, %36, %37, %38, %39, %40, %41, %42, %43, %44, %45, %46, %47, %48, %49, %50, %51, %52, %53, %54, %55, %56, %57, %58, %59, %60, %61, %62, %63, %64, %65, %66, %67, %68, %69, %70, %71, %72, %73, %74, %75, %76, %77, %78, %79, %80, %81, %82, %83, %84, %85, %86, %87, %88, %89, %90, %91, %92, %93, %94, %95, %96, %97, %98, %99, %100, %101, %102, %103, %104, %105, %106, %107, %108, %109, %110, %111, %112, %113, %114, %115, %116, %117, %118, %119, %120, %121, %122, %123, %124, %125, %126, %127}, "
    "{%128, %129, %130, %131}, b, p, 1, 1, 1;\n}\n"
    : "+f"(d[0]), "+f"(d[1]), "+f"(d[2]), "+f"(d[3]), "+f"(d[4]), "+f"(d[5]), "+f"(d[6]), "+f"(d[7]), "+f"(d[8]), "+f"(d[9]), "+f"(d[10]), "+f"(d[11]), "+f"(d[12]), "+f"(d[13]), "+f"(d[14]), "+f"(d[15]), "+f"(d[16]), "+f"(d[17]), "+f"(d[18]), "+f"(d[19]), "+f"(d[20]), "+f"(d[21]), "+f"(d[22]), "+f"(d[23]), "+f"(d[24]), "+f"(d[25]), "+f"(d[26]), "+f"(d[27]), "+f"(d[28]), "+f"(d[29]), "+f"(d[30]), "+f"(d[31]), "+f"(d[32]), "+f"(d[33]), "+f"(d[34]), "+f"(d[35]), "+f"(d[36]), "+f"(d[37]), "+f"(d[38]), "+f"(d[39]), "+f"(d[40]), "+f"(d[41]), "+f"(d[42]), "+f"(d[43]), "+f"(d[44]), "+f"(d[45]), "+f"(d[46]), "+f"(d[47]), "+f"(d[48]), "+f"(d[49]), "+f"(d[50]), "+f"(d[51]), "+f"(d[52]), "+f"(d[53]), "+f"(d[54]), "+f"(d[55]), "+f"(d[56]), "+f"(d[57]), "+f"(d[58]), "+f"(d[59]), "+f"(d[60]), "+f"(d[61]), "+f"(d[62]), "+f"(d[63]), "+f"(d[64]), "+f"(d[65]), "+f"(d[66]), "+f"(d[67]), "+f"(d[68]), "+f"(d[69]), "+f"(d[70]), "+f"(d[71]), "+f"(d[72]), "+f"(d[73]), "+f"(d[74]), "+f"(d[75]), "+f"(d[76]), "+f"(d[77]), "+f"(d[78]), "+f"(d[79]), "+f"(d[80]), "+f"(d[81]), "+f"(d[82]), "+f"(d[83]), "+f"(d[84]), "+f"(d[85]), "+f"(d[86]), "+f"(d[87]), "+f"(d[88]), "+f"(d[89]), "+f"(d[90]), "+f"(d[91]), "+f"(d[92]), "+f"(d[93]), "+f"(d[94]), "+f"(d[95]), "+f"(d[96]), "+f"(d[97]), "+f"(d[98]), "+f"(d[99]), "+f"(d[100]), "+f"(d[101]), "+f"(d[102]), "+f"(d[103]), "+f"(d[104]), "+f"(d[105]), "+f"(d[106]), "+f"(d[107]), "+f"(d[108]), "+f"(d[109]), "+f"(d[110]), "+f"(d[111]), "+f"(d[112]), "+f"(d[113]), "+f"(d[114]), "+f"(d[115]), "+f"(d[116]), "+f"(d[117]), "+f"(d[118]), "+f"(d[119]), "+f"(d[120]), "+f"(d[121]), "+f"(d[122]), "+f"(d[123]), "+f"(d[124]), "+f"(d[125]), "+f"(d[126]), "+f"(d[127])
    : "r"(a0), "r"(a1), "r"(a2), "r"(a3), "l"(db), "r"(scale_d), "n"(OB));
}
template <int OB> __device__ __forceinline__ void wgmma_rs_n128_tb(float (&d)[64], uint32_t a0, uint32_t a1, uint32_t a2, uint32_t a3, uint64_t db, int scale_d) {
  asm volatile("{\n.reg .pred p;\n.reg .b64 b;\nsetp.ne.b32 p, %69, 0;\nadd.s64 b, %68, %70;\n"
    "wgmma.mma_async.sync.aligned.m64n128k16.f32.bf16.bf16 "
    "{%0, %1, %2, %3, %4, %5, %6, %7, %8, %9, %10, %11, %12, %13, %14, %15, %16, %17, %18, %19, %20, %21, %22, %23, %24, %25, %26, %27, %28, %29, %30, %31, %32, %33, %34, %35, %36, %37, %38, %39, %40, %41, %42, %43, %44, %45, %46, %47, %48, %49, %50, %51, %52, %53, %54, %55, %56, %57, %58, %59, %60, %61, %62, %63}, "
    "{%64, %65, %66, %67}, b, p, 1, 1, 1;\n}\n"
    : "+f"(d[0]), "+f"(d[1]), "+f"(d[2]), "+f"(d[3]), "+f"(d[4]), "+f"(d[5]), "+f"(d[6]), "+f"(d[7]), "+f"(d[8]), "+f"(d[9]), "+f"(d[10]), "+f"(d[11]), "+f"(d[12]), "+f"(d[13]), "+f"(d[14]), "+f"(d[15]), "+f"(d[16]), "+f"(d[17]), "+f"(d[18]), "+f"(d[19]), "+f"(d[20]), "+f"(d[21]), "+f"(d[22]), "+f"(d[23]), "+f"(d[24]), "+f"(d[25]), "+f"(d[26]), "+f"(d[27]), "+f"(d[28]), "+f"(d[29]), "+f"(d[30]), "+f"(d[31]), "+f"(d[32]), "+f"(d[33]), "+f"(d[34]), "+f"(d[35]), "+f"(d[36]), "+f"(d[37]), "+f"(d[38]), "+f"(d[39]), "+f"(d[40]), "+f"(d[41]), "+f"(d[42]), "+f"(d[43]), "+f"(d[44]), "+f"(d[45]), "+f"(d[46]), "+f"(d[47]), "+f"(d[48]), "+f"(d[49]), "+f"(d[50]), "+f"(d[51]), "+f"(d[52]), "+f"(d[53]), "+f"(d[54]), "+f"(d[55]), "+f"(d[56]), "+f"(d[57]), "+f"(d[58]), "+f"(d[59]), "+f"(d[60]), "+f"(d[61]), "+f"(d[62]), "+f"(d[63])
    : "r"(a0), "r"(a1), "r"(a2), "r"(a3), "l"(db), "r"(scale_d), "n"(OB));
}
template <int V> using IC = std::integral_constant<int, V>;
template <int I, int N, class F> __device__ __forceinline__ void static_for(F&& f) {
  if constexpr (I < N) { f(std::integral_constant<int, I>{}); static_for<I + 1, N>(f); }
}

constexpr uint32_t SM_Q = 0, SM_BAR = 7 * 32768;
constexpr uint32_t B_FULL = SM_BAR, B_EMPTY = B_FULL + 24, B_WF = B_EMPTY + 24, B_QFULL = B_WF + 32, B_QEMPTY = B_QFULL + 16,
                   B_EVH = B_QEMPTY + 16, B_EVQ = B_EVH + 8, B_EVP0 = B_EVQ + 8, B_BG = B_EVP0 + 16, B_M0 = B_BG + 8, B_HALF = B_M0 + 8,
                   B_SPF = B_HALF + 8, B_EVS = B_SPF + 8, SM_UNSAFE = B_EVS + 8, SM_TS = SM_UNSAFE + 8, SM_ML = (SM_TS + 192 + 15) / 16 * 16, SM_EPOCH = SM_ML + 1024, SM_END = SM_EPOCH + 16;
constexpr uint32_t POS_M = 0x5462;
constexpr int SMEM_BYTES = SM_END;

#define ROW0(u) make_uint4(pack_bf16(o[16 * u], o[16 * u + 1]), pack_bf16(o[16 * u + 4], o[16 * u + 5]), \
                           pack_bf16(o[16 * u + 8], o[16 * u + 9]), pack_bf16(o[16 * u + 12], o[16 * u + 13]))
#define ROW1(u) make_uint4(pack_bf16(o[16 * u + 2], o[16 * u + 3]), pack_bf16(o[16 * u + 6], o[16 * u + 7]), \
                           pack_bf16(o[16 * u + 10], o[16 * u + 11]), pack_bf16(o[16 * u + 14], o[16 * u + 15]))

__global__ void __launch_bounds__(384, 1) gps_kernel(const __grid_constant__ Params P) {
  extern __shared__ __align__(1024) uint8_t smem_raw[];
  constexpr uint32_t sb = 1024;
  if (smem_u32(smem_raw) != sb) return;
  const int cta = blockIdx.x;
  const int wg = __shfl_sync(0xffffffffu, (int)threadIdx.x >> 7, 0);
  const int warp = __shfl_sync(0xffffffffu, ((int)threadIdx.x >> 5) & 3, 0);
  const int lane = threadIdx.x & 31;
#define ROLE                                                                                       \
  const Work& W = P.w[cta_id()];                                                                   \
  [[maybe_unused]] const int n0 = W.nb0 + W.na0, n1 = W.nb1 + W.na1, total = n0 + n1;              \
  [[maybe_unused]] const bool fin = W.role & R_FIN, tail = W.role & R_TAIL;                        \
  [[maybe_unused]] const uint32_t posw = total == 0 || tail ? POS_M : ((total & 1) ? 0x2546 : 0x4326)
  const int g = lane >> 2, t = lane & 3;
  if (wg < 2) {
    const int tid = threadIdx.x & 127;
    ROLE;
    const uint32_t sQ = sb + SM_Q + wg * 32768;
#define st0 tid_is(wg * 128)
    STAMP(st0, wg, 0);
    const int rr = lane >> 3, j = lane & 7;
    const uint32_t c0 = clk();
    if (threadIdx.x == 0) {
      for (int i = 0; i < 3; i++) { mbar_init(sb + B_FULL + 8 * i, 1); mbar_init(sb + B_EMPTY + 8 * i, tail ? 4 : 8); }
      for (int i = 0; i < 4; i++) mbar_init(sb + B_WF + 8 * i, 1);
      for (int i = 0; i < 2; i++) { mbar_init(sb + B_QFULL + 8 * i, 1); mbar_init(sb + B_QEMPTY + 8 * i, 4); mbar_init(sb + B_EVP0 + 8 * i, 4); }
      mbar_init(sb + B_EVH, 8); mbar_init(sb + B_EVQ, 8); mbar_init(sb + B_HALF, 8); mbar_init(sb + B_BG, 1); mbar_init(sb + B_M0, 1); mbar_init(sb + B_SPF, 1); mbar_init(sb + B_EVS, 1);
      asm volatile("fence.mbarrier_init.release.cluster;" ::: "memory");
    }
    __syncwarp();
    while (clk() - c0 < XDELAY) {}
    if (total > 0) {
#pragma unroll 1
      for (int p = 0; p < 4; p++) {
        const int r = warp * 16 + p * 4 + rr;
        const uint4* px = (const uint4*)(P.x + (size_t)min(W.q0 * 128 + wg * 64 + r, NN - 1) * 256) + j;
        const uint32_t off = (r >> 3) * 4096 + (r & 7) * 128 + ((j ^ (r & 7)) << 4);
#pragma unroll
        for (int c = 0; c < 4; c++) cp_async16(sQ + off + c * 1024, px + c * 8);
        cp_commit();
      }
    }
    bar_sync(4, 384);
    if (wg == 1) bar_arrive(5, 256);

    if (total > 0) {
      {
        const bool own = (W.own >> wg) & 1;
        uint8_t* gh = (uint8_t*)g_h + (size_t)W.q0 * 65536 + wg * 32768;
#pragma unroll 1
        for (int p = 0; p < 4; p++) {
          const int r = warp * 16 + p * 4 + rr;
          const uint32_t off = (r >> 3) * 4096 + (r & 7) * 128 + ((j ^ (r & 7)) << 4);
          asm volatile("cp.async.wait_group 3;" ::: "memory");
          cp_commit();
          float f[32];
#pragma unroll
          for (int c = 0; c < 4; c++) {
            const uint4 v = lds128(sQ + off + c * 1024);
            f[c * 8 + 0] = bf_lo(v.x); f[c * 8 + 1] = bf_hi(v.x); f[c * 8 + 2] = bf_lo(v.y); f[c * 8 + 3] = bf_hi(v.y);
            f[c * 8 + 4] = bf_lo(v.z); f[c * 8 + 5] = bf_hi(v.z); f[c * 8 + 6] = bf_lo(v.w); f[c * 8 + 7] = bf_hi(v.w);
          }
          float s0 = 0.f, s1 = 0.f, s2 = 0.f, s3 = 0.f;
#pragma unroll
          for (int i = 0; i < 16; i++) { s0 += f[2 * i]; s1 += f[2 * i + 1]; s2 += f[2 * i] * f[2 * i]; s3 += f[2 * i + 1] * f[2 * i + 1]; }
          float sum = s0 + s1, ss = s2 + s3;
#pragma unroll
          for (int k = 1; k < 8; k *= 2) { sum += __shfl_xor_sync(0xffffffffu, sum, k); ss += __shfl_xor_sync(0xffffffffu, ss, k); }
          const float mean = sum * (1.0f / 256.0f);
          float var = ss * (1.0f / 256.0f) - mean * mean;
          if (__any_sync(0xffffffffu, !(mean * mean <= 16.f * var))) {
            s2 = s3 = 0.f;
#pragma unroll
            for (int i = 0; i < 16; i++) { s2 += (f[2 * i] - mean) * (f[2 * i] - mean); s3 += (f[2 * i + 1] - mean) * (f[2 * i + 1] - mean); }
            ss = s2 + s3;
#pragma unroll
            for (int k = 1; k < 8; k *= 2) ss += __shfl_xor_sync(0xffffffffu, ss, k);
            var = ss * (1.0f / 256.0f);
          }
          float rs;
          asm("rsqrt.approx.ftz.f32 %0, %1;" : "=f"(rs) : "f"(var + 1e-5f));
          if (W.q0 * 128 + wg * 64 + r >= NN) rs = 0.f;
          const float nb = -mean * rs;
          if (own && j == 0) g_stat[W.q0 * 128 + wg * 64 + r] = make_float2(rs, nb);
#pragma unroll
          for (int c = 0; c < 4; c++) {
            uint4 h4 = make_uint4(pack_bf16(fmaf(f[c * 8], rs, nb), fmaf(f[c * 8 + 1], rs, nb)), pack_bf16(fmaf(f[c * 8 + 2], rs, nb), fmaf(f[c * 8 + 3], rs, nb)),
                                  pack_bf16(fmaf(f[c * 8 + 4], rs, nb), fmaf(f[c * 8 + 5], rs, nb)), pack_bf16(fmaf(f[c * 8 + 6], rs, nb), fmaf(f[c * 8 + 7], rs, nb)));
            sts128(sQ + off + c * 1024, h4);
            if (c == 3) {
              const float rk = rs * KS, e = fmaf(j == 7 ? nb - 0.5f * fmaf(f[31], rs, nb) : nb, KS, KC);
              h4 = make_uint4(pack_bf16(fmaf(f[24], rk, e), fmaf(f[25], rk, e)), pack_bf16(fmaf(f[26], rk, e), fmaf(f[27], rk, e)),
                              pack_bf16(fmaf(f[28], rk, e), fmaf(f[29], rk, e)), pack_bf16(fmaf(f[30], rk, e), j == 7 ? KC : fmaf(f[31], rk, e)));
            } else {
              h4 = make_uint4(hfma2(h4.x, KS2, KC2), hfma2(h4.y, KS2, KC2), hfma2(h4.z, KS2, KC2), hfma2(h4.w, KS2, KC2));
            }
            if (own) *(uint4*)(gh + off + c * 1024) = h4;
          }
        }
        __syncwarp();
        if (lane == 0) mbar_arrive(sb + B_EVH);
        fence_async_smem();
        bar_sync(1 + wg, 128);
      }
    }
    asm volatile("setmaxnreg.inc.sync.aligned.u32 %0;" :: "n"(CREG));
    STAMP(st0, wg, 1);

    float o[128];
    int qph = 0, st = tail ? wg : 0, ph = 0;
    auto release = [&](int stg) { if (lane == 0) mbar_arrive(sb + B_EMPTY + 8 * stg); };
    int resume = total > 0 ? -1 : 0;
    auto run = [&](auto hot_) __attribute__((always_inline)) {
    constexpr bool HOT = hot_.value;
    const int nloc = P.w[cta_id()].nloc;
    if (!HOT && resume == 0) {
#pragma unroll 1
      for (int i = 0; i < 32; i++) {
        const int r = i * 8 + wg * 4 + warp;
        cp_async16(sb + ((POS_M >> (r >> 6) * 4) & 15) * 32768 + sw_byte(r & 63, lane * 8), (const uint4*)P.wout + r * 32 + lane);
      }
    }
#pragma unroll 1
    for (int step = HOT || resume ? -1 : -4; step < nloc; step++) {
      ROLE;
      const bool isq = HOT && step < 0, isw = !HOT && step < 0;
      bool wide = false;
      if (HOT || step >= 0 || resume == 0) {
      if (isw) {
        const uint4* src = (const uint4*)(step < -2 ? P.wmsg : P.wv) + ((step & 1) * 128 + wg * 64 + warp) * 32 + lane;
        float cw[8] = {0.f, 0.f, 0.f, 0.f, 0.f, 0.f, 0.f, 0.f};
#pragma unroll 1
        for (int i = 0; i < 16; i++) cp_async16(sQ + sw_byte(i * 4 + warp, lane * 8), src + i * 128);
        cp_commit();
#pragma unroll
        for (int i = 0; i < 8; i++) {
          const uint4 v = __ldg((const uint4*)(step < -2 ? P.wmsg : P.wv) + (248 + i) * 32 + lane);
          const float k = step < -2 ? 0.f : (i == 7 ? -1.0f / 4.5f : -0.5f / 4.5f);
          cw[0] += bf_lo(v.x) * k; cw[1] += bf_hi(v.x) * k; cw[2] += bf_lo(v.y) * k; cw[3] += bf_hi(v.y) * k;
          cw[4] += bf_lo(v.z) * k; cw[5] += bf_hi(v.z) * k; cw[6] += bf_lo(v.w) * k; cw[7] += bf_hi(v.w) * k;
        }
        asm volatile("cp.async.wait_group 0;" ::: "memory");
#pragma unroll 1
        for (int i = 0; i < 16; i++) {
          const uint32_t ad = sQ + sw_byte(i * 4 + warp, lane * 8);
          const uint4 v = lds128(ad);
          uint4 w4 = make_uint4(pack_bf16(bf_lo(v.x) + cw[0], bf_hi(v.x) + cw[1]), pack_bf16(bf_lo(v.y) + cw[2], bf_hi(v.y) + cw[3]),
                                pack_bf16(bf_lo(v.z) + cw[4], bf_hi(v.z) + cw[5]), pack_bf16(bf_lo(v.w) + cw[6], bf_hi(v.w) + cw[7]));
          if (step == -1 && wg * 64 + i * 4 + warp == 127) w4 = make_uint4(0, 0, 0, 0);
          sts128(ad, w4);
        }
        fence_async_smem();
        bar_sync(7, 256);
      } else {
        SSTAMP(0);
        if (!isq) { mbar_wait(sb + B_QFULL + 8 * wg, qph); qph ^= 1; }
        STAMP(st0 && step == 0, wg, 8);
        SSTAMP(1);
        bar_sync(5 + wg, 256);
        SSTAMP(2);
      }
#pragma unroll 1
      for (int c = 0; c < 4; c++) {
        if (isq || step == 0) mbar_wait(isq && c == 0 ? sb + B_M0 : sb + B_WF + 8 * c, !isq && (HOT || resume));
        const int turn2 = isq ? 1 : (HOT || resume ? 3 : 4);
        if (c == turn2) bar_sync(5 + wg, 256);
        wg_fence();
        const uint64_t dA = desc_k(sb + SM_Q, wg * 2048 + c * 64), dW = desc_mn(sb, (((isq ? POS_M : posw) >> c * 4) & 15) * 2048);
        static_for<0, 4>([&](auto k) {
          if (k.value == 1) { if (isq && c == 0) mbar_wait(sb + B_WF, 0); wg_fence(); }
          wgmma_ss_n256_tb<k.value * 2, k.value * 512>(o, dA, dW, k.value > 0 ? 1 : c);
        });
        wg_commit();
        if ((c == 3 || c == turn2 - 1) && !isw) bar_arrive(6 - wg, 256);
        if (c == 0 && isq) { wg_wait<0>(); if (!tail) release(0); }
        wg_wait<1>();
      }
      wg_wait<0>();
      reg_fence(o);
      if (!isq) {
        STAMP(st0 && step == 0, wg, 9);
        SSTAMP(3);
        if (isw) bar_sync(1 + wg, 128); else if (lane == 0) mbar_arrive(sb + B_QEMPTY + 8 * wg);
        uint8_t* dw = (uint8_t*)(step < -2 ? g_Wmo : g_Wvo) + ((step & 1) * 2 + wg) * 32768 + warp * 8192 + g * 128;
        const int row0 = (W.loc0 + step) * 128 + wg * 64 + warp * 16;
        uint4 r[16];
#pragma unroll
        for (int u = 0; u < 8; u++) { r[2 * u] = ROW0(u); r[2 * u + 1] = ROW1(u); }
        if (isw) {
#pragma unroll
          for (int u = 0; u < 16; u++) *(uint4*)(dw + (u >> 2) * 1024 + ((((u & 2) * 2 + t) ^ g) << 4) + (u & 1) * 4096) = r[u];
        } else if (row0 < NN) {
          uint4* po = (uint4*)(P.out + (size_t)(row0 + g) * 256) + t;
          uint32_t c1 = clk();
#pragma unroll
          for (int u = 0; u < 16; u++) {
            if (!(DBG & 1) || !HOT || P.zero) red_bf16x8(po + (u >> 1) * 4 + (u & 1) * 256, r[u]);
            if (!HOT) { c1 += PACE; while ((int)(clk() - c1) < 0) {} }
          }
        }
        if (!HOT && step == -1) { bar_sync(7, 256); if (tid_is(0)) flag_release(F_W); __syncwarp(); STAMP(st0, wg, 3); }
        continue;
      }
      if (!tail) release(1);
      STAMP(st0, wg, 2);
      float c0 = (o[124] + (t == 3 ? 2.f : 1.f) * o[125]) * (-0.5f / 4.5f), c1 = (o[126] + (t == 3 ? 2.f : 1.f) * o[127]) * (-0.5f / 4.5f);
      c0 += __shfl_xor_sync(0xffffffffu, c0, 1); c1 += __shfl_xor_sync(0xffffffffu, c1, 1);
      c0 += __shfl_xor_sync(0xffffffffu, c0, 2); c1 += __shfl_xor_sync(0xffffffffu, c1, 2);
      float r0 = t == 3 ? 0.f : o[125], r1 = t == 3 ? 0.f : o[127], r2 = o[124], r3 = o[126];
#pragma unroll
      for (int i = 0; i < 31; i++) { r2 += o[4 * i]; r0 += o[4 * i + 1]; r3 += o[4 * i + 2]; r1 += o[4 * i + 3]; }
      r0 += r2; r1 += r3;
      r0 += __shfl_xor_sync(0xffffffffu, r0, 1); r1 += __shfl_xor_sync(0xffffffffu, r1, 1);
      r0 += __shfl_xor_sync(0xffffffffu, r0, 2); r1 += __shfl_xor_sync(0xffffffffu, r1, 2);
      r0 = fmaf(c0, -255.f, PSH / KC - r0); r1 = fmaf(c1, -255.f, PSH / KC - r1);
      wide = !(fabsf(c0) <= SAFE_C / KS) || !(fabsf(c1) <= SAFE_C / KS);
      bar_sync(1 + wg, 128);
#pragma unroll
      for (int k = 0; k < 16; k++)
        stsm4(sQ + warp * 8192 + ((lane >> 3) & 1) * 4096 + (k >> 2) * 1024 + (lane & 7) * 128 + ((((k & 3) * 2 + (lane >> 4)) ^ (lane & 7)) << 4),
              pack_bf16(o[8 * k] + c0, o[8 * k + 1] + c0), pack_bf16(o[8 * k + 2] + c1, o[8 * k + 3] + c1),
              pack_bf16(o[8 * k + 4] + c0, k == 15 && t == 3 ? r0 : o[8 * k + 5] + c0), pack_bf16(o[8 * k + 6] + c1, k == 15 && t == 3 ? r1 : o[8 * k + 7] + c1));
      fence_async_smem();
      bar_sync(1 + wg, 128);
      STAMP(st0, wg, 3);
      if (tail) { bar_sync(7, 256); if (wg == 0) { release(0); release(1); release(2); } }
      }

      float m0, m1;
      const int qh = tail ? 0 : wg, tl = W.role >> 2;
      uint32_t qo = qh * 2048;
      const uint32_t ko = (2 - tl) * 2048, stop = 1 + tl + (uint32_t)P.zero;
      float l0, l1;
      auto row_sums = [&]() { l0 = __shfl_sync(0xffffffffu, o[125] + 0.f, lane | 3); l1 = __shfl_sync(0xffffffffu, o[127] + 0.f, lane | 3); };
#define PART(u) make_uint4(pack_bf16(o[8 * u] - l0, o[8 * u + 1] - l0), pack_bf16(o[8 * u + 2] - l1, o[8 * u + 3] - l1), \
                           pack_bf16(o[8 * u + 4] - l0, o[8 * u + 5] - l0), pack_bf16(o[8 * u + 6] - l1, o[8 * u + 7] - l1))
      auto stage = [&]() __attribute__((always_inline)) {
        row_sums();
#pragma unroll
        for (int u = 0; u < 16; u++) sts128(sb + 6 * 32768 + (u * 128 + tid) * 16, PART(u));
        __syncwarp();
        if (lane == 0) mbar_arrive(sb + B_EVP0 + 8 * wg);
      };
      bool unsafe = !HOT;
#pragma unroll 1
      for (int seg = HOT ? 0 : resume - 1;; seg++) {
        ROLE;
        const bool last = __any_sync(0xffffffffu, seg || n1 == 0);
        m0 = m1 = !HOT && unsafe ? -INFINITY : 0.f;
        int first = 1;
        auto tile = [&](auto n_, bool endseg) __attribute__((always_inline)) -> bool {
          constexpr int N = n_.value;
          float s[N / 2]; uint32_t p[N / 4];
          if (N == 128 || !(first && seg)) { if (!mbar_try_wait(sb + B_FULL + 8 * st, ph)) mbar_wait(sb + B_FULL + 8 * st, ph); }
          const bool again = !HOT && N == 112 && first && !seg;
          if (HOT || N == 128) bar_sync(5 + wg, 256);
          else asm volatile("{\n.reg .pred p;\nsetp.eq.u32 p, %1, 0;\n@p bar.sync %0, 256;\n}\n" :: "r"(5 + wg), "r"((uint32_t)again) : "memory");
          wg_fence();
          const uint64_t dQ = desc_k(sb + SM_Q, qo), dK = desc_k(sb, ko + st * 4096);
          qo += (uint32_t)P.zero;
          static_for<0, 16>([&](auto k) { constexpr int kk = (k.value + KROT) & 15, off = (kk >> 2) * 64 + (kk & 3) * 2; wgmma_qk<off, off>(s, dQ, dK, k.value > 0); });
          wg_commit();
          if (HOT || N == 128) bar_arrive(6 - wg, 256);
          else asm volatile("{\n.reg .pred p;\nsetp.eq.u32 p, %1, 0;\n@p bar.arrive %0, 256;\n}\n" :: "r"(6 - wg), "r"((uint32_t)again) : "memory");
          if (N == 112 && first && seg) { if (wg == 1) mbar_wait(sb + B_SPF, 0); stage(); }
          if (HOT && N == 112 && first && !seg) {
            float a0 = 0.f, a1 = 0.f, a2 = 0.f, a3 = 0.f;
#pragma unroll
            for (int i = 0; i < 32; i++) { a0 += o[4 * i] * o[4 * i]; a2 += o[4 * i + 1] * o[4 * i + 1]; a1 += o[4 * i + 2] * o[4 * i + 2]; a3 += o[4 * i + 3] * o[4 * i + 3]; }
            a0 += a2; a1 += a3;
            a0 += __shfl_xor_sync(0xffffffffu, a0, 1); a1 += __shfl_xor_sync(0xffffffffu, a1, 1);
            a0 += __shfl_xor_sync(0xffffffffu, a0, 2); a1 += __shfl_xor_sync(0xffffffffu, a1, 2);
            unsafe = __any_sync(0xffffffffu, bar_red_or(tail ? 7 : 1 + wg, tail ? 256 : 128, wide || !(a0 <= SAFE_N2 / (KS * KS)) || !(a1 <= SAFE_N2 / (KS * KS))));
            if (lane == 0) { asm volatile("st.shared.u8 [%0], %1;" :: "r"(sb + SM_UNSAFE + wg), "r"((uint32_t)unsafe) : "memory"); mbar_arrive(sb + B_EVQ); }
          }
          STAMP(N == 112 && first && !seg && st0, wg, 0);
          wg_wait<0>();
          reg_fence(s);
          if (HOT && N == 112 && unsafe) return true;
          if (endseg) { if (lane == 0) mbar_arrive(sb + B_QEMPTY + 8 * wg); }
          if (!HOT && unsafe) {
            float a0 = fmaxf(s[0], s[1]), a1 = fmaxf(s[2], s[3]);
#pragma unroll
            for (int i = 1; i < N / 8; i++) { a0 = fmaxf(a0, fmaxf(s[4 * i], s[4 * i + 1])); a1 = fmaxf(a1, fmaxf(s[4 * i + 2], s[4 * i + 3])); }
            if (__any_sync(0xffffffffu, (a0 > m0 + TAU) || (a1 > m1 + TAU))) {
              a0 = fmaxf(a0, __shfl_xor_sync(0xffffffffu, a0, 1)); a1 = fmaxf(a1, __shfl_xor_sync(0xffffffffu, a1, 1));
              a0 = fmaxf(a0, __shfl_xor_sync(0xffffffffu, a0, 2)); a1 = fmaxf(a1, __shfl_xor_sync(0xffffffffu, a1, 2));
              const float x0 = ceilf(fmaxf(m0, a0)), x1 = ceilf(fmaxf(m1, a1)), sc0 = ex2(m0 - x0), sc1 = ex2(m1 - x1);
              m0 = x0; m1 = x1;
#pragma unroll
              for (int i = 0; i < 32; i++) { o[4 * i] *= sc0; o[4 * i + 1] *= sc0; o[4 * i + 2] *= sc1; o[4 * i + 3] *= sc1; }
            }
#pragma unroll
            for (int i = 0; i < N / 8; i++) { s[4 * i] -= m0; s[4 * i + 1] -= m0; s[4 * i + 2] -= m1; s[4 * i + 3] -= m1; }
          }
          auto pv = [&](auto k) { wgmma_rs_n256_tb<k.value * 512 + (63 << 16)>(o, p[4 * k.value], p[4 * k.value + 1], p[4 * k.value + 2], p[4 * k.value + 3], dK, k.value > 0 || N == 128 ? 1 : !first); };
#pragma unroll
          for (int i = 0; i < 16; i++) { p[i] = pack_bf16(ex2(s[2 * i]), ex2(s[2 * i + 1])); asm volatile("" : "+r"(p[i]) :: "memory"); }
          reg_fence(o);
          do bar_sync(5 + wg, 256); while (P.zero);
          wg_fence();
          static_for<0, 4>(pv);
          wg_commit();
#pragma unroll
          for (int i = 16; i < N / 4; i++) { p[i] = pack_bf16(ex2(s[2 * i]), ex2(s[2 * i + 1])); asm volatile("" : "+r"(p[i]) :: "memory"); }
          wg_fence();
          static_for<4, N / 16>(pv);
          wg_commit();
          bar_arrive(6 - wg, 256);
          if (N == 128) { wg_wait<1>(); if (endseg && last) { if (lane == 0) mbar_arrive(sb + B_HALF); } }
          wg_wait<0>();
          reg_fence(o); reg_fence(p);
          release(st);
          if (st) { st--; ph ^= 1; } else st = stop;
          return false;
        };
#pragma unroll 1
        for (int left = tail ? 8 - wg : (seg ? W.nb1 : W.nb0); left > 0; left--) { if (tile(IC<112>{}, false)) { resume = 1; return; } STAMP(first && !seg && st0, wg, 4); first = 0; }
#pragma unroll 1
        for (int left = tail ? 32 + wg : (seg ? W.na1 : W.na0); left > 0; left--) tile(IC<128>{}, left == 1);
        STAMP(st0 && last, wg, 6);
        {
        ROLE;
        if (last && fin && !(tail && wg == 1)) break;
        if (last) {
          row_sums();
          mbar_wait(sb + (tail ? B_QEMPTY : B_HALF), 0);
          const uint32_t sp = sb + (tail ? 0 : (posw >> 12) + wg) * 32768, sm = sb + SM_ML + (tail ? 0 : wg) * 512;
#pragma unroll
          for (int u = 0; u < 16; u++) sts128(sp + (u * 128 + tid) * 16, PART(u));
          if (t == 0) {
            asm volatile("st.shared.v2.f32 [%0], {%1,%2};" :: "r"(sm + (warp * 16 + g) * 8), "f"(m0), "f"(l0) : "memory");
            asm volatile("st.shared.v2.f32 [%0], {%1,%2};" :: "r"(sm + (warp * 16 + g) * 8 + 64), "f"(m1), "f"(l1) : "memory");
          }
          __syncwarp();
          if (lane == 0) mbar_arrive(sb + B_EVP0 + 8 * wg);
          STAMP(st0, wg, 7);
          break;
        }
        mbar_wait(sb + B_QFULL + 8 * wg, qph); qph ^= 1;
        uint32_t u; asm volatile("ld.shared.u8 %0, [%1];" : "=r"(u) : "r"(sb + SM_UNSAFE + wg) : "memory");
        unsafe = __any_sync(0xffffffffu, u != 0);
        mbar_wait(sb + B_FULL + 8 * st, ph);
        if (t == 3) {
          float2* ml = g_ml + W.slotA * 128 + wg * 64 + warp * 16 + g;
          ml[0] = make_float2(m0, o[125] + 0.f); ml[8] = make_float2(m1, o[127] + 0.f);
        }
        if (HOT && unsafe) { resume = 2; return; }
        }
      }

      if (P.w[cta_id()].role & R_FIN) {
        ROLE;
        if (tail && wg == 1) break;
        row_sums();
        const int rl = wg * 64 + warp * 16 + g;
        uint32_t a[64];
#pragma unroll
        for (int i = 0; i < 64; i++) a[i] = pack_bf16(o[2 * i] - (i & 1 ? l1 : l0), o[2 * i + 1] - (i & 1 ? l1 : l0));
        reg_fence(a);
        {
          float2 e0, e1;
          mbar_wait(sb + B_QFULL + 8 * wg, qph);
          asm volatile("ld.shared.v2.f32 {%0,%1}, [%2];" : "=f"(e0.x), "=f"(e0.y) : "r"(sb + SM_ML + rl * 8) : "memory");
          asm volatile("ld.shared.v2.f32 {%0,%1}, [%2];" : "=f"(e1.x), "=f"(e1.y) : "r"(sb + SM_ML + rl * 8 + 64) : "memory");
          STAMP(st0, wg, 7);
          uint4 v[16];
#pragma unroll
          for (int u = 0; u < 16; u++) v[u] = lds128(sQ + (u * 128 + tid) * 16);
          uint32_t fb0 = 0x3f803f80u, fb1 = 0x3f803f80u;
          const float s0 = l0 + e0.y, s1 = l1 + e1.y;
          if (__any_sync(0xffffffffu, m0 != e0.x || m1 != e1.x || !(fmaxf(s0, s1) < 0x1p40f) || !(fminf(s0, s1) > 0x1p-40f))) {
            const float x0 = fmaxf(m0, e0.x), x1 = fmaxf(m1, e1.x);
            const float d0 = fmaxf(m0 - x0, -1000.f), d1 = fmaxf(m1 - x1, -1000.f), f0 = fmaxf(e0.x - x0, -1000.f), f1 = fmaxf(e1.x - x1, -1000.f);
            l0 = l0 * ex2(d0) + e0.y * ex2(f0); l1 = l1 * ex2(d1) + e1.y * ex2(f1);
            const int E0 = fexp(l0), E1 = fexp(l1);
            const uint32_t fa0 = pow2_bf2((int)d0 - E0), fa1 = pow2_bf2((int)d1 - E1);
            fb0 = pow2_bf2((int)f0 - E0); fb1 = pow2_bf2((int)f1 - E1);
            l0 = __uint_as_float(__float_as_uint(l0) - (E0 << 23)); l1 = __uint_as_float(__float_as_uint(l1) - (E1 << 23));
#pragma unroll
            for (int i = 0; i < 32; i++) { a[2 * i] = hmul2(a[2 * i], fa0); a[2 * i + 1] = hmul2(a[2 * i + 1], fa1); }
          } else { l0 = s0; l1 = s1; }
#pragma unroll
          for (int u = 0; u < 16; u++) {
            a[4 * u] = hfma2(v[u].x, fb0, a[4 * u]); a[4 * u + 1] = hfma2(v[u].y, fb1, a[4 * u + 1]);
            a[4 * u + 2] = hfma2(v[u].z, fb0, a[4 * u + 2]); a[4 * u + 3] = hfma2(v[u].w, fb1, a[4 * u + 3]);
          }
        }
        float fs0, fs1;
        asm("rcp.approx.ftz.f32 %0, %1;" : "=f"(fs0) : "f"(l0 * (KS / KC))); asm("rcp.approx.ftz.f32 %0, %1;" : "=f"(fs1) : "f"(l1 * (KS / KC)));
        STAMP(st0, wg, 8);
        reg_fence(a);
        bar_sync(5 + wg, 256);
        uint64_t dW[4];
        float y0[64], y1[64];
        auto half0 = [&](auto u_) {
          constexpr int u = u_.value;
          if (u % 4 == 0) { mbar_wait(sb + B_WF + 2 * u, 1); wg_fence(); dW[u / 4] = desc_mn(sb, ((posw >> u) & 15) * 2048); }
          wgmma_rs_n128_tb<(u & 3) * 512>(y0, a[4 * u], a[4 * u + 1], a[4 * u + 2], a[4 * u + 3], dW[u / 4], u != 0);
        };
        auto half1 = [&](auto u_) {
          constexpr int u = u_.value;
          wgmma_rs_n128_tb<(u & 3) * 512 + 128>(y1, a[4 * u], a[4 * u + 1], a[4 * u + 2], a[4 * u + 3], dW[u / 4], u != 0);
        };
        const bool wr = W.q0 * 128 + wg * 64 + warp * 16 < NN;
        uint4* po = (uint4*)(P.out + (size_t)(W.q0 * 128 + rl) * 256) + t;
        auto emit = [&](const float* y, uint4* dst) {
          if (wr && (!(DBG & 2) || P.zero)) {
            OUTW(dst, make_uint4(pack_bf16(y[0] * fs0, y[1] * fs0), pack_bf16(y[4] * fs0, y[5] * fs0), pack_bf16(y[8] * fs0, y[9] * fs0), pack_bf16(y[12] * fs0, y[13] * fs0)));
            OUTW(dst + 8 * 32, make_uint4(pack_bf16(y[2] * fs1, y[3] * fs1), pack_bf16(y[6] * fs1, y[7] * fs1), pack_bf16(y[10] * fs1, y[11] * fs1), pack_bf16(y[14] * fs1, y[15] * fs1)));
          }
          wg_fence();
        };
        static_for<0, 16>(half0);
        wg_commit();
        static_for<0, 4>(half1);
        wg_commit();
        wg_wait<1>();
        reg_fence(y0);
        emit(y0, po); static_for<4, 8>(half1);
        emit(y0 + 16, po + 4); static_for<8, 12>(half1);
        emit(y0 + 32, po + 8); static_for<12, 16>(half1);
        wg_commit();
        bar_arrive(6 - wg, 256);
        emit(y0 + 48, po + 12);
        wg_wait<0>();
        reg_fence(a); reg_fence(y1);
        STAMP(st0, wg, 9);
#pragma unroll
        for (int u = 0; u < 4; u++) emit(y1 + 16 * u, po + 16 + 4 * u);
        break;
      }
    }
    STAMP(st0, wg, 11);
    DUMP(st0, wg, 0, 16);
    if (!P.zero) { asm volatile("exit;"); __builtin_unreachable(); }
#pragma unroll
    for (int i = 0; i < 32; i++)
      asm volatile("ld.volatile.shared.v4.f32 {%0,%1,%2,%3}, [%4];" : "=f"(o[4 * i]), "=f"(o[4 * i + 1]), "=f"(o[4 * i + 2]), "=f"(o[4 * i + 3]) : "r"(sb) : "memory");
    };
    if (resume < 0) run(std::true_type{});
    run(std::false_type{});
    asm volatile("setmaxnreg.dec.sync.aligned.u32 %0;" :: "n"(504 - 2 * CREG));
  } else {
    STAMP(lane == 0 && warp == 0, 2, 0);
        const int mi = cta >> 3;
    const uint32_t sW = sb + 3 * 32768;
    uint4 wa[4], wb[8];
    {
      const uint4* pq = (const uint4*)(P.wq + ((mi & 15) * 16 + g) * 256) + warp * 8 + t;
      const uint4* pk = (const uint4*)(P.wk + ((cta & 7) * 32 + g) * 256) + warp * 8 + t;
#pragma unroll
      for (int i = 0; i < 4; i++) wa[i] = __ldg(pq + (i >> 1) * 256 + (i & 1) * 4);
#pragma unroll
      for (int i = 0; i < 8; i++) wb[i] = __ldg(pk + (i >> 1) * 256 + (i & 1) * 4);
    }
    bar_sync(4, 384);
    {
#pragma unroll
      for (int n = 0; n < 4; n++) {
        float c[4] = {0.f, 0.f, 0.f, 0.f};
#pragma unroll
        for (int u = 0; u < 2; u++) {
          mma16816(c, wa[u].x, wa[2 + u].x, wa[u].y, wa[2 + u].y, wb[2 * n + u].x, wb[2 * n + u].y);
          mma16816(c, wa[u].z, wa[2 + u].z, wa[u].w, wa[2 + u].w, wb[2 * n + u].z, wb[2 * n + u].w);
        }
        asm volatile("st.shared.v2.f32 [%0], {%1,%2};" :: "r"(sW + ((warp * 16 + g) * 40 + n * 8 + 2 * t) * 4), "f"(c[0]), "f"(c[1]) : "memory");
        asm volatile("st.shared.v2.f32 [%0], {%1,%2};" :: "r"(sW + ((warp * 16 + g + 8) * 40 + n * 8 + 2 * t) * 4), "f"(c[2]), "f"(c[3]) : "memory");
      }
      STAMP(lane == 0 && warp == 0, 2, 7);
      bar_sync(3, 128);
      if (warp < 2) {
        float c[8] = {0.f, 0.f, 0.f, 0.f, 0.f, 0.f, 0.f, 0.f};
#pragma unroll
        for (int k = 0; k < 4; k++) {
          const uint4 v = lds128(sW + ((k * 16 + warp * 8 + g) * 40 + t * 8) * 4), w = lds128(sW + ((k * 16 + warp * 8 + g) * 40 + t * 8 + 4) * 4);
          c[0] += __uint_as_float(v.x); c[1] += __uint_as_float(v.y); c[2] += __uint_as_float(v.z); c[3] += __uint_as_float(v.w);
          c[4] += __uint_as_float(w.x); c[5] += __uint_as_float(w.y); c[6] += __uint_as_float(w.z); c[7] += __uint_as_float(w.w);
        }
        const float ms = 1.4426950408889634f / 16.0f / KS;
        if (cta < 128)
          *(uint4*)((uint8_t*)g_M + sw_byte(mi * 16 + warp * 8 + g, (cta & 7) * 32 + t * 8)) =
              make_uint4(pack_bf16(c[0] * ms, c[1] * ms), pack_bf16(c[2] * ms, c[3] * ms), pack_bf16(c[4] * ms, c[5] * ms), pack_bf16(c[6] * ms, c[7] * ms));
      }
    }
    asm volatile("setmaxnreg.dec.sync.aligned.u32 %0;" :: "n"(504 - 2 * CREG));
    STAMP(lane == 0 && warp == 0, 2, 13);
    bar_sync(3, 128);
#define ep1 (lds32(sb + SM_EPOCH) + 1)
    if (threadIdx.x == 256 && cta < 128) flag_release(F_M + (cta >> 5));
    __syncwarp();
    ROLE;
    if (warp == 3 && W.own) { mbar_wait_w(sb + B_EVH, 0); flag_release_w(F_H); STAMP(lane == 0, 2, 6); }
    if (warp == 0) {
      if (lane == 0) {
        STAMP(true, 2, 1);
        const uint32_t epoch = ld_relaxed(g_flag + F_EPOCH);
        if (total > 0) {
#pragma unroll
          for (int c = 0; c < 3; c++) mbar_expect_tx(sb + B_WF + 8 * c, c == 0 ? WCH_B - 8192 : WCH_B);
          mbar_expect_tx(sb + B_M0, 8192);
          int c = 0;
#pragma unroll 1
          for (uint32_t it = 0; c < 4; it++) {
            uint4 f;
            asm volatile("ld.relaxed.gpu.global.v4.u32 {%0,%1,%2,%3}, [%4];" : "=r"(f.x), "=r"(f.y), "=r"(f.z), "=r"(f.w) : "l"(g_flag + F_M) : "memory");
            uint32_t tm;
            asm volatile("mad.lo.u32 %0, %1, 32, 32;" : "=r"(tm) : "r"(epoch));
            int ok = (int)(f.x - tm) < 0 ? 0 : (int)(f.y - tm) < 0 ? 1 : (int)(f.z - tm) < 0 ? 2 : (int)(f.w - tm) < 0 ? 3 : 4;
            if (it > (1u << 23)) ok = 4;
            if (ok > c) {
              asm volatile("fence.acquire.gpu;" ::: "memory"); fence_async_gmem();
              if (c == 0) bulk_g2s(sb + (POS_M & 15) * 32768, g_M, 8192, sb + B_M0);
            }
#pragma unroll 1
            for (; c < ok; c++) {
              const uint32_t skip = c == 0 ? 8192 : 0;
              bulk_g2s(sb + ((POS_M >> c * 4) & 15) * 32768 + skip, pofs<const uint8_t>(g_M, c * WCH_B + skip), WCH_B - skip, sb + B_WF + 8 * c);
              STAMP(c == 0, 2, 2);
            }
          }
        }
        asm volatile("st.shared.u32 [%0], %1;" :: "r"(sb + SM_EPOCH), "r"(epoch) : "memory");
        if (total > 0) mbar_expect_tx(sb + B_WF + 24, WCH_B);
        int st = 0, ph = 0, qph = 0;
        const int nsl = tail ? 3 : 2;
        auto next_slot = [&]() { mbar_wait(sb + B_EMPTY + 8 * st, ph); if (++st == nsl) { st = 0; ph ^= 1; } };
        auto w_load = [&](int c0, int c1) {
#pragma unroll 1
          for (int c = c0; c < c1; c++) {
            mbar_expect_tx(sb + B_WF + 8 * c, WCH_B);
            bulk_g2s(sb + ((posw >> c * 4) & 15) * 32768, pofs<const uint8_t>(fin ? g_Wvo : g_Wmo, c * WCH_B), WCH_B, sb + B_WF + 8 * c);
          }
        };
        auto q_load = [&](const uint4* src, bool wait_empty) {
#pragma unroll 1
          for (int h = 0; h < 2; h++) {
            if (wait_empty) mbar_wait(sb + B_QEMPTY + 8 * h, qph);
            mbar_expect_tx(sb + B_QFULL + 8 * h, 32768);
            (HINT & 2 ? bulk_g2s_last : bulk_g2s)(sb + SM_Q + h * 32768, src + h * 2048, 32768, sb + B_QFULL + 8 * h);
          }
          if (wait_empty) qph ^= 1;
        };
        if (total > 0) {
          STAMP(true, 2, 3);
          flag_wait(F_H, ep1 * NHSIG); fence_async_gmem();
          STAMP(true, 2, 4);
          uint32_t ko = W.k0 * 8192;
#pragma unroll 1
          for (int j = 0; j < total; j++) {
            if (j == n0) {
              flag_wait(F_QP + W.q1 * LN_, ep1); fence_async_gmem();
              const uint32_t u = __ldcg(g_unsafe + W.q1);
              asm volatile("st.shared.u32 [%0], %1;" :: "r"(sb + SM_UNSAFE), "r"(u) : "memory");
              ko = W.k1 * 8192;
            }
            if (j == n0 + 1) q_load(g_qp + W.q1 * 4096, true);
            if (j == total - 1) { flag_wait(F_W, ep1); fence_async_gmem(); if (!tail) w_load(0, 1); }
            const uint32_t bytes = (j < n0 ? j < W.nb0 : j - n0 < W.nb1) ? 112 * 512 : 128 * 512, s0 = st;
            next_slot();
            mbar_expect_tx(sb + B_FULL + 8 * s0, bytes);
            bulk_g2s(sb + ((tail ? 1 : 2) + 2 * s0) * 32768, pofs<const uint8_t>(g_h, ko), bytes, sb + B_FULL + 8 * s0);
            ko += bytes;
            if (j == n0 + 1) {
#pragma unroll 1
              for (int h = 0; h < 2; h++) {
                bulk_wait_read();
                if (h) mbar_arrive(sb + B_SPF);
                mbar_wait(sb + B_EVP0 + 8 * h, 0);
                fence_async_smem();
                bulk_s2g(pofs<uint4>(g_part, W.slotA * 65536 + h * 32768), sb + 6 * 32768, 32768);
                bulk_commit();
              }
            }
            if (j == n0 + 2) { bulk_wait_all(); mbar_arrive(sb + B_EVS); }
          }
          next_slot();
          if (tail) { next_slot(); next_slot(); }
        } else { flag_wait(F_W, ep1); fence_async_gmem(); }
        STAMP(true, 2, 5);
        const bool staged = total > 0 && !tail;
        w_load(staged, staged ? (fin ? 2 : 3) : 4);
#pragma unroll 1
        for (int i = 0; i < W.nloc; i++) {
          const int tl = W.loc0 + i, last = tl * 128 + 127 < NN ? tl * 128 + 127 : NN - 1;
          flag_wait(F_AGG + ((last >= NGW) + (last >= 4 * NGW) + (last >= 9 * NGW)) * LN_, ep1 * NGW); fence_async_gmem();
          if (total == 0) g_flag[F_EPOCH] = epoch + 1;
          q_load(g_agg + tl * 4096, total > 0 || i > 0);
        }
        if (tail) { mbar_wait(sb + B_BG, 0); mbar_wait(sb + B_EVP0 + 8, 0); mbar_arrive(sb + B_QFULL); }
        else if (fin) {
          int h = 0, c = 2, have = W.slotB >= 0 ? 2 : 0;
          mbar_wait(sb + B_BG, 0);
#pragma unroll 1
          for (uint32_t it = 0; (h < 2 || c < 4) && it < (1u << 23); it++) {
            if (have < 2) {
              uint2 f;
              asm volatile("ld.relaxed.gpu.global.v2.u32 {%0,%1}, [%2];" : "=r"(f.x), "=r"(f.y) : "l"(g_flag + F_PART + W.slotA * LN_) : "memory");
              have = (int)(f.x - (epoch + 1)) < 0 ? 0 : ((int)(f.y - (epoch + 1)) < 0 ? 1 : 2);
            }
            if (h < have && mbar_try_wait_nb(sb + B_QEMPTY + 8 * h, 0)) {
              asm volatile("fence.acquire.gpu;" ::: "memory"); fence_async_gmem();
              STAMP(true, 2, 14 + h);
              mbar_expect_tx(sb + B_QFULL + 8 * h, 32768 + 512);
              bulk_g2s(sb + SM_ML + h * 512, g_ml + W.slotA * 128 + h * 64, 512, sb + B_QFULL + 8 * h);
              bulk_g2s(sb + SM_Q + h * 32768, g_part + W.slotA * 4096 + h * 2048, 32768, sb + B_QFULL + 8 * h);
              h++;
            }
            const bool half = mbar_try_wait_nb(sb + B_HALF, 0);
            const int c1 = half ? 4 : (h > 0 ? 3 : 2);
            if (c < c1) { w_load(c, c1); c = c1; }
          }
        } else if (total > 0) {
#pragma unroll 1
          for (int h = 0; h < 2; h++) {
            mbar_wait(sb + B_EVP0 + 8 * h, 1);
            fence_async_smem();
            bulk_s2g(g_part + W.slotB * 4096 + h * 2048, sb + ((posw >> 12) + h) * 32768, 32768);
            bulk_s2g(g_ml + W.slotB * 128 + h * 64, sb + SM_ML + h * 512, 512);
            bulk_commit();
          }
          asm volatile("cp.async.bulk.wait_group.read 1;" ::: "memory");
          w_load(3, 4);
          {
#pragma unroll 1
            for (int k = 0; k < 2; k++) {
              if (k) bulk_wait_all(); else asm volatile("cp.async.bulk.wait_group 1;" ::: "memory");
              if (RELF) { fence_async_gmem(); flag_release(F_PART + W.slotB * LN_ + k); }
              else asm volatile("red.relaxed.gpu.global.add.u32 [%0], 1;" :: "l"(g_flag + F_PART + W.slotB * LN_ + k) : "memory");
              STAMP(true, 2, 14 + k);
            }
          }
        }
        DUMP(true, 2, 14, 16);
        DUMP(true, 2, 0, 8);
      }
      return;
    }
  }
    {
      const int gw = cta * 3 + warp - 1;
      ROLE;
      int early = warp == 1 && n1 > 0;
      if (total > 0) {
        mbar_wait_w(sb + B_EVQ, 0);
        const uint32_t c0 = clk();
        if (warp == 1 && (W.role & R_PUB)) {
          g_unsafe[W.q0] = lds32(sb + SM_UNSAFE);
#pragma unroll 1
          for (int k = 0; k < 4; k++) {
            __nanosleep(2000);
            if (lane == 0) bulk_s2g(pofs<uint4>(g_qp, W.q0 * 65536 + k * 16384), sb + SM_Q + k * 16384, 16384);
            bulk_commit();
          }
          bulk_wait_all();
          flag_release_w(F_QP + W.q0 * LN_);
        }
        while (__any_sync(0xffffffffu, clk() - c0 < GSTART)) __nanosleep(500);
        STAMP(lane == 0 && warp == 1, 2, 8);
#define ovf_cnt pofs<uint32_t>(g_flag, (F_OVF + (ep1 & 1) * LN_) * 4)
        if (gw == 0) g_flag[F_OVF + ((ep1 + 1) & 1) * LN_] = 0;
#pragma unroll 1
        for (int e0 = gw * 32; e0 < NE; e0 += NGW * 32 * 7) {
          int d[7], s[7], pos[7];
          const int* pd = pofs<const int>(P.dst, (e0 + lane) * 4);
          const int* ps = pofs<const int>(P.src, (e0 + lane) * 4);
#pragma unroll
          for (int k = 0; k < 7; k++) { const bool ok = e0 + k * NGW * 32 < NE; d[k] = ok ? (HINT & 1 ? __ldcs(pd + k * NGW * 32) : __ldg(pd + k * NGW * 32)) : -1; s[k] = ok ? (HINT & 1 ? __ldcs(ps + k * NGW * 32) : __ldg(ps + k * NGW * 32)) : 0; }
          uint32_t ov = 0;
#pragma unroll
          for (int k = 0; k < 7; k++) {
            pos[k] = 0;
            if (d[k] >= 0) asm volatile("atom.relaxed.gpu.global.add.u32 %0, [%1], 1;" : "=r"(pos[k]) : "l"(pofs<int>(g_cnt, d[k] << 2)) : "memory");
            s[k] = (uint32_t)(uintptr_t)g_u + s[k] * 512;
            if (d[k] >= 0 && pos[k] < CAP) asm volatile("st.volatile.global.u32 [%0], %1;" :: "l"(pofs<int>(g_bin, (d[k] * CAPS + pos[k]) << 2)), "r"(s[k]) : "memory");
            ov |= (pos[k] >= CAP) << k;
          }
          if (__any_sync(0xffffffffu, ov != 0)) {
            uint32_t at;
            asm volatile("atom.relaxed.gpu.global.add.u32 %0, [%1], %2;" : "=r"(at) : "l"(ovf_cnt), "r"(__popc(ov)) : "memory");
#pragma unroll
            for (int k = 0; k < 7; k++) if ((ov >> k) & 1) g_ovf[at++] = make_int2(d[k], s[k]);
          }
        }
        flag_wait_w(F_H, ep1 * NHSIG);
#pragma unroll 1
        for (int n0 = gw; n0 < NN; n0 += 4 * NGW) {
          uint4 xv[4]; float2 st[4];
#pragma unroll
          for (int k = 0; k < 4; k++) {
            const int n = n0 + k * NGW < NN ? n0 + k * NGW : n0;
            xv[k] = (HINT & 1 ? ldcs_v : ldcg_v)(pofs<const uint4>(P.x, n * 512 + lane * 16));
            st[k] = __ldcg(pofs<const float2>(g_stat, n * 8));
          }
#pragma unroll
          for (int k = 3; k >= 0; k--) {
            const int n = n0 + k * NGW;
            const float a = st[k].x * US, c = fmaf(st[k].y, US, UB + 8388608.0f);
#define FIX(w) __byte_perm(__float_as_uint(fmaf(bf_lo(w), a, c)), __float_as_uint(fmaf(bf_hi(w), a, c)), 0x5410)
            if (n < NN) {
              *pofs<uint4>(P.out, n * 512 + lane * 16) = xv[k];
              *pofs<uint4>(g_u, n * 512 + lane * 16) = make_uint4(FIX(xv[k].x), FIX(xv[k].y), FIX(xv[k].z), FIX(xv[k].w));
            }
          }
        }
        flag_release_w(F_BIN);
        STAMP(lane == 0 && warp == 1, 2, 9);
        flag_wait_w(F_BIN, ep1 * NGW);
        STAMP(lane == 0 && warp == 1, 2, 10);
        const int myn = gw + lane * NGW < NN ? gw + lane * NGW : gw;
        int cnts = __ldcg(g_cnt + myn);
        cnts = gw + lane * NGW < NN ? (cnts > CAP ? CAP + 1 : cnts) | ((int)__ldg((const unsigned short*)P.dinv + myn) << 16) : 0;
        __syncwarp();
        g_cnt[myn] = 0;
        const uint32_t uhi = (uintptr_t)g_u >> 32, lx = lane * 16;
        uint32_t obin = gw * CAPS * 4;
        uint32_t ent = __ldcg(pofs<const uint32_t>(g_bin, obin + lane * 4)), entn = __ldcg(pofs<const uint32_t>(g_bin, obin + NGW * CAPS * 4 + lane * 4));
        int cd = __shfl_sync(0xffffffffu, cnts, 0), cb = min(cd & 0xffff, CAP), e = 0;
        uint32_t sa[4] = {0, 0, 0, 0}, sh[4] = {0, 0, 0, 0};
        auto add = [&](uint32_t x, uint32_t y, uint32_t z, uint32_t w) {
          sa[0] += x; sa[1] += y; sa[2] += z; sa[3] += w;
          sh[0] += x >> 16; sh[1] += y >> 16; sh[2] += z >> 16; sh[3] += w >> 16;
        };
        int rnd = -1, rows = -1, cdo = 0;
#pragma unroll 1
        for (;;) {
          const bool hold = rows >= 0 && rnd == 8;
          const int m = hold ? 0 : cb - e;
          uint4 v[8];
          if (m >= 8) {
#pragma unroll
            for (int k = 0; k < 8; k++) v[k] = ldcg_v(addr64(__shfl_sync(0xffffffffu, ent, k) + lx, uhi));
          } else {
#pragma unroll
            for (int k = 0; k < 8; k++) {
              v[k] = make_uint4(0, 0, 0, 0);
              if (k < 7) ldcg_if(v[k], addr64(__shfl_sync(0xffffffffu, ent, k) + lx, uhi), k < m);
            }
          }
          if (rows >= 0) {
            const int n = gw + rnd * NGW;
            if (n < NN) {
              const float di = __uint_as_float(cdo & 0xffff0000u) * (1.0f / US), nl = -di * UB * (float)rows;
#define AGG(k) pack_bf16(fmaf((float)(sa[k] - (sh[k] << 16)), di, nl), fmaf((float)sh[k], di, nl))
              *pofs<uint4>(g_agg, ((n >> 3) * 4096 + (n & 7) * 144) ^ ((lx & 0x70) | ((lx & 0x180) << 3))) = make_uint4(AGG(0), AGG(1), AGG(2), AGG(3));
            }
#pragma unroll
            for (int k = 0; k < 4; k++) sa[k] = sh[k] = 0;
            rows = -1;
            if (early && __all_sync(0xffffffffu, mbar_try_wait_nb(sb + B_EVS, 0))) { flag_release_w(F_PART + W.slotA * LN_); early = 0; }
            if (rnd == 0 || rnd == 3 || rnd == 8 || rnd == NRND - 1) flag_release_w(F_AGG + ((rnd > 0) + (rnd > 3) + (rnd > 8)) * LN_);
            if (rnd == NRND - 1) break;
            if (hold) {
              if (fin && W.slotB >= 0) {
        #pragma unroll 1
                for (int k = 0; k < 2; k++) flag_wait_w(F_PART + (k ? W.slotB : W.slotA) * LN_, ep1);
        #pragma unroll 1
                for (int b = warp - 1; b < 8; b += 3) {
                  float2* ma = g_ml + W.slotA * 128 + b * 16 + g;
                  const float2* mb = g_ml + W.slotB * 128 + b * 16 + g;
                  const float2 a0 = __ldcg(ma), a1 = __ldcg(ma + 8), b0 = __ldcg(mb), b1 = __ldcg(mb + 8);
                  const float x0 = fmaxf(a0.x, b0.x), x1 = fmaxf(a1.x, b1.x);
                  const float fa0 = ex2(a0.x - x0), fa1 = ex2(a1.x - x1), fb0 = ex2(b0.x - x0), fb1 = ex2(b1.x - x1);
                  __syncwarp();
                  if (t == 0) { ma[0] = make_float2(x0, a0.y * fa0 + b0.y * fb0); ma[8] = make_float2(x1, a1.y * fa1 + b1.y * fb1); }
                  const uint32_t ofs = ((b >> 2) * 2048 + (b & 3) * 32 + lane) * 16;
        #pragma unroll 1
                  for (int u = 0; u < 16; u += 4) {
                    uint4* pa = pofs<uint4>(g_part, W.slotA * 65536 + ofs + u * 2048);
                    const uint4* pb = pofs<const uint4>(g_part, W.slotB * 65536 + ofs + u * 2048);
                    uint4 va[4], vb[4];
        #pragma unroll
                    for (int k = 0; k < 4; k++) { va[k] = ldcg_v(pa + k * 128); vb[k] = (HINT & 2 ? ldcs_v : ldcg_v)(pb + k * 128); }
        #define FOLD(w, fa, fb) pack_bf16(bf_lo(va[k].w) * fa + bf_lo(vb[k].w) * fb, bf_hi(va[k].w) * fa + bf_hi(vb[k].w) * fb)
        #pragma unroll
                    for (int k = 3; k >= 0; k--) pa[k * 128] = make_uint4(FOLD(x, fa0, fb0), FOLD(y, fa1, fb1), FOLD(z, fa0, fb0), FOLD(w, fa1, fb1));
                  }
                }
                bar_sync(3, 96);
                if (warp == 1) asm volatile("fence.acq_rel.gpu;" ::: "memory");
              }
              if (fin && warp == 1 && lane == 0) mbar_arrive(sb + B_BG);
              while (__any_sync(0xffffffffu, clk() - c0 < GPAUSE)) {
                if (early && __all_sync(0xffffffffu, mbar_try_wait_nb(sb + B_EVS, 0))) { flag_release_w(F_PART + W.slotA * LN_); early = 0; }
                __nanosleep(500);
              }
              continue;
            }
          }
#define SUM8(f) (v[7].f + v[6].f + v[5].f + v[4].f + v[3].f + v[2].f + v[1].f + v[0].f)
          add(SUM8(x), SUM8(y), SUM8(z), SUM8(w));
          e += 8;
          if (e < cb) {
            ent = __shfl_down_sync(0xffffffffu, ent, 8);
            if (e == 32) ent = __ldcg(pofs<const uint32_t>(g_bin, obin + 128 + lx / 4));
            continue;
          }
          rnd++; rows = cb; cdo = cd;
          if ((cd & 0xffff) > CAP) {
            const int no = __shfl_sync(0xffffffffu, (int)ld_relaxed(ovf_cnt), 0);
#pragma unroll 1
            for (int i0 = 0; i0 < no; i0 += 32) {
              int2 en = __ldcg(g_ovf + min(i0 + lane, no - 1));
              uint32_t mk = __ballot_sync(0xffffffffu, en.x == gw + rnd * NGW && i0 + lane < no);
              rows += __popc(mk);
#pragma unroll 1
              while (mk) {
                const int bit = __ffs(mk) - 1; mk &= mk - 1;
                const uint4 r = ldcg_v(addr64((uint32_t)__shfl_sync(0xffffffffu, en.y, bit) + lx, uhi));
                add(r.x, r.y, r.z, r.w);
              }
            }
          }
          obin += NGW * CAPS * 4;
          ent = entn; entn = __ldcg(pofs<const uint32_t>(g_bin, obin + NGW * CAPS * 4 + lx / 4));
          cd = __shfl_sync(0xffffffffu, cnts, rnd + 1); cb = min(cd & 0xffff, CAP); e = 0;
        }
      }
      STAMP(lane == 0 && warp == 1, 2, 11);
      if ((HINT & 4) && warp == 2 && fin && lane == 0) {
        prefetch_l2(pofs<uint8_t>(P.out, W.q0 * 65536), tail ? 8192 : 65536);
        if (W.slotB >= 0) prefetch_l2(pofs<uint8_t>(g_part, W.slotA * 65536), 65536);
        prefetch_l2(pofs<uint8_t>(g_Wvo, (cta & 63) * 4096), 4096);
      }
      if (early) { mbar_wait_w(sb + B_EVS, 0); flag_release_w(F_PART + W.slotA * LN_); }
      DUMP(warp == 1 && lane == 0, 2, 8, 14);
    }
}

}

extern "C" void kernel_launch(void* const* d_in, const int* in_sizes, int n_in, void* d_out, int out_size) {
  Params P;
  P.x = (const __nv_bfloat16*)d_in[0];
  P.src = (const int*)d_in[1];
  P.dst = (const int*)d_in[2];
  P.dinv = (const __nv_bfloat16*)d_in[3];
  P.wmsg = (const __nv_bfloat16*)d_in[4];
  P.wq = (const __nv_bfloat16*)d_in[5];
  P.wk = (const __nv_bfloat16*)d_in[6];
  P.wv = (const __nv_bfloat16*)d_in[7];
  P.wout = (const __nv_bfloat16*)d_in[8];
  P.out = (__nv_bfloat16*)d_out;
  P.zero = 0;
  for (int c = 0; c < NCTA; c++) P.w[c] = make_work(c);
  static void* scr = nullptr;
  if (!scr) {
    cudaFuncSetAttribute(gps_kernel, cudaFuncAttributeMaxDynamicSharedMemorySize, SMEM_BYTES);
    cudaGetSymbolAddress(&scr, g_scr);
  }
  P.s = (Scratch*)((((uintptr_t)scr + SCR_ALIGN - 1) & ~(uintptr_t)(SCR_ALIGN - 1)) + SCR_OFS);
  P.u = (uint4*)(((uintptr_t)P.s->u + 511) & ~(uintptr_t)511);
  if (((uintptr_t)P.u >> 32) != (((uintptr_t)(P.u + NN * 32) - 1) >> 32)) P.u += NN * 32;
  gps_kernel<<<NCTA, 384, SMEM_BYTES>>>(P);
}
```

```cpp
#include <cuda_runtime.h>
#include <cuda_bf16.h>
#include <stdint.h>
#include <stddef.h>
#include <type_traits>
#define FB 5
#define MB 5
#define GSTART 18000
#define HINT 7
#define RELF 0
#define DBG 0
#define OUTW red_bf16x8
#define PACE 64
#define GPAUSE 120000
#define XDELAY 200
#define CREG 224
#define BACKOFF 1000

namespace {

constexpr int NN = 10000;
constexpr int NE = 160000;
constexpr int NQT = 79;
constexpr int NCTA = 132;
constexpr int CAP = 64;
constexpr int CAPS = 64;
constexpr int NHSIG = 105;
constexpr uint32_t WCH_B = 32768;
constexpr int NGW = (NCTA - 1) * 3;
constexpr float TAU = 16.0f;
constexpr float SAFE_N2 = 36.0f, SAFE_C = 0.6f;
#define KOFF 3
#define PSH -8.0f
#define KROT 15
constexpr float US = 256.0f, UB = 4095.0f;
constexpr float KS = 0.25f, KC = KOFF * KS;
constexpr uint32_t KS2 = 0x3e803e80u, KC2 = KOFF == 2 ? 0x3f003f00u : (KOFF == 1 ? 0x3e803e80u : 0x3f403f40u);

constexpr int NAGG = 4;
constexpr int NRND = (NN + NGW - 1) / NGW;
constexpr int NSLOT = 105;
constexpr int F_EPOCH = 0, F_H = 1, F_M = 4  , LN_ = 32;
constexpr int F_BIN = LN_, F_W = 2 * LN_, F_OVF = 3 * LN_  , F_QP = 5 * LN_, F_AGG = F_QP + NQT * LN_,
              F_PART = F_AGG + NAGG * LN_, F_END = F_PART + NSLOT * LN_;

struct Scratch {
  uint32_t flag[F_END];
  alignas(4096) uint4 M[8192];
  uint4 Wvo[8192], Wmo[8192];
  float2 ml[NSLOT * 128];
  uint32_t unsafe[96];
  int cnt[NN + 32];
  float2 stat[NQT * 128];
  alignas(4096) uint4 h[NQT * 4096];
  uint4 u[2 * NN * 32 + 32];
  uint4 qp[NQT * 4096];
  uint4 agg[NQT * 4096];
  uint4 part[NSLOT * 4096];
  int bin[(NRND + 2) * NGW * CAPS];
  int2 ovf[NE];
};
static_assert(offsetof(Scratch, h) % 128 == 0, "alignment");
#define SCR_ALIGN (2u << 20)
#define SCR_OFS 0
__device__ uint4 g_scr[(sizeof(Scratch) + SCR_ALIGN + SCR_OFS) / 16];
struct alignas(16) Work { short k0, k1; signed char q0, q1, nb0, na0, nb1, na1, slotA, slotB, loc0, nloc, own, role; };
constexpr int R_FIN = 1, R_PUB = 2, R_TAIL = 4;
struct Params {
  const __nv_bfloat16 *x, *wq, *wk;
  Scratch* s;
  uint4* u;
  __nv_bfloat16* out;
  const __nv_bfloat16 *wout, *wmsg, *wv, *dinv;
  const int *src, *dst;
  long long zero;
  Work w[NCTA];
};
constexpr int NSERV = NQT - 52;
inline Work make_work(int c) {
  Work w;
  const int gi = c / 5, r = c % 5, q = gi * 3;
  const bool helper = r & 1, mid = r == 2;
  w.q0 = helper ? q + 1 : q + (r >> 1);
  const int hb1 = (15 - MB) / 2, hb3 = 15 - MB - hb1;
  w.nb0 = helper ? (r == 1 ? hb1 : hb3) : (mid ? MB : FB);
  w.na0 = (helper ? 16 : 48) - w.nb0;
  w.k0 = helper ? (48 * 8 - MB) + (r >> 1) * (16 * 8 - hb1) : 0;
  w.q1 = q + (r & 2);
  w.k1 = 48 * 8 - FB;
  w.nb1 = helper ? 7 - FB : 0;
  w.na1 = helper ? 31 - w.nb1 : 0;
  w.slotA = 4 * gi + (helper ? r - 1 : (mid ? 0 : (r >> 1) + 1));
  w.slotB = helper ? 4 * gi + r : (mid ? 4 * gi + 2 : -1);
  w.loc0 = NSERV + gi * 2 + (r >> 1);
  w.nloc = helper;
  w.own = helper ? (r + 1) >> 1 : (mid ? 0 : 3);
  w.role = helper ? 0 : (mid ? R_FIN : R_FIN | R_PUB);
  if (c == 130) { w.nb0 = 15; w.na0 = 65; w.slotA = NSLOT - 1; w.own = 1; w.role = R_FIN | R_TAIL; }
  if (c == 131) { w.nb0 = w.na0 = w.nb1 = w.na1 = 0; w.loc0 = 0; w.nloc = NSERV; w.own = 0; }
  return w;
}
#define g_flag P.s->flag
#define g_M P.s->M
#define g_Wvo P.s->Wvo
#define g_Wmo P.s->Wmo
#define g_ml P.s->ml
#define g_unsafe P.s->unsafe
#define g_cnt P.s->cnt
#define g_h P.s->h
#define g_u P.u
#define g_stat P.s->stat
#define g_qp P.s->qp
#define g_agg P.s->agg
#define g_part P.s->part
#define g_bin P.s->bin
#define g_ovf P.s->ovf

__device__ __forceinline__ uint32_t smem_u32(const void* p) { return (uint32_t)__cvta_generic_to_shared(p); }
__device__ __forceinline__ void mbar_init(uint32_t bar, uint32_t cnt) { asm volatile("mbarrier.init.shared::cta.b64 [%0], %1;" :: "r"(bar), "r"(cnt) : "memory"); }
__device__ __forceinline__ void mbar_arrive(uint32_t bar) { asm volatile("mbarrier.arrive.shared::cta.b64 _, [%0];" :: "r"(bar) : "memory"); }
__device__ __forceinline__ void mbar_expect_tx(uint32_t bar, uint32_t bytes) { asm volatile("mbarrier.arrive.expect_tx.shared::cta.b64 _, [%0], %1;" :: "r"(bar), "r"(bytes) : "memory"); }
__device__ __forceinline__ bool mbar_try_wait(uint32_t bar, uint32_t parity) {
  uint32_t ok;
  asm volatile("{\n.reg .pred p;\nmbarrier.try_wait.parity.shared::cta.b64 p, [%1], %2;\nselp.b32 %0, 1, 0, p;\n}\n" : "=r"(ok) : "r"(bar), "r"(parity) : "memory");
  return ok;
}
__device__ __forceinline__ bool mbar_try_wait_nb(uint32_t bar, uint32_t parity) {
  uint32_t ok;
  asm volatile("{\n.reg .pred p;\nmbarrier.test_wait.parity.shared::cta.b64 p, [%1], %2;\nselp.b32 %0, 1, 0, p;\n}\n" : "=r"(ok) : "r"(bar), "r"(parity) : "memory");
  return ok;
}
__device__ __forceinline__ void mbar_wait(uint32_t bar, uint32_t parity) {
#pragma unroll 1
  for (uint32_t it = 0; it < (1u << 25); it++) if (mbar_try_wait(bar, parity)) break;
}
__device__ __forceinline__ void bulk_s2g(void* dst, uint32_t src, uint32_t bytes) {
  asm volatile("cp.async.bulk.global.shared::cta.bulk_group [%0], [%1], %2;" :: "l"(dst), "r"(src), "r"(bytes) : "memory");
}
__device__ __forceinline__ void bulk_commit() { asm volatile("cp.async.bulk.commit_group;" ::: "memory"); }
__device__ __forceinline__ void bulk_wait_read() { asm volatile("cp.async.bulk.wait_group.read 0;" ::: "memory"); }
__device__ __forceinline__ void bulk_wait_all() { asm volatile("cp.async.bulk.wait_group 0;" ::: "memory"); }
__device__ __forceinline__ bool bar_red_or(int id, int cnt, bool c) {
  uint32_t r;
  asm volatile("{\n.reg .pred p, q;\nsetp.ne.b32 q, %3, 0;\nbar.red.or.pred p, %1, %2, q;\nselp.b32 %0, 1, 0, p;\n}\n"
               : "=r"(r) : "r"(id), "r"(cnt), "r"((uint32_t)c) : "memory");
  return r != 0;
}
template <class T> __device__ __forceinline__ T* pofs(const void* base, uint32_t off) {
  asm volatile("" : "+r"(off));
  return (T*)((uint8_t*)base + off);
}
__device__ __forceinline__ const void* addr64(uint32_t lo, uint32_t hi) { uint64_t a; asm("mov.b64 %0, {%1, %2};" : "=l"(a) : "r"(lo), "r"(hi)); return (const void*)a; }
__device__ __forceinline__ uint4 ldcg_v(const void* a) {
  uint4 v;
  asm volatile("ld.volatile.global.v4.u32 {%0,%1,%2,%3}, [%4];" : "=r"(v.x), "=r"(v.y), "=r"(v.z), "=r"(v.w) : "l"(a) : "memory");
  return v;
}
__device__ __forceinline__ uint4 ldcs_v(const void* a) {
  uint4 v;
  asm volatile("ld.global.cs.v4.u32 {%0,%1,%2,%3}, [%4];" : "=r"(v.x), "=r"(v.y), "=r"(v.z), "=r"(v.w) : "l"(a) : "memory");
  return v;
}
__device__ __forceinline__ void prefetch_l2(const void* a, uint32_t bytes) { asm volatile("cp.async.bulk.prefetch.L2.global [%0], %1;" :: "l"(a), "r"(bytes) : "memory"); }
__device__ __forceinline__ void ldcg_if(uint4& v, const void* a, bool c) {
  asm volatile("{\n.reg .pred p;\nsetp.ne.b32 p, %5, 0;\n@p ld.volatile.global.v4.u32 {%0,%1,%2,%3}, [%4];\n}\n"
               : "+r"(v.x), "+r"(v.y), "+r"(v.z), "+r"(v.w) : "l"(a), "r"((uint32_t)c) : "memory");
}
__device__ __forceinline__ void cp_async16(uint32_t dst, const void* src) {
  asm volatile("cp.async.cg.shared.global [%0], [%1], 16;" :: "r"(dst), "l"(src) : "memory");
}
__device__ __forceinline__ void red_bf16x8(void* a, uint4 v) {
  asm volatile("red.global.add.noftz.v4.bf16x2 [%0], {%1,%2,%3,%4};" :: "l"(a), "r"(v.x), "r"(v.y), "r"(v.z), "r"(v.w) : "memory");
}
__device__ __forceinline__ uint32_t clk() { uint32_t c; asm volatile("mov.u32 %0, %%clock;" : "=r"(c) :: "memory"); return c; }
__device__ __forceinline__ void stsm4(uint32_t a, uint32_t r0, uint32_t r1, uint32_t r2, uint32_t r3) {
  asm volatile("stmatrix.sync.aligned.m8n8.x4.shared.b16 [%0], {%1,%2,%3,%4};" :: "r"(a), "r"(r0), "r"(r1), "r"(r2), "r"(r3) : "memory");
}
__device__ __forceinline__ uint32_t lds32(uint32_t a) { uint32_t v; asm volatile("ld.shared.u32 %0, [%1];" : "=r"(v) : "r"(a) : "memory"); return v; }
__device__ __forceinline__ void cp_commit() { asm volatile("cp.async.commit_group;" ::: "memory"); }
__device__ __forceinline__ uint32_t hmul2(uint32_t a, uint32_t b) { uint32_t d; asm("mul.rn.bf16x2 %0, %1, %2;" : "=r"(d) : "r"(a), "r"(b)); return d; }
__device__ __forceinline__ uint32_t hfma2(uint32_t a, uint32_t b, uint32_t c) { uint32_t d; asm("fma.rn.bf16x2 %0, %1, %2, %3;" : "=r"(d) : "r"(a), "r"(b), "r"(c)); return d; }
__device__ __forceinline__ uint32_t pow2_bf2(int n) { return (uint32_t)max(n + 127, 0) * 0x00800080u; }
__device__ __forceinline__ int fexp(float x) { return (int)(__float_as_uint(x) >> 23) - 127; }
__device__ __forceinline__ void bulk_g2s(uint32_t dst, const void* src, uint32_t bytes, uint32_t bar) {
  asm volatile("cp.async.bulk.shared::cta.global.mbarrier::complete_tx::bytes [%0], [%1], %2, [%3];"
    :: "r"(dst), "l"(src), "r"(bytes), "r"(bar) : "memory");
}
__device__ __forceinline__ void bulk_g2s_last(uint32_t dst, const void* src, uint32_t bytes, uint32_t bar) {
  asm volatile("{\n.reg .b64 p;\ncreatepolicy.fractional.L2::evict_first.b64 p;\n"
    "cp.async.bulk.shared::cta.global.mbarrier::complete_tx::bytes.L2::cache_hint [%0], [%1], %2, [%3], p;\n}\n"
    :: "r"(dst), "l"(src), "r"(bytes), "r"(bar) : "memory");
}
__device__ __forceinline__ void wg_fence() { asm volatile("wgmma.fence.sync.aligned;" ::: "memory"); }
__device__ __forceinline__ void wg_commit() { asm volatile("wgmma.commit_group.sync.aligned;" ::: "memory"); }
template<int N> __device__ __forceinline__ void wg_wait() { asm volatile("wgmma.wait_group.sync.aligned %0;" :: "n"(N) : "memory"); }
__device__ __forceinline__ void bar_sync(int id, int cnt) { asm volatile("bar.sync %0, %1;" :: "r"(id), "r"(cnt) : "memory"); }
__device__ __forceinline__ void fence_async_smem() { asm volatile("fence.proxy.async.shared::cta;" ::: "memory"); }
__device__ __forceinline__ void fence_async_gmem() { asm volatile("fence.proxy.async.global;" ::: "memory"); }
__device__ __forceinline__ void bar_arrive(int id, int cnt) { asm volatile("bar.arrive %0, %1;" :: "r"(id), "r"(cnt) : "memory"); }
__device__ __forceinline__ void red_release(uint32_t* p) { asm volatile("red.release.gpu.global.add.u32 [%0], 1;" :: "l"(p) : "memory"); }
__device__ __forceinline__ void red_release_w(uint32_t* p) {
  __syncwarp();
  asm volatile("{\n.reg .pred q;\n.reg .b32 l;\nmov.u32 l, %%laneid;\nsetp.eq.u32 q, l, 0;\n@q fence.release.gpu;\n@q red.relaxed.gpu.global.add.u32 [%0], 1;\n}\n" :: "l"(p) : "memory");
}
__device__ __forceinline__ void mbar_wait_w(uint32_t bar, uint32_t parity) {
#pragma unroll 1
  for (uint32_t it = 0; it < (1u << 25); it++) if (__all_sync(0xffffffffu, mbar_try_wait(bar, parity))) break;
}
#define flag_release_w(f) red_release_w(g_flag + (f))
#define flag_wait_w(f, target) poll_acquire_w(g_flag + (f), target)
#define flag_release(f) red_release(g_flag + (f))
__device__ __forceinline__ uint32_t ld_relaxed(const uint32_t* p) {
  uint32_t v; asm volatile("ld.relaxed.gpu.global.u32 %0, [%1];" : "=r"(v) : "l"(p) : "memory"); return v;
}
#define flag_wait(f, target) poll_acquire(g_flag + (f), target)
__device__ __forceinline__ void poll_acquire(const uint32_t* p, uint32_t target) {
#pragma unroll 1
  for (uint32_t it = 0; it < (1u << 23); it++) if ((int)(ld_relaxed(p) - target) >= 0) break;
  asm volatile("fence.acquire.gpu;" ::: "memory");
}
__device__ __forceinline__ void poll_acquire_w(const uint32_t* p, uint32_t target) {
#pragma unroll 1
  for (uint32_t it = 0; it < (1u << 23); it++) {
    if (__all_sync(0xffffffffu, (int)(ld_relaxed(p) - target) >= 0)) break;
    if (BACKOFF) __nanosleep(BACKOFF);
  }
  asm volatile("fence.acquire.gpu;" ::: "memory");
}
template<int N> __device__ __forceinline__ void reg_fence(float (&d)[N]) {
#pragma unroll
  for (int i = 0; i < N; i++) asm volatile("" : "+f"(d[i]) :: "memory");
}
template<int N> __device__ __forceinline__ void reg_fence(uint32_t (&d)[N]) {
#pragma unroll
  for (int i = 0; i < N; i++) asm volatile("" : "+r"(d[i]) :: "memory");
}
__device__ __forceinline__ float ex2(float x) { float y; asm("ex2.approx.ftz.f32 %0, %1;" : "=f"(y) : "f"(x)); return y; }
__device__ __forceinline__ uint32_t pack_bf16(float lo, float hi) { uint32_t r; asm("cvt.rn.bf16x2.f32 %0, %1, %2;" : "=r"(r) : "f"(hi), "f"(lo)); return r; }
__device__ __forceinline__ float bf_lo(uint32_t w) { return __uint_as_float(w << 16); }
__device__ __forceinline__ float bf_hi(uint32_t w) { return __uint_as_float(w & 0xffff0000u); }
__device__ __forceinline__ uint64_t desc_k(uint32_t addr, uint32_t add) { return (uint64_t)((((addr & 0x3FFFF) >> 4) | (1u << 16)) + add) | (0x40000100ull << 32); }
__device__ __forceinline__ uint64_t desc_mn(uint32_t addr, uint32_t add) { return (uint64_t)((((addr & 0x3FFFF) >> 4) | ((1024u >> 4) << 16)) + add) | (0x40000100ull << 32); }
__device__ __forceinline__ void sts128(uint32_t a, uint4 v) { asm volatile("st.shared.v4.u32 [%0], {%1,%2,%3,%4};" :: "r"(a), "r"(v.x), "r"(v.y), "r"(v.z), "r"(v.w) : "memory"); }
__device__ __forceinline__ uint4 lds128(uint32_t a) { uint4 v; asm volatile("ld.shared.v4.u32 {%0,%1,%2,%3}, [%4];" : "=r"(v.x), "=r"(v.y), "=r"(v.z), "=r"(v.w) : "r"(a) : "memory"); return v; }
__device__ __forceinline__ void mma16816(float (&c)[4], uint32_t a0, uint32_t a1, uint32_t a2, uint32_t a3, uint32_t b0, uint32_t b1) {
  asm volatile("mma.sync.aligned.m16n8k16.row.col.f32.bf16.bf16.f32 {%0,%1,%2,%3}, {%4,%5,%6,%7}, {%8,%9}, {%0,%1,%2,%3};"
    : "+f"(c[0]), "+f"(c[1]), "+f"(c[2]), "+f"(c[3]) : "r"(a0), "r"(a1), "r"(a2), "r"(a3), "r"(b0), "r"(b1));
}
__device__ __forceinline__ uint32_t sw_byte(int r, int c) {
  return (uint32_t)((r >> 3) * 4096 + (c >> 6) * 1024 + (r & 7) * 128 + ((((c >> 3) & 7) ^ (r & 7)) << 4) + (c & 7) * 2);
}
__device__ __forceinline__ int cta_id() { int c; asm volatile("mov.u32 %0, %%ctaid.x;" : "=r"(c)); return c; }
__device__ __forceinline__ bool tid_is(int v) { int t; asm volatile("mov.u32 %0, %%tid.x;" : "=r"(t)); return t == v; }
#define STAMP(cond, who, i)
#define CSTAMP(cond, who, i)
#define DUMP(cond, who, i0, i1)
#define XSTAMP(cond, i)
#define SSTAMP(i)

template <int OA, int OB> __device__ __forceinline__ void wgmma_ss_n256_tb(float (&d)[128], uint64_t da, uint64_t db, int scale_d) {
  asm volatile("{\n.reg .pred p;\n.reg .b64 a, b;\nsetp.ne.b32 p, %130, 0;\nadd.s64 a, %128, %131;\nadd.s64 b, %129, %132;\n"
    "wgmma.mma_async.sync.aligned.m64n256k16.f32.bf16.bf16 "
    "{%0, %1, %2, %3, %4, %5, %6, %7, %8, %9, %10, %11, %12, %13, %14, %15, %16, %17, %18, %19, %20, %21, %22, %23, %24, %25, %26, %27, %28, %29, %30, %31, %32, %33, %34, %35, %36, %37, %38, %39, %40, %41, %42, %43, %44, %45, %46, %47, %48, %49, %50, %51, %52, %53, %54, %55, %56, %57, %58, %59, %60, %61, %62, %63, %64, %65, %66, %67, %68, %69, %70, %71, %72, %73, %74, %75, %76, %77, %78, %79, %80, %81, %82, %83, %84, %85, %86, %87, %88, %89, %90, %91, %92, %93, %94, %95, %96, %97, %98, %99, %100, %101, %102, %103, %104, %105, %106, %107, %108, %109, %110, %111, %112, %113, %114, %115, %116, %117, %118, %119, %120, %121, %122, %123, %124, %125, %126, %127}, "
    "a, b, p, 1, 1, 0, 1;\n}\n"
    : "+f"(d[0]), "+f"(d[1]), "+f"(d[2]), "+f"(d[3]), "+f"(d[4]), "+f"(d[5]), "+f"(d[6]), "+f"(d[7]), "+f"(d[8]), "+f"(d[9]), "+f"(d[10]), "+f"(d[11]), "+f"(d[12]), "+f"(d[13]), "+f"(d[14]), "+f"(d[15]), "+f"(d[16]), "+f"(d[17]), "+f"(d[18]), "+f"(d[19]), "+f"(d[20]), "+f"(d[21]), "+f"(d[22]), "+f"(d[23]), "+f"(d[24]), "+f"(d[25]), "+f"(d[26]), "+f"(d[27]), "+f"(d[28]), "+f"(d[29]), "+f"(d[30]), "+f"(d[31]), "+f"(d[32]), "+f"(d[33]), "+f"(d[34]), "+f"(d[35]), "+f"(d[36]), "+f"(d[37]), "+f"(d[38]), "+f"(d[39]), "+f"(d[40]), "+f"(d[41]), "+f"(d[42]), "+f"(d[43]), "+f"(d[44]), "+f"(d[45]), "+f"(d[46]), "+f"(d[47]), "+f"(d[48]), "+f"(d[49]), "+f"(d[50]), "+f"(d[51]), "+f"(d[52]), "+f"(d[53]), "+f"(d[54]), "+f"(d[55]), "+f"(d[56]), "+f"(d[57]), "+f"(d[58]), "+f"(d[59]), "+f"(d[60]), "+f"(d[61]), "+f"(d[62]), "+f"(d[63]), "+f"(d[64]), "+f"(d[65]), "+f"(d[66]), "+f"(d[67]), "+f"(d[68]), "+f"(d[69]), "+f"(d[70]), "+f"(d[71]), "+f"(d[72]), "+f"(d[73]), "+f"(d[74]), "+f"(d[75]), "+f"(d[76]), "+f"(d[77]), "+f"(d[78]), "+f"(d[79]), "+f"(d[80]), "+f"(d[81]), "+f"(d[82]), "+f"(d[83]), "+f"(d[84]), "+f"(d[85]), "+f"(d[86]), "+f"(d[87]), "+f"(d[88]), "+f"(d[89]), "+f"(d[90]), "+f"(d[91]), "+f"(d[92]), "+f"(d[93]), "+f"(d[94]), "+f"(d[95]), "+f"(d[96]), "+f"(d[97]), "+f"(d[98]), "+f"(d[99]), "+f"(d[100]), "+f"(d[101]), "+f"(d[102]), "+f"(d[103]), "+f"(d[104]), "+f"(d[105]), "+f"(d[106]), "+f"(d[107]), "+f"(d[108]), "+f"(d[109]), "+f"(d[110]), "+f"(d[111]), "+f"(d[112]), "+f"(d[113]), "+f"(d[114]), "+f"(d[115]), "+f"(d[116]), "+f"(d[117]), "+f"(d[118]), "+f"(d[119]), "+f"(d[120]), "+f"(d[121]), "+f"(d[122]), "+f"(d[123]), "+f"(d[124]), "+f"(d[125]), "+f"(d[126]), "+f"(d[127])
    : "l"(da), "l"(db), "r"(scale_d), "n"(OA), "n"(OB));
}
template <int OA, int OB> __device__ __forceinline__ void wgmma_qk(float (&d)[64], uint64_t da, uint64_t db, int scale_d) {
  asm volatile("{\n.reg .pred p;\n.reg .b64 a, b;\nsetp.ne.b32 p, %66, 0;\nadd.s64 a, %64, %67;\nadd.s64 b, %65, %68;\n"
    "wgmma.mma_async.sync.aligned.m64n128k16.f32.bf16.bf16 "
    "{%0, %1, %2, %3, %4, %5, %6, %7, %8, %9, %10, %11, %12, %13, %14, %15, %16, %17, %18, %19, %20, %21, %22, %23, %24, %25, %26, %27, %28, %29, %30, %31, %32, %33, %34, %35, %36, %37, %38, %39, %40, %41, %42, %43, %44, %45, %46, %47, %48, %49, %50, %51, %52, %53, %54, %55, %56, %57, %58, %59, %60, %61, %62, %63}, "
    "a, b, p, 1, 1, 0, 0;\n}\n"
    : "+f"(d[0]), "+f"(d[1]), "+f"(d[2]), "+f"(d[3]), "+f"(d[4]), "+f"(d[5]), "+f"(d[6]), "+f"(d[7]), "+f"(d[8]), "+f"(d[9]), "+f"(d[10]), "+f"(d[11]), "+f"(d[12]), "+f"(d[13]), "+f"(d[14]), "+f"(d[15]), "+f"(d[16]), "+f"(d[17]), "+f"(d[18]), "+f"(d[19]), "+f"(d[20]), "+f"(d[21]), "+f"(d[22]), "+f"(d[23]), "+f"(d[24]), "+f"(d[25]), "+f"(d[26]), "+f"(d[27]), "+f"(d[28]), "+f"(d[29]), "+f"(d[30]), "+f"(d[31]), "+f"(d[32]), "+f"(d[33]), "+f"(d[34]), "+f"(d[35]), "+f"(d[36]), "+f"(d[37]), "+f"(d[38]), "+f"(d[39]), "+f"(d[40]), "+f"(d[41]), "+f"(d[42]), "+f"(d[43]), "+f"(d[44]), "+f"(d[45]), "+f"(d[46]), "+f"(d[47]), "+f"(d[48]), "+f"(d[49]), "+f"(d[50]), "+f"(d[51]), "+f"(d[52]), "+f"(d[53]), "+f"(d[54]), "+f"(d[55]), "+f"(d[56]), "+f"(d[57]), "+f"(d[58]), "+f"(d[59]), "+f"(d[60]), "+f"(d[61]), "+f"(d[62]), "+f"(d[63])
    : "l"(da), "l"(db), "r"(scale_d), "n"(OA), "n"(OB));
}
template <int OA, int OB> __device__ __forceinline__ void wgmma_qk(float (&d)[56], uint64_t da, uint64_t db, int scale_d) {
  asm volatile("{\n.reg .pred p;\n.reg .b64 a, b;\nsetp.ne.b32 p, %58, 0;\nadd.s64 a, %56, %59;\nadd.s64 b, %57, %60;\n"
    "wgmma.mma_async.sync.aligned.m64n112k16.f32.bf16.bf16 "
    "{%0, %1, %2, %3, %4, %5, %6, %7, %8, %9, %10, %11, %12, %13, %14, %15, %16, %17, %18, %19, %20, %21, %22, %23, %24, %25, %26, %27, %28, %29, %30, %31, %32, %33, %34, %35, %36, %37, %38, %39, %40, %41, %42, %43, %44, %45, %46, %47, %48, %49, %50, %51, %52, %53, %54, %55}, "
    "a, b, p, 1, 1, 0, 0;\n}\n"
    : "+f"(d[0]), "+f"(d[1]), "+f"(d[2]), "+f"(d[3]), "+f"(d[4]), "+f"(d[5]), "+f"(d[6]), "+f"(d[7]), "+f"(d[8]), "+f"(d[9]), "+f"(d[10]), "+f"(d[11]), "+f"(d[12]), "+f"(d[13]), "+f"(d[14]), "+f"(d[15]), "+f"(d[16]), "+f"(d[17]), "+f"(d[18]), "+f"(d[19]), "+f"(d[20]), "+f"(d[21]), "+f"(d[22]), "+f"(d[23]), "+f"(d[24]), "+f"(d[25]), "+f"(d[26]), "+f"(d[27]), "+f"(d[28]), "+f"(d[29]), "+f"(d[30]), "+f"(d[31]), "+f"(d[32]), "+f"(d[33]), "+f"(d[34]), "+f"(d[35]), "+f"(d[36]), "+f"(d[37]), "+f"(d[38]), "+f"(d[39]), "+f"(d[40]), "+f"(d[41]), "+f"(d[42]), "+f"(d[43]), "+f"(d[44]), "+f"(d[45]), "+f"(d[46]), "+f"(d[47]), "+f"(d[48]), "+f"(d[49]), "+f"(d[50]), "+f"(d[51]), "+f"(d[52]), "+f"(d[53]), "+f"(d[54]), "+f"(d[55])
    : "l"(da), "l"(db), "r"(scale_d), "n"(OA), "n"(OB));
}
template <int OB> __device__ __forceinline__ void wgmma_rs_n256_tb(float (&d)[128], uint32_t a0, uint32_t a1, uint32_t a2, uint32_t a3, uint64_t db, int scale_d) {
  asm volatile("{\n.reg .pred p;\n.reg .b64 b;\nsetp.ne.b32 p, %133, 0;\nadd.s64 b, %132, %134;\n"
    "wgmma.mma_async.sync.aligned.m64n256k16.f32.bf16.bf16 "
    "{%0, %1, %2, %3, %4, %5, %6, %7, %8, %9, %10, %11, %12, %13, %14, %15, %16, %17, %18, %19, %20, %21, %22, %23, %24, %25, %26, %27, %28, %29, %30, %31, %32, %33, %34, %35, %36, %37, %38, %39, %40, %41, %42, %43, %44, %45, %46, %47, %48, %49, %50, %51, %52, %53, %54, %55, %56, %57, %58, %59, %60, %61, %62, %63, %64, %65, %66, %67, %68, %69, %70, %71, %72, %73, %74, %75, %76, %77, %78, %79, %80, %81, %82, %83, %84, %85, %86, %87, %88, %89, %90, %91, %92, %93, %94, %95, %96, %97, %98, %99, %100, %101, %102, %103, %104, %105, %106, %107, %108, %109, %110, %111, %112, %113, %114, %115, %116, %117, %118, %119, %120, %121, %122, %123, %124, %125, %126, %127}, "
    "{%128, %129, %130, %131}, b, p, 1, 1, 1;\n}\n"
    : "+f"(d[0]), "+f"(d[1]), "+f"(d[2]), "+f"(d[3]), "+f"(d[4]), "+f"(d[5]), "+f"(d[6]), "+f"(d[7]), "+f"(d[8]), "+f"(d[9]), "+f"(d[10]), "+f"(d[11]), "+f"(d[12]), "+f"(d[13]), "+f"(d[14]), "+f"(d[15]), "+f"(d[16]), "+f"(d[17]), "+f"(d[18]), "+f"(d[19]), "+f"(d[20]), "+f"(d[21]), "+f"(d[22]), "+f"(d[23]), "+f"(d[24]), "+f"(d[25]), "+f"(d[26]), "+f"(d[27]), "+f"(d[28]), "+f"(d[29]), "+f"(d[30]), "+f"(d[31]), "+f"(d[32]), "+f"(d[33]), "+f"(d[34]), "+f"(d[35]), "+f"(d[36]), "+f"(d[37]), "+f"(d[38]), "+f"(d[39]), "+f"(d[40]), "+f"(d[41]), "+f"(d[42]), "+f"(d[43]), "+f"(d[44]), "+f"(d[45]), "+f"(d[46]), "+f"(d[47]), "+f"(d[48]), "+f"(d[49]), "+f"(d[50]), "+f"(d[51]), "+f"(d[52]), "+f"(d[53]), "+f"(d[54]), "+f"(d[55]), "+f"(d[56]), "+f"(d[57]), "+f"(d[58]), "+f"(d[59]), "+f"(d[60]), "+f"(d[61]), "+f"(d[62]), "+f"(d[63]), "+f"(d[64]), "+f"(d[65]), "+f"(d[66]), "+f"(d[67]), "+f"(d[68]), "+f"(d[69]), "+f"(d[70]), "+f"(d[71]), "+f"(d[72]), "+f"(d[73]), "+f"(d[74]), "+f"(d[75]), "+f"(d[76]), "+f"(d[77]), "+f"(d[78]), "+f"(d[79]), "+f"(d[80]), "+f"(d[81]), "+f"(d[82]), "+f"(d[83]), "+f"(d[84]), "+f"(d[85]), "+f"(d[86]), "+f"(d[87]), "+f"(d[88]), "+f"(d[89]), "+f"(d[90]), "+f"(d[91]), "+f"(d[92]), "+f"(d[93]), "+f"(d[94]), "+f"(d[95]), "+f"(d[96]), "+f"(d[97]), "+f"(d[98]), "+f"(d[99]), "+f"(d[100]), "+f"(d[101]), "+f"(d[102]), "+f"(d[103]), "+f"(d[104]), "+f"(d[105]), "+f"(d[106]), "+f"(d[107]), "+f"(d[108]), "+f"(d[109]), "+f"(d[110]), "+f"(d[111]), "+f"(d[112]), "+f"(d[113]), "+f"(d[114]), "+f"(d[115]), "+f"(d[116]), "+f"(d[117]), "+f"(d[118]), "+f"(d[119]), "+f"(d[120]), "+f"(d[121]), "+f"(d[122]), "+f"(d[123]), "+f"(d[124]), "+f"(d[125]), "+f"(d[126]), "+f"(d[127])
    : "r"(a0), "r"(a1), "r"(a2), "r"(a3), "l"(db), "r"(scale_d), "n"(OB));
}
template <int OB> __device__ __forceinline__ void wgmma_rs_n128_tb(float (&d)[64], uint32_t a0, uint32_t a1, uint32_t a2, uint32_t a3, uint64_t db, int scale_d) {
  asm volatile("{\n.reg .pred p;\n.reg .b64 b;\nsetp.ne.b32 p, %69, 0;\nadd.s64 b, %68, %70;\n"
    "wgmma.mma_async.sync.aligned.m64n128k16.f32.bf16.bf16 "
    "{%0, %1, %2, %3, %4, %5, %6, %7, %8, %9, %10, %11, %12, %13, %14, %15, %16, %17, %18, %19, %20, %21, %22, %23, %24, %25, %26, %27, %28, %29, %30, %31, %32, %33, %34, %35, %36, %37, %38, %39, %40, %41, %42, %43, %44, %45, %46, %47, %48, %49, %50, %51, %52, %53, %54, %55, %56, %57, %58, %59, %60, %61, %62, %63}, "
    "{%64, %65, %66, %67}, b, p, 1, 1, 1;\n}\n"
    : "+f"(d[0]), "+f"(d[1]), "+f"(d[2]), "+f"(d[3]), "+f"(d[4]), "+f"(d[5]), "+f"(d[6]), "+f"(d[7]), "+f"(d[8]), "+f"(d[9]), "+f"(d[10]), "+f"(d[11]), "+f"(d[12]), "+f"(d[13]), "+f"(d[14]), "+f"(d[15]), "+f"(d[16]), "+f"(d[17]), "+f"(d[18]), "+f"(d[19]), "+f"(d[20]), "+f"(d[21]), "+f"(d[22]), "+f"(d[23]), "+f"(d[24]), "+f"(d[25]), "+f"(d[26]), "+f"(d[27]), "+f"(d[28]), "+f"(d[29]), "+f"(d[30]), "+f"(d[31]), "+f"(d[32]), "+f"(d[33]), "+f"(d[34]), "+f"(d[35]), "+f"(d[36]), "+f"(d[37]), "+f"(d[38]), "+f"(d[39]), "+f"(d[40]), "+f"(d[41]), "+f"(d[42]), "+f"(d[43]), "+f"(d[44]), "+f"(d[45]), "+f"(d[46]), "+f"(d[47]), "+f"(d[48]), "+f"(d[49]), "+f"(d[50]), "+f"(d[51]), "+f"(d[52]), "+f"(d[53]), "+f"(d[54]), "+f"(d[55]), "+f"(d[56]), "+f"(d[57]), "+f"(d[58]), "+f"(d[59]), "+f"(d[60]), "+f"(d[61]), "+f"(d[62]), "+f"(d[63])
    : "r"(a0), "r"(a1), "r"(a2), "r"(a3), "l"(db), "r"(scale_d), "n"(OB));
}
template <int V> using IC = std::integral_constant<int, V>;
template <int I, int N, class F> __device__ __forceinline__ void static_for(F&& f) {
  if constexpr (I < N) { f(std::integral_constant<int, I>{}); static_for<I + 1, N>(f); }
}

constexpr uint32_t SM_Q = 0, SM_BAR = 7 * 32768;
constexpr uint32_t B_FULL = SM_BAR, B_EMPTY = B_FULL + 24, B_WF = B_EMPTY + 24, B_QFULL = B_WF + 32, B_QEMPTY = B_QFULL + 16,
                   B_EVH = B_QEMPTY + 16, B_EVQ = B_EVH + 8, B_EVP0 = B_EVQ + 8, B_BG = B_EVP0 + 16, B_M0 = B_BG + 8, B_HALF = B_M0 + 8,
                   SM_UNSAFE = B_HALF + 8, SM_TS = SM_UNSAFE + 8, SM_ML = (SM_TS + 192 + 15) / 16 * 16, SM_EPOCH = SM_ML + 1024, SM_END = SM_EPOCH + 16;
constexpr uint32_t POS_M = 0x5462;
constexpr int SMEM_BYTES = SM_END;

#define ROW0(u) make_uint4(pack_bf16(o[16 * u], o[16 * u + 1]), pack_bf16(o[16 * u + 4], o[16 * u + 5]), \
                           pack_bf16(o[16 * u + 8], o[16 * u + 9]), pack_bf16(o[16 * u + 12], o[16 * u + 13]))
#define ROW1(u) make_uint4(pack_bf16(o[16 * u + 2], o[16 * u + 3]), pack_bf16(o[16 * u + 6], o[16 * u + 7]), \
                           pack_bf16(o[16 * u + 10], o[16 * u + 11]), pack_bf16(o[16 * u + 14], o[16 * u + 15]))

__global__ void __launch_bounds__(384, 1) gps_kernel(const __grid_constant__ Params P) {
  extern __shared__ __align__(1024) uint8_t smem_raw[];
  constexpr uint32_t sb = 1024;
  if (smem_u32(smem_raw) != sb) return;
  const int cta = blockIdx.x;
  const int wg = __shfl_sync(0xffffffffu, (int)threadIdx.x >> 7, 0);
  const int warp = __shfl_sync(0xffffffffu, ((int)threadIdx.x >> 5) & 3, 0);
  const int lane = threadIdx.x & 31;
#define ROLE                                                                                       \
  const Work& W = P.w[cta_id()];                                                                   \
  [[maybe_unused]] const int n0 = W.nb0 + W.na0, n1 = W.nb1 + W.na1, total = n0 + n1;              \
  [[maybe_unused]] const bool fin = W.role & R_FIN, tail = W.role & R_TAIL;                        \
  [[maybe_unused]] const uint32_t posw = total == 0 || tail ? POS_M : ((total & 1) ? 0x2546 : 0x4326)
  const int g = lane >> 2, t = lane & 3;
  if (wg < 2) {
    const int tid = threadIdx.x & 127;
    ROLE;
    const uint32_t sQ = sb + SM_Q + wg * 32768;
#define st0 tid_is(wg * 128)
    STAMP(st0, wg, 0);
    const int rr = lane >> 3, j = lane & 7;
    const uint32_t c0 = clk();
    if (threadIdx.x == 0) {
      for (int i = 0; i < 3; i++) { mbar_init(sb + B_FULL + 8 * i, 1); mbar_init(sb + B_EMPTY + 8 * i, tail ? 4 : 8); }
      for (int i = 0; i < 4; i++) mbar_init(sb + B_WF + 8 * i, 1);
      for (int i = 0; i < 2; i++) { mbar_init(sb + B_QFULL + 8 * i, 1); mbar_init(sb + B_QEMPTY + 8 * i, 4); mbar_init(sb + B_EVP0 + 8 * i, 4); }
      mbar_init(sb + B_EVH, 8); mbar_init(sb + B_EVQ, 8); mbar_init(sb + B_HALF, 8); mbar_init(sb + B_BG, 1); mbar_init(sb + B_M0, 1);
      asm volatile("fence.mbarrier_init.release.cluster;" ::: "memory");
    }
    __syncwarp();
    while (clk() - c0 < XDELAY) {}
    if (total > 0) {
#pragma unroll 1
      for (int p = 0; p < 4; p++) {
        const int r = warp * 16 + p * 4 + rr;
        const uint4* px = (const uint4*)(P.x + (size_t)min(W.q0 * 128 + wg * 64 + r, NN - 1) * 256) + j;
        const uint32_t off = (r >> 3) * 4096 + (r & 7) * 128 + ((j ^ (r & 7)) << 4);
#pragma unroll
        for (int c = 0; c < 4; c++) cp_async16(sQ + off + c * 1024, px + c * 8);
        cp_commit();
      }
    }
    bar_sync(4, 384);
    if (wg == 1) bar_arrive(5, 256);

    if (total > 0) {
      {
        const bool own = (W.own >> wg) & 1;
        uint8_t* gh = (uint8_t*)g_h + (size_t)W.q0 * 65536 + wg * 32768;
#pragma unroll 1
        for (int p = 0; p < 4; p++) {
          const int r = warp * 16 + p * 4 + rr;
          const uint32_t off = (r >> 3) * 4096 + (r & 7) * 128 + ((j ^ (r & 7)) << 4);
          asm volatile("cp.async.wait_group 3;" ::: "memory");
          cp_commit();
          float f[32];
#pragma unroll
          for (int c = 0; c < 4; c++) {
            const uint4 v = lds128(sQ + off + c * 1024);
            f[c * 8 + 0] = bf_lo(v.x); f[c * 8 + 1] = bf_hi(v.x); f[c * 8 + 2] = bf_lo(v.y); f[c * 8 + 3] = bf_hi(v.y);
            f[c * 8 + 4] = bf_lo(v.z); f[c * 8 + 5] = bf_hi(v.z); f[c * 8 + 6] = bf_lo(v.w); f[c * 8 + 7] = bf_hi(v.w);
          }
          float s0 = 0.f, s1 = 0.f, s2 = 0.f, s3 = 0.f;
#pragma unroll
          for (int i = 0; i < 16; i++) { s0 += f[2 * i]; s1 += f[2 * i + 1]; s2 += f[2 * i] * f[2 * i]; s3 += f[2 * i + 1] * f[2 * i + 1]; }
          float sum = s0 + s1, ss = s2 + s3;
#pragma unroll
          for (int k = 1; k < 8; k *= 2) { sum += __shfl_xor_sync(0xffffffffu, sum, k); ss += __shfl_xor_sync(0xffffffffu, ss, k); }
          const float mean = sum * (1.0f / 256.0f);
          float var = ss * (1.0f / 256.0f) - mean * mean;
          if (__any_sync(0xffffffffu, !(mean * mean <= 16.f * var))) {
            s2 = s3 = 0.f;
#pragma unroll
            for (int i = 0; i < 16; i++) { s2 += (f[2 * i] - mean) * (f[2 * i] - mean); s3 += (f[2 * i + 1] - mean) * (f[2 * i + 1] - mean); }
            ss = s2 + s3;
#pragma unroll
            for (int k = 1; k < 8; k *= 2) ss += __shfl_xor_sync(0xffffffffu, ss, k);
            var = ss * (1.0f / 256.0f);
          }
          float rs;
          asm("rsqrt.approx.ftz.f32 %0, %1;" : "=f"(rs) : "f"(var + 1e-5f));
          if (W.q0 * 128 + wg * 64 + r >= NN) rs = 0.f;
          const float nb = -mean * rs;
          if (own && j == 0) g_stat[W.q0 * 128 + wg * 64 + r] = make_float2(rs, nb);
#pragma unroll
          for (int c = 0; c < 4; c++) {
            uint4 h4 = make_uint4(pack_bf16(fmaf(f[c * 8], rs, nb), fmaf(f[c * 8 + 1], rs, nb)), pack_bf16(fmaf(f[c * 8 + 2], rs, nb), fmaf(f[c * 8 + 3], rs, nb)),
                                  pack_bf16(fmaf(f[c * 8 + 4], rs, nb), fmaf(f[c * 8 + 5], rs, nb)), pack_bf16(fmaf(f[c * 8 + 6], rs, nb), fmaf(f[c * 8 + 7], rs, nb)));
            sts128(sQ + off + c * 1024, h4);
            if (c == 3) {
              const float rk = rs * KS, e = fmaf(j == 7 ? nb - 0.5f * fmaf(f[31], rs, nb) : nb, KS, KC);
              h4 = make_uint4(pack_bf16(fmaf(f[24], rk, e), fmaf(f[25], rk, e)), pack_bf16(fmaf(f[26], rk, e), fmaf(f[27], rk, e)),
                              pack_bf16(fmaf(f[28], rk, e), fmaf(f[29], rk, e)), pack_bf16(fmaf(f[30], rk, e), j == 7 ? KC : fmaf(f[31], rk, e)));
            } else {
              h4 = make_uint4(hfma2(h4.x, KS2, KC2), hfma2(h4.y, KS2, KC2), hfma2(h4.z, KS2, KC2), hfma2(h4.w, KS2, KC2));
            }
            if (own) *(uint4*)(gh + off + c * 1024) = h4;
          }
        }
        __syncwarp();
        if (lane == 0) mbar_arrive(sb + B_EVH);
        fence_async_smem();
        bar_sync(1 + wg, 128);
      }
    }
    asm volatile("setmaxnreg.inc.sync.aligned.u32 %0;" :: "n"(CREG));
    STAMP(st0, wg, 1);

    float o[128];
    int qph = 0, st = tail ? wg : 0, ph = 0;
    auto release = [&](int stg) { if (lane == 0) mbar_arrive(sb + B_EMPTY + 8 * stg); };
    int resume = total > 0 ? -1 : 0;
    auto run = [&](auto hot_) __attribute__((always_inline)) {
    constexpr bool HOT = hot_.value;
    const int nloc = P.w[cta_id()].nloc;
    if (!HOT && resume == 0) {
#pragma unroll 1
      for (int i = 0; i < 32; i++) {
        const int r = i * 8 + wg * 4 + warp;
        cp_async16(sb + ((POS_M >> (r >> 6) * 4) & 15) * 32768 + sw_byte(r & 63, lane * 8), (const uint4*)P.wout + r * 32 + lane);
      }
    }
#pragma unroll 1
    for (int step = HOT || resume ? -1 : -4; step < nloc; step++) {
      ROLE;
      const bool isq = HOT && step < 0, isw = !HOT && step < 0;
      bool wide = false;
      if (HOT || step >= 0 || resume == 0) {
      if (isw) {
        const uint4* src = (const uint4*)(step < -2 ? P.wmsg : P.wv) + ((step & 1) * 128 + wg * 64 + warp) * 32 + lane;
        float cw[8] = {0.f, 0.f, 0.f, 0.f, 0.f, 0.f, 0.f, 0.f};
#pragma unroll 1
        for (int i = 0; i < 16; i++) cp_async16(sQ + sw_byte(i * 4 + warp, lane * 8), src + i * 128);
        cp_commit();
#pragma unroll
        for (int i = 0; i < 8; i++) {
          const uint4 v = __ldg((const uint4*)(step < -2 ? P.wmsg : P.wv) + (248 + i) * 32 + lane);
          const float k = step < -2 ? 0.f : (i == 7 ? -1.0f / 4.5f : -0.5f / 4.5f);
          cw[0] += bf_lo(v.x) * k; cw[1] += bf_hi(v.x) * k; cw[2] += bf_lo(v.y) * k; cw[3] += bf_hi(v.y) * k;
          cw[4] += bf_lo(v.z) * k; cw[5] += bf_hi(v.z) * k; cw[6] += bf_lo(v.w) * k; cw[7] += bf_hi(v.w) * k;
        }
        asm volatile("cp.async.wait_group 0;" ::: "memory");
#pragma unroll 1
        for (int i = 0; i < 16; i++) {
          const uint32_t ad = sQ + sw_byte(i * 4 + warp, lane * 8);
          const uint4 v = lds128(ad);
          uint4 w4 = make_uint4(pack_bf16(bf_lo(v.x) + cw[0], bf_hi(v.x) + cw[1]), pack_bf16(bf_lo(v.y) + cw[2], bf_hi(v.y) + cw[3]),
                                pack_bf16(bf_lo(v.z) + cw[4], bf_hi(v.z) + cw[5]), pack_bf16(bf_lo(v.w) + cw[6], bf_hi(v.w) + cw[7]));
          if (step == -1 && wg * 64 + i * 4 + warp == 127) w4 = make_uint4(0, 0, 0, 0);
          sts128(ad, w4);
        }
        fence_async_smem();
        bar_sync(7, 256);
      } else {
        SSTAMP(0);
        if (!isq) { mbar_wait(sb + B_QFULL + 8 * wg, qph); qph ^= 1; }
        STAMP(st0 && step == 0, wg, 8);
        SSTAMP(1);
        bar_sync(5 + wg, 256);
        SSTAMP(2);
      }
#pragma unroll 1
      for (int c = 0; c < 4; c++) {
        if (isq || step == 0) mbar_wait(isq && c == 0 ? sb + B_M0 : sb + B_WF + 8 * c, !isq && (HOT || resume));
        const int turn2 = isq ? 1 : (HOT || resume ? 3 : 4);
        if (c == turn2) bar_sync(5 + wg, 256);
        wg_fence();
        const uint64_t dA = desc_k(sb + SM_Q, wg * 2048 + c * 64), dW = desc_mn(sb, (((isq ? POS_M : posw) >> c * 4) & 15) * 2048);
        static_for<0, 4>([&](auto k) {
          if (k.value == 1) { if (isq && c == 0) mbar_wait(sb + B_WF, 0); wg_fence(); }
          wgmma_ss_n256_tb<k.value * 2, k.value * 512>(o, dA, dW, k.value > 0 ? 1 : c);
        });
        wg_commit();
        if ((c == 3 || c == turn2 - 1) && !isw) bar_arrive(6 - wg, 256);
        if (c == 0 && isq) { wg_wait<0>(); if (!tail) release(0); }
        wg_wait<1>();
      }
      wg_wait<0>();
      reg_fence(o);
      if (!isq) {
        STAMP(st0 && step == 0, wg, 9);
        SSTAMP(3);
        if (isw) bar_sync(1 + wg, 128); else if (lane == 0) mbar_arrive(sb + B_QEMPTY + 8 * wg);
        uint8_t* dw = (uint8_t*)(step < -2 ? g_Wmo : g_Wvo) + ((step & 1) * 2 + wg) * 32768 + warp * 8192 + g * 128;
        const int row0 = (W.loc0 + step) * 128 + wg * 64 + warp * 16;
        uint4 r[16];
#pragma unroll
        for (int u = 0; u < 8; u++) { r[2 * u] = ROW0(u); r[2 * u + 1] = ROW1(u); }
        if (isw) {
#pragma unroll
          for (int u = 0; u < 16; u++) *(uint4*)(dw + (u >> 2) * 1024 + ((((u & 2) * 2 + t) ^ g) << 4) + (u & 1) * 4096) = r[u];
        } else if (row0 < NN) {
          uint4* po = (uint4*)(P.out + (size_t)(row0 + g) * 256) + t;
          uint32_t c1 = clk();
#pragma unroll
          for (int u = 0; u < 16; u++) {
            if (!(DBG & 1) || !HOT || P.zero) red_bf16x8(po + (u >> 1) * 4 + (u & 1) * 256, r[u]);
            if (!HOT) { c1 += PACE; while ((int)(clk() - c1) < 0) {} }
          }
        }
        if (!HOT && step == -1) { bar_sync(7, 256); if (tid_is(0)) flag_release(F_W); __syncwarp(); STAMP(st0, wg, 3); }
        continue;
      }
      if (!tail) release(1);
      STAMP(st0, wg, 2);
      float c0 = (o[124] + (t == 3 ? 2.f : 1.f) * o[125]) * (-0.5f / 4.5f), c1 = (o[126] + (t == 3 ? 2.f : 1.f) * o[127]) * (-0.5f / 4.5f);
      c0 += __shfl_xor_sync(0xffffffffu, c0, 1); c1 += __shfl_xor_sync(0xffffffffu, c1, 1);
      c0 += __shfl_xor_sync(0xffffffffu, c0, 2); c1 += __shfl_xor_sync(0xffffffffu, c1, 2);
      float r0 = t == 3 ? 0.f : o[125], r1 = t == 3 ? 0.f : o[127], r2 = o[124], r3 = o[126];
#pragma unroll
      for (int i = 0; i < 31; i++) { r2 += o[4 * i]; r0 += o[4 * i + 1]; r3 += o[4 * i + 2]; r1 += o[4 * i + 3]; }
      r0 += r2; r1 += r3;
      r0 += __shfl_xor_sync(0xffffffffu, r0, 1); r1 += __shfl_xor_sync(0xffffffffu, r1, 1);
      r0 += __shfl_xor_sync(0xffffffffu, r0, 2); r1 += __shfl_xor_sync(0xffffffffu, r1, 2);
      r0 = fmaf(c0, -255.f, PSH / KC - r0); r1 = fmaf(c1, -255.f, PSH / KC - r1);
      wide = !(fabsf(c0) <= SAFE_C / KS) || !(fabsf(c1) <= SAFE_C / KS);
      bar_sync(1 + wg, 128);
#pragma unroll
      for (int k = 0; k < 16; k++)
        stsm4(sQ + warp * 8192 + ((lane >> 3) & 1) * 4096 + (k >> 2) * 1024 + (lane & 7) * 128 + ((((k & 3) * 2 + (lane >> 4)) ^ (lane & 7)) << 4),
              pack_bf16(o[8 * k] + c0, o[8 * k + 1] + c0), pack_bf16(o[8 * k + 2] + c1, o[8 * k + 3] + c1),
              pack_bf16(o[8 * k + 4] + c0, k == 15 && t == 3 ? r0 : o[8 * k + 5] + c0), pack_bf16(o[8 * k + 6] + c1, k == 15 && t == 3 ? r1 : o[8 * k + 7] + c1));
      fence_async_smem();
      bar_sync(1 + wg, 128);
      STAMP(st0, wg, 3);
      if (tail) { bar_sync(7, 256); if (wg == 0) { release(0); release(1); release(2); } }
      }

      float m0, m1;
      const int qh = tail ? 0 : wg, tl = W.role >> 2;
      uint32_t qo = qh * 2048;
      const uint32_t ko = (2 - tl) * 2048, stop = 1 + tl + (uint32_t)P.zero;
      float l0, l1;
      auto row_sums = [&]() { l0 = __shfl_sync(0xffffffffu, o[125] + 0.f, lane | 3); l1 = __shfl_sync(0xffffffffu, o[127] + 0.f, lane | 3); };
#define PART(u) make_uint4(pack_bf16(o[8 * u] - l0, o[8 * u + 1] - l0), pack_bf16(o[8 * u + 2] - l1, o[8 * u + 3] - l1), \
                           pack_bf16(o[8 * u + 4] - l0, o[8 * u + 5] - l0), pack_bf16(o[8 * u + 6] - l1, o[8 * u + 7] - l1))
      bool unsafe = !HOT;
#pragma unroll 1
      for (int seg = HOT ? 0 : resume - 1;; seg++) {
        ROLE;
        const bool last = __any_sync(0xffffffffu, seg || n1 == 0);
        m0 = m1 = !HOT && unsafe ? -INFINITY : 0.f;
        int first = 1;
        auto tile = [&](auto n_, bool endseg) __attribute__((always_inline)) -> bool {
          constexpr int N = n_.value;
          float s[N / 2]; uint32_t p[N / 4];
          if (!mbar_try_wait(sb + B_FULL + 8 * st, ph)) mbar_wait(sb + B_FULL + 8 * st, ph);
          const bool again = !HOT && N == 112 && first && !seg;
          if (HOT || N == 128) bar_sync(5 + wg, 256);
          else asm volatile("{\n.reg .pred p;\nsetp.eq.u32 p, %1, 0;\n@p bar.sync %0, 256;\n}\n" :: "r"(5 + wg), "r"((uint32_t)again) : "memory");
          wg_fence();
          const uint64_t dQ = desc_k(sb + SM_Q, qo), dK = desc_k(sb, ko + st * 4096);
          qo += (uint32_t)P.zero;
          static_for<0, 16>([&](auto k) { constexpr int kk = (k.value + KROT) & 15, off = (kk >> 2) * 64 + (kk & 3) * 2; wgmma_qk<off, off>(s, dQ, dK, k.value > 0); });
          wg_commit();
          if (HOT || N == 128) bar_arrive(6 - wg, 256);
          else asm volatile("{\n.reg .pred p;\nsetp.eq.u32 p, %1, 0;\n@p bar.arrive %0, 256;\n}\n" :: "r"(6 - wg), "r"((uint32_t)again) : "memory");
          if (HOT && N == 112 && first && !seg) {
            float a0 = 0.f, a1 = 0.f, a2 = 0.f, a3 = 0.f;
#pragma unroll
            for (int i = 0; i < 32; i++) { a0 += o[4 * i] * o[4 * i]; a2 += o[4 * i + 1] * o[4 * i + 1]; a1 += o[4 * i + 2] * o[4 * i + 2]; a3 += o[4 * i + 3] * o[4 * i + 3]; }
            a0 += a2; a1 += a3;
            a0 += __shfl_xor_sync(0xffffffffu, a0, 1); a1 += __shfl_xor_sync(0xffffffffu, a1, 1);
            a0 += __shfl_xor_sync(0xffffffffu, a0, 2); a1 += __shfl_xor_sync(0xffffffffu, a1, 2);
            unsafe = __any_sync(0xffffffffu, bar_red_or(tail ? 7 : 1 + wg, tail ? 256 : 128, wide || !(a0 <= SAFE_N2 / (KS * KS)) || !(a1 <= SAFE_N2 / (KS * KS))));
            if (lane == 0) { asm volatile("st.shared.u8 [%0], %1;" :: "r"(sb + SM_UNSAFE + wg), "r"((uint32_t)unsafe) : "memory"); mbar_arrive(sb + B_EVQ); }
          }
          STAMP(N == 112 && first && !seg && st0, wg, 0);
          wg_wait<0>();
          reg_fence(s);
          if (HOT && N == 112 && unsafe) return true;
          if (endseg) { if (lane == 0) mbar_arrive(sb + B_QEMPTY + 8 * wg); }
          if (!HOT && unsafe) {
            float a0 = fmaxf(s[0], s[1]), a1 = fmaxf(s[2], s[3]);
#pragma unroll
            for (int i = 1; i < N / 8; i++) { a0 = fmaxf(a0, fmaxf(s[4 * i], s[4 * i + 1])); a1 = fmaxf(a1, fmaxf(s[4 * i + 2], s[4 * i + 3])); }
            if (__any_sync(0xffffffffu, (a0 > m0 + TAU) || (a1 > m1 + TAU))) {
              a0 = fmaxf(a0, __shfl_xor_sync(0xffffffffu, a0, 1)); a1 = fmaxf(a1, __shfl_xor_sync(0xffffffffu, a1, 1));
              a0 = fmaxf(a0, __shfl_xor_sync(0xffffffffu, a0, 2)); a1 = fmaxf(a1, __shfl_xor_sync(0xffffffffu, a1, 2));
              const float x0 = ceilf(fmaxf(m0, a0)), x1 = ceilf(fmaxf(m1, a1)), sc0 = ex2(m0 - x0), sc1 = ex2(m1 - x1);
              m0 = x0; m1 = x1;
#pragma unroll
              for (int i = 0; i < 32; i++) { o[4 * i] *= sc0; o[4 * i + 1] *= sc0; o[4 * i + 2] *= sc1; o[4 * i + 3] *= sc1; }
            }
#pragma unroll
            for (int i = 0; i < N / 8; i++) { s[4 * i] -= m0; s[4 * i + 1] -= m0; s[4 * i + 2] -= m1; s[4 * i + 3] -= m1; }
          }
          auto pv = [&](auto k) { wgmma_rs_n256_tb<k.value * 512 + (63 << 16)>(o, p[4 * k.value], p[4 * k.value + 1], p[4 * k.value + 2], p[4 * k.value + 3], dK, k.value > 0 || N == 128 ? 1 : !first); };
#pragma unroll
          for (int i = 0; i < 16; i++) { p[i] = pack_bf16(ex2(s[2 * i]), ex2(s[2 * i + 1])); asm volatile("" : "+r"(p[i]) :: "memory"); }
          reg_fence(o);
          do bar_sync(5 + wg, 256); while (P.zero);
          wg_fence();
          static_for<0, 4>(pv);
          wg_commit();
#pragma unroll
          for (int i = 16; i < N / 4; i++) { p[i] = pack_bf16(ex2(s[2 * i]), ex2(s[2 * i + 1])); asm volatile("" : "+r"(p[i]) :: "memory"); }
          wg_fence();
          static_for<4, N / 16>(pv);
          wg_commit();
          bar_arrive(6 - wg, 256);
          if (N == 128) { wg_wait<1>(); if (endseg && last) { if (lane == 0) mbar_arrive(sb + B_HALF); } }
          wg_wait<0>();
          reg_fence(o); reg_fence(p);
          release(st);
          if (st) { st--; ph ^= 1; } else st = stop;
          return false;
        };
#pragma unroll 1
        for (int left = tail ? 8 - wg : (seg ? W.nb1 : W.nb0); left > 0; left--) { if (tile(IC<112>{}, false)) { resume = 1; return; } STAMP(first && !seg && st0, wg, 4); first = 0; }
#pragma unroll 1
        for (int left = tail ? 32 + wg : (seg ? W.na1 : W.na0); left > 0; left--) tile(IC<128>{}, left == 1);
        STAMP(st0 && last, wg, 6);
        {
        ROLE;
        if (last && fin && !(tail && wg == 1)) break;
        row_sums();
        if (last) mbar_wait(sb + (tail ? B_QEMPTY : B_HALF), 0);
        const uint32_t sp = sb + (tail ? 0 : (last ? (posw >> 12) + wg : (wg ? 4 - 2 * st : 6))) * 32768, sm = sb + SM_ML + (tail ? 0 : wg) * 512;
#pragma unroll
        for (int u = 0; u < 16; u++) sts128(sp + (u * 128 + tid) * 16, PART(u));
        if (t == 0) {
          asm volatile("st.shared.v2.f32 [%0], {%1,%2};" :: "r"(sm + (warp * 16 + g) * 8), "f"(m0), "f"(l0) : "memory");
          asm volatile("st.shared.v2.f32 [%0], {%1,%2};" :: "r"(sm + (warp * 16 + g) * 8 + 64), "f"(m1), "f"(l1) : "memory");
        }
        __syncwarp();
        if (lane == 0) mbar_arrive(sb + B_EVP0 + 8 * wg);
        STAMP(st0 && last, wg, 7);
        if (last) break;
        mbar_wait(sb + B_QFULL + 8 * wg, qph); qph ^= 1;
        uint32_t u; asm volatile("ld.shared.u8 %0, [%1];" : "=r"(u) : "r"(sb + SM_UNSAFE + wg) : "memory");
        unsafe = __any_sync(0xffffffffu, u != 0);
        if (HOT && unsafe) { resume = 2; return; }
        }
      }

      if (P.w[cta_id()].role & R_FIN) {
        ROLE;
        if (tail && wg == 1) break;
        row_sums();
        const int rl = wg * 64 + warp * 16 + g;
        uint32_t a[64];
#pragma unroll
        for (int i = 0; i < 64; i++) a[i] = pack_bf16(o[2 * i] - (i & 1 ? l1 : l0), o[2 * i + 1] - (i & 1 ? l1 : l0));
        reg_fence(a);
        {
          float2 e0, e1;
          mbar_wait(sb + B_QFULL + 8 * wg, qph);
          asm volatile("ld.shared.v2.f32 {%0,%1}, [%2];" : "=f"(e0.x), "=f"(e0.y) : "r"(sb + SM_ML + rl * 8) : "memory");
          asm volatile("ld.shared.v2.f32 {%0,%1}, [%2];" : "=f"(e1.x), "=f"(e1.y) : "r"(sb + SM_ML + rl * 8 + 64) : "memory");
          STAMP(st0, wg, 7);
          uint4 v[16];
#pragma unroll
          for (int u = 0; u < 16; u++) v[u] = lds128(sQ + (u * 128 + tid) * 16);
          uint32_t fb0 = 0x3f803f80u, fb1 = 0x3f803f80u;
          const float s0 = l0 + e0.y, s1 = l1 + e1.y;
          if (__any_sync(0xffffffffu, m0 != e0.x || m1 != e1.x || !(fmaxf(s0, s1) < 0x1p40f) || !(fminf(s0, s1) > 0x1p-40f))) {
            const float x0 = fmaxf(m0, e0.x), x1 = fmaxf(m1, e1.x);
            const float d0 = fmaxf(m0 - x0, -1000.f), d1 = fmaxf(m1 - x1, -1000.f), f0 = fmaxf(e0.x - x0, -1000.f), f1 = fmaxf(e1.x - x1, -1000.f);
            l0 = l0 * ex2(d0) + e0.y * ex2(f0); l1 = l1 * ex2(d1) + e1.y * ex2(f1);
            const int E0 = fexp(l0), E1 = fexp(l1);
            const uint32_t fa0 = pow2_bf2((int)d0 - E0), fa1 = pow2_bf2((int)d1 - E1);
            fb0 = pow2_bf2((int)f0 - E0); fb1 = pow2_bf2((int)f1 - E1);
            l0 = __uint_as_float(__float_as_uint(l0) - (E0 << 23)); l1 = __uint_as_float(__float_as_uint(l1) - (E1 << 23));
#pragma unroll
            for (int i = 0; i < 32; i++) { a[2 * i] = hmul2(a[2 * i], fa0); a[2 * i + 1] = hmul2(a[2 * i + 1], fa1); }
          } else { l0 = s0; l1 = s1; }
#pragma unroll
          for (int u = 0; u < 16; u++) {
            a[4 * u] = hfma2(v[u].x, fb0, a[4 * u]); a[4 * u + 1] = hfma2(v[u].y, fb1, a[4 * u + 1]);
            a[4 * u + 2] = hfma2(v[u].z, fb0, a[4 * u + 2]); a[4 * u + 3] = hfma2(v[u].w, fb1, a[4 * u + 3]);
          }
        }
        float fs0, fs1;
        asm("rcp.approx.ftz.f32 %0, %1;" : "=f"(fs0) : "f"(l0 * (KS / KC))); asm("rcp.approx.ftz.f32 %0, %1;" : "=f"(fs1) : "f"(l1 * (KS / KC)));
        STAMP(st0, wg, 8);
        reg_fence(a);
        bar_sync(5 + wg, 256);
        uint64_t dW[4];
        float y0[64], y1[64];
        auto half0 = [&](auto u_) {
          constexpr int u = u_.value;
          if (u % 4 == 0) { mbar_wait(sb + B_WF + 2 * u, 1); wg_fence(); dW[u / 4] = desc_mn(sb, ((posw >> u) & 15) * 2048); }
          wgmma_rs_n128_tb<(u & 3) * 512>(y0, a[4 * u], a[4 * u + 1], a[4 * u + 2], a[4 * u + 3], dW[u / 4], u != 0);
        };
        auto half1 = [&](auto u_) {
          constexpr int u = u_.value;
          wgmma_rs_n128_tb<(u & 3) * 512 + 128>(y1, a[4 * u], a[4 * u + 1], a[4 * u + 2], a[4 * u + 3], dW[u / 4], u != 0);
        };
        const bool wr = W.q0 * 128 + wg * 64 + warp * 16 < NN;
        uint4* po = (uint4*)(P.out + (size_t)(W.q0 * 128 + rl) * 256) + t;
        auto emit = [&](const float* y, uint4* dst) {
          if (wr && (!(DBG & 2) || P.zero)) {
            OUTW(dst, make_uint4(pack_bf16(y[0] * fs0, y[1] * fs0), pack_bf16(y[4] * fs0, y[5] * fs0), pack_bf16(y[8] * fs0, y[9] * fs0), pack_bf16(y[12] * fs0, y[13] * fs0)));
            OUTW(dst + 8 * 32, make_uint4(pack_bf16(y[2] * fs1, y[3] * fs1), pack_bf16(y[6] * fs1, y[7] * fs1), pack_bf16(y[10] * fs1, y[11] * fs1), pack_bf16(y[14] * fs1, y[15] * fs1)));
          }
          wg_fence();
        };
        static_for<0, 16>(half0);
        wg_commit();
        static_for<0, 4>(half1);
        wg_commit();
        wg_wait<1>();
        reg_fence(y0);
        emit(y0, po); static_for<4, 8>(half1);
        emit(y0 + 16, po + 4); static_for<8, 12>(half1);
        emit(y0 + 32, po + 8); static_for<12, 16>(half1);
        wg_commit();
        bar_arrive(6 - wg, 256);
        emit(y0 + 48, po + 12);
        wg_wait<0>();
        reg_fence(a); reg_fence(y1);
        STAMP(st0, wg, 9);
#pragma unroll
        for (int u = 0; u < 4; u++) emit(y1 + 16 * u, po + 16 + 4 * u);
        break;
      }
    }
    STAMP(st0, wg, 11);
    DUMP(st0, wg, 0, 16);
    if (!P.zero) { asm volatile("exit;"); __builtin_unreachable(); }
#pragma unroll
    for (int i = 0; i < 32; i++)
      asm volatile("ld.volatile.shared.v4.f32 {%0,%1,%2,%3}, [%4];" : "=f"(o[4 * i]), "=f"(o[4 * i + 1]), "=f"(o[4 * i + 2]), "=f"(o[4 * i + 3]) : "r"(sb) : "memory");
    };
    if (resume < 0) run(std::true_type{});
    run(std::false_type{});
    asm volatile("setmaxnreg.dec.sync.aligned.u32 %0;" :: "n"(504 - 2 * CREG));
  } else {
    STAMP(lane == 0 && warp == 0, 2, 0);
        const int mi = cta >> 3;
    const uint32_t sW = sb + 3 * 32768;
    uint4 wa[4], wb[8];
    {
      const uint4* pq = (const uint4*)(P.wq + ((mi & 15) * 16 + g) * 256) + warp * 8 + t;
      const uint4* pk = (const uint4*)(P.wk + ((cta & 7) * 32 + g) * 256) + warp * 8 + t;
#pragma unroll
      for (int i = 0; i < 4; i++) wa[i] = __ldg(pq + (i >> 1) * 256 + (i & 1) * 4);
#pragma unroll
      for (int i = 0; i < 8; i++) wb[i] = __ldg(pk + (i >> 1) * 256 + (i & 1) * 4);
    }
    bar_sync(4, 384);
    {
#pragma unroll
      for (int n = 0; n < 4; n++) {
        float c[4] = {0.f, 0.f, 0.f, 0.f};
#pragma unroll
        for (int u = 0; u < 2; u++) {
          mma16816(c, wa[u].x, wa[2 + u].x, wa[u].y, wa[2 + u].y, wb[2 * n + u].x, wb[2 * n + u].y);
          mma16816(c, wa[u].z, wa[2 + u].z, wa[u].w, wa[2 + u].w, wb[2 * n + u].z, wb[2 * n + u].w);
        }
        asm volatile("st.shared.v2.f32 [%0], {%1,%2};" :: "r"(sW + ((warp * 16 + g) * 40 + n * 8 + 2 * t) * 4), "f"(c[0]), "f"(c[1]) : "memory");
        asm volatile("st.shared.v2.f32 [%0], {%1,%2};" :: "r"(sW + ((warp * 16 + g + 8) * 40 + n * 8 + 2 * t) * 4), "f"(c[2]), "f"(c[3]) : "memory");
      }
      STAMP(lane == 0 && warp == 0, 2, 7);
      bar_sync(3, 128);
      if (warp < 2) {
        float c[8] = {0.f, 0.f, 0.f, 0.f, 0.f, 0.f, 0.f, 0.f};
#pragma unroll
        for (int k = 0; k < 4; k++) {
          const uint4 v = lds128(sW + ((k * 16 + warp * 8 + g) * 40 + t * 8) * 4), w = lds128(sW + ((k * 16 + warp * 8 + g) * 40 + t * 8 + 4) * 4);
          c[0] += __uint_as_float(v.x); c[1] += __uint_as_float(v.y); c[2] += __uint_as_float(v.z); c[3] += __uint_as_float(v.w);
          c[4] += __uint_as_float(w.x); c[5] += __uint_as_float(w.y); c[6] += __uint_as_float(w.z); c[7] += __uint_as_float(w.w);
        }
        const float ms = 1.4426950408889634f / 16.0f / KS;
        if (cta < 128)
          *(uint4*)((uint8_t*)g_M + sw_byte(mi * 16 + warp * 8 + g, (cta & 7) * 32 + t * 8)) =
              make_uint4(pack_bf16(c[0] * ms, c[1] * ms), pack_bf16(c[2] * ms, c[3] * ms), pack_bf16(c[4] * ms, c[5] * ms), pack_bf16(c[6] * ms, c[7] * ms));
      }
    }
    asm volatile("setmaxnreg.dec.sync.aligned.u32 %0;" :: "n"(504 - 2 * CREG));
    STAMP(lane == 0 && warp == 0, 2, 13);
    bar_sync(3, 128);
#define ep1 (lds32(sb + SM_EPOCH) + 1)
    if (threadIdx.x == 256 && cta < 128) flag_release(F_M + (cta >> 5));
    __syncwarp();
    ROLE;
    if (warp == 3 && W.own) { mbar_wait_w(sb + B_EVH, 0); flag_release_w(F_H); STAMP(lane == 0, 2, 6); }
    if (warp == 0) {
      if (lane == 0) {
        STAMP(true, 2, 1);
        const uint32_t epoch = ld_relaxed(g_flag + F_EPOCH);
        if (total > 0) {
#pragma unroll
          for (int c = 0; c < 3; c++) mbar_expect_tx(sb + B_WF + 8 * c, c == 0 ? WCH_B - 8192 : WCH_B);
          mbar_expect_tx(sb + B_M0, 8192);
          int c = 0;
#pragma unroll 1
          for (uint32_t it = 0; c < 4; it++) {
            uint4 f;
            asm volatile("ld.relaxed.gpu.global.v4.u32 {%0,%1,%2,%3}, [%4];" : "=r"(f.x), "=r"(f.y), "=r"(f.z), "=r"(f.w) : "l"(g_flag + F_M) : "memory");
            uint32_t tm;
            asm volatile("mad.lo.u32 %0, %1, 32, 32;" : "=r"(tm) : "r"(epoch));
            int ok = (int)(f.x - tm) < 0 ? 0 : (int)(f.y - tm) < 0 ? 1 : (int)(f.z - tm) < 0 ? 2 : (int)(f.w - tm) < 0 ? 3 : 4;
            if (it > (1u << 23)) ok = 4;
            if (ok > c) {
              asm volatile("fence.acquire.gpu;" ::: "memory"); fence_async_gmem();
              if (c == 0) bulk_g2s(sb + (POS_M & 15) * 32768, g_M, 8192, sb + B_M0);
            }
#pragma unroll 1
            for (; c < ok; c++) {
              const uint32_t skip = c == 0 ? 8192 : 0;
              bulk_g2s(sb + ((POS_M >> c * 4) & 15) * 32768 + skip, pofs<const uint8_t>(g_M, c * WCH_B + skip), WCH_B - skip, sb + B_WF + 8 * c);
              STAMP(c == 0, 2, 2);
            }
          }
        }
        asm volatile("st.shared.u32 [%0], %1;" :: "r"(sb + SM_EPOCH), "r"(epoch) : "memory");
        if (total > 0) mbar_expect_tx(sb + B_WF + 24, WCH_B);
        int st = 0, ph = 0, qph = 0;
        const int nsl = tail ? 3 : 2;
        auto next_slot = [&]() { mbar_wait(sb + B_EMPTY + 8 * st, ph); if (++st == nsl) { st = 0; ph ^= 1; } };
        auto w_load = [&](int c0, int c1) {
#pragma unroll 1
          for (int c = c0; c < c1; c++) {
            mbar_expect_tx(sb + B_WF + 8 * c, WCH_B);
            bulk_g2s(sb + ((posw >> c * 4) & 15) * 32768, pofs<const uint8_t>(fin ? g_Wvo : g_Wmo, c * WCH_B), WCH_B, sb + B_WF + 8 * c);
          }
        };
        auto q_load = [&](const uint4* src, bool wait_empty) {
#pragma unroll 1
          for (int h = 0; h < 2; h++) {
            if (wait_empty) mbar_wait(sb + B_QEMPTY + 8 * h, qph);
            mbar_expect_tx(sb + B_QFULL + 8 * h, 32768);
            (HINT & 2 ? bulk_g2s_last : bulk_g2s)(sb + SM_Q + h * 32768, src + h * 2048, 32768, sb + B_QFULL + 8 * h);
          }
          if (wait_empty) qph ^= 1;
        };
        auto part_out = [&](int slot, int h, uint32_t region, int parity) {
          mbar_wait(sb + B_EVP0 + 8 * h, parity);
          fence_async_smem();
          bulk_s2g(g_part + slot * 4096 + h * 2048, sb + region * 32768, 32768);
          bulk_s2g(g_ml + slot * 128 + h * 64, sb + SM_ML + h * 512, 512);
          bulk_commit();
        };
        auto announce = [&](int f) {
          if (RELF) { fence_async_gmem(); flag_release(f); }
          else asm volatile("red.relaxed.gpu.global.add.u32 [%0], 1;" :: "l"(g_flag + f) : "memory");
        };
        if (total > 0) {
          STAMP(true, 2, 3);
          flag_wait(F_H, ep1 * NHSIG); fence_async_gmem();
          STAMP(true, 2, 4);
          uint32_t ko = W.k0 * 8192;
#pragma unroll 1
          for (int j = 0; j < total; j++) {
            if (j == n0) {
              flag_wait(F_QP + W.q1 * LN_, ep1); fence_async_gmem();
              const uint32_t u = __ldcg(g_unsafe + W.q1);
              asm volatile("st.shared.u32 [%0], %1;" :: "r"(sb + SM_UNSAFE), "r"(u) : "memory");
              ko = W.k1 * 8192;
            }
            if (j == n0 + 1) q_load(g_qp + W.q1 * 4096, true);
            if (j == total - 1) { flag_wait(F_W, ep1); fence_async_gmem(); if (!tail) w_load(0, 1); }
            const uint32_t bytes = (j < n0 ? j < W.nb0 : j - n0 < W.nb1) ? 112 * 512 : 128 * 512, s0 = st;
            const uint32_t region = (tail ? 1 : 2) + 2 * s0, skip = j == n0 + 1 ? 32768 : 0;
            if (skip) part_out(W.slotA, 0, 6, 0);
            next_slot();
            mbar_expect_tx(sb + B_FULL + 8 * s0, bytes);
            bulk_g2s(sb + region * 32768 + skip, pofs<const uint8_t>(g_h, ko + skip), bytes - skip, sb + B_FULL + 8 * s0);
            if (skip) {
              part_out(W.slotA, 1, region, 0);
              bulk_wait_read();
              bulk_g2s(sb + region * 32768, pofs<const uint8_t>(g_h, ko), skip, sb + B_FULL + 8 * s0);
              bulk_wait_all();
              announce(F_PART + W.slotA * LN_);
            }
            ko += bytes;
          }
          next_slot();
          if (tail) { next_slot(); next_slot(); }
        } else { flag_wait(F_W, ep1); fence_async_gmem(); }
        STAMP(true, 2, 5);
        const bool staged = total > 0 && !tail;
        w_load(staged, staged ? (fin ? 2 : 3) : 4);
#pragma unroll 1
        for (int i = 0; i < W.nloc; i++) {
          const int tl = W.loc0 + i, last = tl * 128 + 127 < NN ? tl * 128 + 127 : NN - 1;
          flag_wait(F_AGG + ((last >= NGW) + (last >= 4 * NGW) + (last >= 9 * NGW)) * LN_, ep1 * NGW); fence_async_gmem();
          if (total == 0) g_flag[F_EPOCH] = epoch + 1;
          q_load(g_agg + tl * 4096, total > 0 || i > 0);
        }
        if (tail) { mbar_wait(sb + B_BG, 0); mbar_wait(sb + B_EVP0 + 8, 0); mbar_arrive(sb + B_QFULL); }
        else if (fin) {
          int h = 0, c = 2, have = W.slotB >= 0 ? 2 : 0;
          mbar_wait(sb + B_BG, 0);
#pragma unroll 1
          for (uint32_t it = 0; (h < 2 || c < 4) && it < (1u << 23); it++) {
            if (have < 2) {
              uint2 f;
              asm volatile("ld.relaxed.gpu.global.v2.u32 {%0,%1}, [%2];" : "=r"(f.x), "=r"(f.y) : "l"(g_flag + F_PART + W.slotA * LN_) : "memory");
              have = (int)(f.x - (epoch + 1)) < 0 ? 0 : ((int)(f.y - (epoch + 1)) < 0 ? 1 : 2);
            }
            if (h < have && mbar_try_wait_nb(sb + B_QEMPTY + 8 * h, 0)) {
              asm volatile("fence.acquire.gpu;" ::: "memory"); fence_async_gmem();
              STAMP(true, 2, 14 + h);
              mbar_expect_tx(sb + B_QFULL + 8 * h, 32768 + 512);
              bulk_g2s(sb + SM_ML + h * 512, g_ml + W.slotA * 128 + h * 64, 512, sb + B_QFULL + 8 * h);
              bulk_g2s(sb + SM_Q + h * 32768, g_part + W.slotA * 4096 + h * 2048, 32768, sb + B_QFULL + 8 * h);
              h++;
            }
            const bool half = mbar_try_wait_nb(sb + B_HALF, 0);
            const int c1 = half ? 4 : (h > 0 ? 3 : 2);
            if (c < c1) { w_load(c, c1); c = c1; }
          }
        } else if (total > 0) {
#pragma unroll 1
          for (int h = 0; h < 2; h++) part_out(W.slotB, h, (posw >> 12) + h, 1);
          asm volatile("cp.async.bulk.wait_group.read 1;" ::: "memory");
          w_load(3, 4);
          asm volatile("cp.async.bulk.wait_group 1;" ::: "memory");
          announce(F_PART + W.slotB * LN_);
          STAMP(true, 2, 14);
          bulk_wait_all();
          announce(F_PART + W.slotB * LN_ + 1);
          STAMP(true, 2, 15);
        }
        DUMP(true, 2, 14, 16);
        DUMP(true, 2, 0, 8);
      }
      return;
    }
  }
    {
      const int gw = cta * 3 + warp - 1;
      ROLE;
      if (total > 0) {
        mbar_wait_w(sb + B_EVQ, 0);
        const uint32_t c0 = clk();
        if (warp == 1 && (W.role & R_PUB)) {
          g_unsafe[W.q0] = lds32(sb + SM_UNSAFE);
#pragma unroll 1
          for (int k = 0; k < 4; k++) {
            __nanosleep(2000);
            if (lane == 0) bulk_s2g(pofs<uint4>(g_qp, W.q0 * 65536 + k * 16384), sb + SM_Q + k * 16384, 16384);
            bulk_commit();
          }
          bulk_wait_all();
          flag_release_w(F_QP + W.q0 * LN_);
        }
        while (__any_sync(0xffffffffu, clk() - c0 < GSTART)) __nanosleep(500);
        STAMP(lane == 0 && warp == 1, 2, 8);
#define ovf_cnt pofs<uint32_t>(g_flag, (F_OVF + (ep1 & 1) * LN_) * 4)
        if (gw == 0) g_flag[F_OVF + ((ep1 + 1) & 1) * LN_] = 0;
#pragma unroll 1
        for (int e0 = gw * 32; e0 < NE; e0 += NGW * 32 * 7) {
          int d[7], s[7], pos[7];
          const int* pd = pofs<const int>(P.dst, (e0 + lane) * 4);
          const int* ps = pofs<const int>(P.src, (e0 + lane) * 4);
#pragma unroll
          for (int k = 0; k < 7; k++) { const bool ok = e0 + k * NGW * 32 < NE; d[k] = ok ? (HINT & 1 ? __ldcs(pd + k * NGW * 32) : __ldg(pd + k * NGW * 32)) : -1; s[k] = ok ? (HINT & 1 ? __ldcs(ps + k * NGW * 32) : __ldg(ps + k * NGW * 32)) : 0; }
          uint32_t ov = 0;
#pragma unroll
          for (int k = 0; k < 7; k++) {
            pos[k] = 0;
            if (d[k] >= 0) asm volatile("atom.relaxed.gpu.global.add.u32 %0, [%1], 1;" : "=r"(pos[k]) : "l"(pofs<int>(g_cnt, d[k] << 2)) : "memory");
            s[k] = (uint32_t)(uintptr_t)g_u + s[k] * 512;
            if (d[k] >= 0 && pos[k] < CAP) asm volatile("st.volatile.global.u32 [%0], %1;" :: "l"(pofs<int>(g_bin, (d[k] * CAPS + pos[k]) << 2)), "r"(s[k]) : "memory");
            ov |= (pos[k] >= CAP) << k;
          }
          if (__any_sync(0xffffffffu, ov != 0)) {
            uint32_t at;
            asm volatile("atom.relaxed.gpu.global.add.u32 %0, [%1], %2;" : "=r"(at) : "l"(ovf_cnt), "r"(__popc(ov)) : "memory");
#pragma unroll
            for (int k = 0; k < 7; k++) if ((ov >> k) & 1) g_ovf[at++] = make_int2(d[k], s[k]);
          }
        }
        flag_wait_w(F_H, ep1 * NHSIG);
#pragma unroll 1
        for (int n0 = gw; n0 < NN; n0 += 4 * NGW) {
          uint4 xv[4]; float2 st[4];
#pragma unroll
          for (int k = 0; k < 4; k++) {
            const int n = n0 + k * NGW < NN ? n0 + k * NGW : n0;
            xv[k] = (HINT & 1 ? ldcs_v : ldcg_v)(pofs<const uint4>(P.x, n * 512 + lane * 16));
            st[k] = __ldcg(pofs<const float2>(g_stat, n * 8));
          }
#pragma unroll
          for (int k = 3; k >= 0; k--) {
            const int n = n0 + k * NGW;
            const float a = st[k].x * US, c = fmaf(st[k].y, US, UB + 8388608.0f);
#define FIX(w) __byte_perm(__float_as_uint(fmaf(bf_lo(w), a, c)), __float_as_uint(fmaf(bf_hi(w), a, c)), 0x5410)
            if (n < NN) {
              *pofs<uint4>(P.out, n * 512 + lane * 16) = xv[k];
              *pofs<uint4>(g_u, n * 512 + lane * 16) = make_uint4(FIX(xv[k].x), FIX(xv[k].y), FIX(xv[k].z), FIX(xv[k].w));
            }
          }
        }
        flag_release_w(F_BIN);
        STAMP(lane == 0 && warp == 1, 2, 9);
        flag_wait_w(F_BIN, ep1 * NGW);
        STAMP(lane == 0 && warp == 1, 2, 10);
        const int myn = gw + lane * NGW < NN ? gw + lane * NGW : gw;
        int cnts = __ldcg(g_cnt + myn);
        cnts = gw + lane * NGW < NN ? (cnts > CAP ? CAP + 1 : cnts) | ((int)__ldg((const unsigned short*)P.dinv + myn) << 16) : 0;
        __syncwarp();
        g_cnt[myn] = 0;
        const uint32_t uhi = (uintptr_t)g_u >> 32, lx = lane * 16;
        uint32_t obin = gw * CAPS * 4;
        uint32_t ent = __ldcg(pofs<const uint32_t>(g_bin, obin + lane * 4)), entn = __ldcg(pofs<const uint32_t>(g_bin, obin + NGW * CAPS * 4 + lane * 4));
        int cd = __shfl_sync(0xffffffffu, cnts, 0), cb = min(cd & 0xffff, CAP), e = 0;
        uint32_t sa[4] = {0, 0, 0, 0}, sh[4] = {0, 0, 0, 0};
        auto add = [&](uint32_t x, uint32_t y, uint32_t z, uint32_t w) {
          sa[0] += x; sa[1] += y; sa[2] += z; sa[3] += w;
          sh[0] += x >> 16; sh[1] += y >> 16; sh[2] += z >> 16; sh[3] += w >> 16;
        };
        int rnd = -1, rows = -1, cdo = 0;
#pragma unroll 1
        for (;;) {
          const bool hold = rows >= 0 && rnd == 8;
          const int m = hold ? 0 : cb - e;
          uint4 v[8];
          if (m >= 8) {
#pragma unroll
            for (int k = 0; k < 8; k++) v[k] = ldcg_v(addr64(__shfl_sync(0xffffffffu, ent, k) + lx, uhi));
          } else {
#pragma unroll
            for (int k = 0; k < 8; k++) {
              v[k] = make_uint4(0, 0, 0, 0);
              if (k < 7) ldcg_if(v[k], addr64(__shfl_sync(0xffffffffu, ent, k) + lx, uhi), k < m);
            }
          }
          if (rows >= 0) {
            const int n = gw + rnd * NGW;
            if (n < NN) {
              const float di = __uint_as_float(cdo & 0xffff0000u) * (1.0f / US), nl = -di * UB * (float)rows;
#define AGG(k) pack_bf16(fmaf((float)(sa[k] - (sh[k] << 16)), di, nl), fmaf((float)sh[k], di, nl))
              *pofs<uint4>(g_agg, ((n >> 3) * 4096 + (n & 7) * 144) ^ ((lx & 0x70) | ((lx & 0x180) << 3))) = make_uint4(AGG(0), AGG(1), AGG(2), AGG(3));
            }
#pragma unroll
            for (int k = 0; k < 4; k++) sa[k] = sh[k] = 0;
            rows = -1;
            if (rnd == 0 || rnd == 3 || rnd == 8 || rnd == NRND - 1) flag_release_w(F_AGG + ((rnd > 0) + (rnd > 3) + (rnd > 8)) * LN_);
            if (rnd == NRND - 1) break;
            if (hold) {
              if (fin && W.slotB >= 0) {
        #pragma unroll 1
                for (int k = 0; k < 2; k++) flag_wait_w(F_PART + (k ? W.slotB : W.slotA) * LN_, ep1);
        #pragma unroll 1
                for (int b = warp - 1; b < 8; b += 3) {
                  float2* ma = g_ml + W.slotA * 128 + b * 16 + g;
                  const float2* mb = g_ml + W.slotB * 128 + b * 16 + g;
                  const float2 a0 = __ldcg(ma), a1 = __ldcg(ma + 8), b0 = __ldcg(mb), b1 = __ldcg(mb + 8);
                  const float x0 = fmaxf(a0.x, b0.x), x1 = fmaxf(a1.x, b1.x);
                  const float fa0 = ex2(a0.x - x0), fa1 = ex2(a1.x - x1), fb0 = ex2(b0.x - x0), fb1 = ex2(b1.x - x1);
                  __syncwarp();
                  if (t == 0) { ma[0] = make_float2(x0, a0.y * fa0 + b0.y * fb0); ma[8] = make_float2(x1, a1.y * fa1 + b1.y * fb1); }
                  const uint32_t ofs = ((b >> 2) * 2048 + (b & 3) * 32 + lane) * 16;
        #pragma unroll 1
                  for (int u = 0; u < 16; u += 4) {
                    uint4* pa = pofs<uint4>(g_part, W.slotA * 65536 + ofs + u * 2048);
                    const uint4* pb = pofs<const uint4>(g_part, W.slotB * 65536 + ofs + u * 2048);
                    uint4 va[4], vb[4];
        #pragma unroll
                    for (int k = 0; k < 4; k++) { va[k] = ldcg_v(pa + k * 128); vb[k] = (HINT & 2 ? ldcs_v : ldcg_v)(pb + k * 128); }
        #define FOLD(w, fa, fb) pack_bf16(bf_lo(va[k].w) * fa + bf_lo(vb[k].w) * fb, bf_hi(va[k].w) * fa + bf_hi(vb[k].w) * fb)
        #pragma unroll
                    for (int k = 3; k >= 0; k--) pa[k * 128] = make_uint4(FOLD(x, fa0, fb0), FOLD(y, fa1, fb1), FOLD(z, fa0, fb0), FOLD(w, fa1, fb1));
                  }
                }
                bar_sync(3, 96);
                if (warp == 1) asm volatile("fence.acq_rel.gpu;" ::: "memory");
              }
              if (fin && warp == 1 && lane == 0) mbar_arrive(sb + B_BG);
              while (__any_sync(0xffffffffu, clk() - c0 < GPAUSE)) __nanosleep(500);
              continue;
            }
          }
#define SUM8(f) (v[7].f + v[6].f + v[5].f + v[4].f + v[3].f + v[2].f + v[1].f + v[0].f)
          add(SUM8(x), SUM8(y), SUM8(z), SUM8(w));
          e += 8;
          if (e < cb) {
            ent = __shfl_down_sync(0xffffffffu, ent, 8);
            if (e == 32) ent = __ldcg(pofs<const uint32_t>(g_bin, obin + 128 + lx / 4));
            continue;
          }
          rnd++; rows = cb; cdo = cd;
          if ((cd & 0xffff) > CAP) {
            const int no = __shfl_sync(0xffffffffu, (int)ld_relaxed(ovf_cnt), 0);
#pragma unroll 1
            for (int i0 = 0; i0 < no; i0 += 32) {
              int2 en = __ldcg(g_ovf + min(i0 + lane, no - 1));
              uint32_t mk = __ballot_sync(0xffffffffu, en.x == gw + rnd * NGW && i0 + lane < no);
              rows += __popc(mk);
#pragma unroll 1
              while (mk) {
                const int bit = __ffs(mk) - 1; mk &= mk - 1;
                const uint4 r = ldcg_v(addr64((uint32_t)__shfl_sync(0xffffffffu, en.y, bit) + lx, uhi));
                add(r.x, r.y, r.z, r.w);
              }
            }
          }
          obin += NGW * CAPS * 4;
          ent = entn; entn = __ldcg(pofs<const uint32_t>(g_bin, obin + NGW * CAPS * 4 + lx / 4));
          cd = __shfl_sync(0xffffffffu, cnts, rnd + 1); cb = min(cd & 0xffff, CAP); e = 0;
        }
      }
      STAMP(lane == 0 && warp == 1, 2, 11);
      if ((HINT & 4) && warp == 2 && fin && lane == 0) {
        prefetch_l2(pofs<uint8_t>(P.out, W.q0 * 65536), tail ? 8192 : 65536);
        if (W.slotB >= 0) prefetch_l2(pofs<uint8_t>(g_part, W.slotA * 65536), 65536);
        prefetch_l2(pofs<uint8_t>(g_Wvo, (cta & 63) * 4096), 4096);
      }
      DUMP(warp == 1 && lane == 0, 2, 8, 14);
    }
}

}

extern "C" void kernel_launch(void* const* d_in, const int* in_sizes, int n_in, void* d_out, int out_size) {
  Params P;
  P.x = (const __nv_bfloat16*)d_in[0];
  P.src = (const int*)d_in[1];
  P.dst = (const int*)d_in[2];
  P.dinv = (const __nv_bfloat16*)d_in[3];
  P.wmsg = (const __nv_bfloat16*)d_in[4];
  P.wq = (const __nv_bfloat16*)d_in[5];
  P.wk = (const __nv_bfloat16*)d_in[6];
  P.wv = (const __nv_bfloat16*)d_in[7];
  P.wout = (const __nv_bfloat16*)d_in[8];
  P.out = (__nv_bfloat16*)d_out;
  P.zero = 0;
  for (int c = 0; c < NCTA; c++) P.w[c] = make_work(c);
  static void* scr = nullptr;
  if (!scr) {
    cudaFuncSetAttribute(gps_kernel, cudaFuncAttributeMaxDynamicSharedMemorySize, SMEM_BYTES);
    cudaGetSymbolAddress(&scr, g_scr);
  }
  P.s = (Scratch*)((((uintptr_t)scr + SCR_ALIGN - 1) & ~(uintptr_t)(SCR_ALIGN - 1)) + SCR_OFS);
  P.u = (uint4*)(((uintptr_t)P.s->u + 511) & ~(uintptr_t)511);
  if (((uintptr_t)P.u >> 32) != (((uintptr_t)(P.u + NN * 32) - 1) >> 32)) P.u += NN * 32;
  gps_kernel<<<NCTA, 384, SMEM_BYTES>>>(P);
}
```

```cpp
#include <cuda_runtime.h>
#include <cuda_bf16.h>
#include <stdint.h>
#include <stddef.h>
#include <type_traits>
#define FB 5
#define MB 5
#define GSTART 18000
#define HINT 7
#define RELF 0
#define DBG 0
#define OUTW red_bf16x8
#define EPF 1
#define XD 2
#define PACE 64
#define GPAUSE 120000
#define XDELAY 200
#define CREG 224
#define BACKOFF 1000

namespace {

constexpr int NN = 10000;
constexpr int NE = 160000;
constexpr int NQT = 79;
constexpr int NCTA = 132;
constexpr int CAP = 64;
constexpr int CAPS = 64;
constexpr int NHSIG = 105;
constexpr uint32_t WCH_B = 32768;
constexpr int NGW = (NCTA - 1) * 3;
constexpr float TAU = 16.0f;
constexpr float SAFE_N2 = 36.0f, SAFE_C = 0.6f;
#define KOFF 3
#define PSH -8.0f
#define KROT 15
constexpr float US = 256.0f, UB = 4095.0f;
constexpr float KS = 0.25f, KC = KOFF * KS;
constexpr uint32_t KS2 = 0x3e803e80u, KC2 = KOFF == 2 ? 0x3f003f00u : (KOFF == 1 ? 0x3e803e80u : 0x3f403f40u);

constexpr int NAGG = 4;
constexpr int NRND = (NN + NGW - 1) / NGW;
constexpr int NSLOT = 105;
constexpr int F_EPOCH = 0, F_H = 1, F_M = 4  , LN_ = 32;
constexpr int F_BIN = LN_, F_W = 2 * LN_, F_OVF = 3 * LN_  , F_QP = 5 * LN_, F_AGG = F_QP + NQT * LN_,
              F_PART = F_AGG + NAGG * LN_, F_END = F_PART + NSLOT * LN_;

struct Scratch {
  uint32_t flag[F_END];
  alignas(4096) uint4 M[8192];
  uint4 Wvo[8192], Wmo[8192];
  float2 ml[NSLOT * 128];
  uint32_t unsafe[96];
  int cnt[NN + 32];
  float2 stat[NQT * 128];
  alignas(4096) uint4 h[NQT * 4096];
  uint4 u[2 * NN * 32 + 32];
  uint4 qp[NQT * 4096];
  uint4 agg[NQT * 4096];
  uint4 part[NSLOT * 4096];
  int bin[(NRND + 2) * NGW * CAPS];
  int2 ovf[NE];
};
static_assert(offsetof(Scratch, h) % 128 == 0, "alignment");
#define SCR_ALIGN (2u << 20)
#define SCR_OFS 0
__device__ uint4 g_scr[(sizeof(Scratch) + SCR_ALIGN + SCR_OFS) / 16];
struct alignas(16) Work { short k0, k1; signed char q0, q1, nb0, na0, nb1, na1, slotA, slotB, loc0, nloc, own, role; };
constexpr int R_FIN = 1, R_PUB = 2, R_TAIL = 4;
struct Params {
  const __nv_bfloat16 *x, *wq, *wk;
  Scratch* s;
  uint4* u;
  __nv_bfloat16* out;
  const __nv_bfloat16 *wout, *wmsg, *wv, *dinv;
  const int *src, *dst;
  long long zero;
  Work w[NCTA];
};
constexpr int NSERV = NQT - 52;
inline Work make_work(int c) {
  Work w;
  const int gi = c / 5, r = c % 5, q = gi * 3;
  const bool helper = r & 1, mid = r == 2;
  w.q0 = helper ? q + 1 : q + (r >> 1);
  const int hb1 = (15 - MB) / 2, hb3 = 15 - MB - hb1;
  w.nb0 = helper ? (r == 1 ? hb1 : hb3) : (mid ? MB : FB);
  w.na0 = (helper ? 16 : 48) - w.nb0;
  w.k0 = helper ? (48 * 8 - MB) + (r >> 1) * (16 * 8 - hb1) : 0;
  w.q1 = q + (r & 2);
  w.k1 = 48 * 8 - FB;
  w.nb1 = helper ? (FB < 7 ? 7 : 15) - FB : 0;
  w.na1 = helper ? (FB < 7 ? 31 : 32) - w.nb1 : 0;
  w.slotA = 4 * gi + (helper ? r - 1 : (mid ? 0 : (r >> 1) + 1));
  w.slotB = helper ? 4 * gi + r : (mid ? 4 * gi + 2 : -1);
  w.loc0 = NSERV + gi * 2 + (r >> 1);
  w.nloc = helper;
  w.own = helper ? (r + 1) >> 1 : (mid ? 0 : 3);
  w.role = helper ? 0 : (mid ? R_FIN : R_FIN | R_PUB);
  if (c == 130) { w.nb0 = 15; w.na0 = 65; w.slotA = NSLOT - 1; w.own = 1; w.role = R_FIN | R_TAIL; }
  if (c == 131) { w.nb0 = w.na0 = w.nb1 = w.na1 = 0; w.loc0 = 0; w.nloc = NSERV; w.own = 0; }
  return w;
}
#define g_flag P.s->flag
#define g_M P.s->M
#define g_Wvo P.s->Wvo
#define g_Wmo P.s->Wmo
#define g_ml P.s->ml
#define g_unsafe P.s->unsafe
#define g_cnt P.s->cnt
#define g_h P.s->h
#define g_u P.u
#define g_stat P.s->stat
#define g_qp P.s->qp
#define g_agg P.s->agg
#define g_part P.s->part
#define g_bin P.s->bin
#define g_ovf P.s->ovf

__device__ __forceinline__ uint32_t smem_u32(const void* p) { return (uint32_t)__cvta_generic_to_shared(p); }
__device__ __forceinline__ void mbar_init(uint32_t bar, uint32_t cnt) { asm volatile("mbarrier.init.shared::cta.b64 [%0], %1;" :: "r"(bar), "r"(cnt) : "memory"); }
__device__ __forceinline__ void mbar_arrive(uint32_t bar) { asm volatile("mbarrier.arrive.shared::cta.b64 _, [%0];" :: "r"(bar) : "memory"); }
__device__ __forceinline__ void mbar_expect_tx(uint32_t bar, uint32_t bytes) { asm volatile("mbarrier.arrive.expect_tx.shared::cta.b64 _, [%0], %1;" :: "r"(bar), "r"(bytes) : "memory"); }
__device__ __forceinline__ bool mbar_try_wait(uint32_t bar, uint32_t parity) {
  uint32_t ok;
  asm volatile("{\n.reg .pred p;\nmbarrier.try_wait.parity.shared::cta.b64 p, [%1], %2;\nselp.b32 %0, 1, 0, p;\n}\n" : "=r"(ok) : "r"(bar), "r"(parity) : "memory");
  return ok;
}
__device__ __forceinline__ bool mbar_try_wait_nb(uint32_t bar, uint32_t parity) {
  uint32_t ok;
  asm volatile("{\n.reg .pred p;\nmbarrier.test_wait.parity.shared::cta.b64 p, [%1], %2;\nselp.b32 %0, 1, 0, p;\n}\n" : "=r"(ok) : "r"(bar), "r"(parity) : "memory");
  return ok;
}
__device__ __forceinline__ void mbar_wait(uint32_t bar, uint32_t parity) {
#pragma unroll 1
  for (uint32_t it = 0; it < (1u << 25); it++) if (mbar_try_wait(bar, parity)) break;
}
__device__ __forceinline__ void bulk_s2g(void* dst, uint32_t src, uint32_t bytes) {
  asm volatile("cp.async.bulk.global.shared::cta.bulk_group [%0], [%1], %2;" :: "l"(dst), "r"(src), "r"(bytes) : "memory");
}
__device__ __forceinline__ void bulk_commit() { asm volatile("cp.async.bulk.commit_group;" ::: "memory"); }
__device__ __forceinline__ void bulk_wait_read() { asm volatile("cp.async.bulk.wait_group.read 0;" ::: "memory"); }
__device__ __forceinline__ void bulk_wait_all() { asm volatile("cp.async.bulk.wait_group 0;" ::: "memory"); }
__device__ __forceinline__ bool bar_red_or(int id, int cnt, bool c) {
  uint32_t r;
  asm volatile("{\n.reg .pred p, q;\nsetp.ne.b32 q, %3, 0;\nbar.red.or.pred p, %1, %2, q;\nselp.b32 %0, 1, 0, p;\n}\n"
               : "=r"(r) : "r"(id), "r"(cnt), "r"((uint32_t)c) : "memory");
  return r != 0;
}
template <class T> __device__ __forceinline__ T* pofs(const void* base, uint32_t off) {
  asm volatile("" : "+r"(off));
  return (T*)((uint8_t*)base + off);
}
__device__ __forceinline__ const void* addr64(uint32_t lo, uint32_t hi) { uint64_t a; asm("mov.b64 %0, {%1, %2};" : "=l"(a) : "r"(lo), "r"(hi)); return (const void*)a; }
__device__ __forceinline__ uint4 ldcg_v(const void* a) {
  uint4 v;
  asm volatile("ld.volatile.global.v4.u32 {%0,%1,%2,%3}, [%4];" : "=r"(v.x), "=r"(v.y), "=r"(v.z), "=r"(v.w) : "l"(a) : "memory");
  return v;
}
__device__ __forceinline__ uint4 ldcs_v(const void* a) {
  uint4 v;
  asm volatile("ld.global.cs.v4.u32 {%0,%1,%2,%3}, [%4];" : "=r"(v.x), "=r"(v.y), "=r"(v.z), "=r"(v.w) : "l"(a) : "memory");
  return v;
}
__device__ __forceinline__ void prefetch_l2(const void* a, uint32_t bytes) { asm volatile("cp.async.bulk.prefetch.L2.global [%0], %1;" :: "l"(a), "r"(bytes) : "memory"); }
__device__ __forceinline__ void ldcg_if(uint4& v, const void* a, bool c) {
  asm volatile("{\n.reg .pred p;\nsetp.ne.b32 p, %5, 0;\n@p ld.volatile.global.v4.u32 {%0,%1,%2,%3}, [%4];\n}\n"
               : "+r"(v.x), "+r"(v.y), "+r"(v.z), "+r"(v.w) : "l"(a), "r"((uint32_t)c) : "memory");
}
__device__ __forceinline__ void cp_async16(uint32_t dst, const void* src) {
  asm volatile("cp.async.cg.shared.global [%0], [%1], 16;" :: "r"(dst), "l"(src) : "memory");
}
__device__ __forceinline__ void red_bf16x8(void* a, uint4 v) {
  asm volatile("red.global.add.noftz.v4.bf16x2 [%0], {%1,%2,%3,%4};" :: "l"(a), "r"(v.x), "r"(v.y), "r"(v.z), "r"(v.w) : "memory");
}
__device__ __forceinline__ uint32_t clk() { uint32_t c; asm volatile("mov.u32 %0, %%clock;" : "=r"(c) :: "memory"); return c; }
__device__ __forceinline__ void stsm4(uint32_t a, uint32_t r0, uint32_t r1, uint32_t r2, uint32_t r3) {
  asm volatile("stmatrix.sync.aligned.m8n8.x4.shared.b16 [%0], {%1,%2,%3,%4};" :: "r"(a), "r"(r0), "r"(r1), "r"(r2), "r"(r3) : "memory");
}
__device__ __forceinline__ uint32_t lds32(uint32_t a) { uint32_t v; asm volatile("ld.shared.u32 %0, [%1];" : "=r"(v) : "r"(a) : "memory"); return v; }
__device__ __forceinline__ void cp_commit() { asm volatile("cp.async.commit_group;" ::: "memory"); }
__device__ __forceinline__ uint32_t hmul2(uint32_t a, uint32_t b) { uint32_t d; asm("mul.rn.bf16x2 %0, %1, %2;" : "=r"(d) : "r"(a), "r"(b)); return d; }
__device__ __forceinline__ uint32_t hfma2(uint32_t a, uint32_t b, uint32_t c) { uint32_t d; asm("fma.rn.bf16x2 %0, %1, %2, %3;" : "=r"(d) : "r"(a), "r"(b), "r"(c)); return d; }
__device__ __forceinline__ uint32_t pow2_bf2(int n) { return (uint32_t)max(n + 127, 0) * 0x00800080u; }
__device__ __forceinline__ int fexp(float x) { return (int)(__float_as_uint(x) >> 23) - 127; }
__device__ __forceinline__ void bulk_g2s(uint32_t dst, const void* src, uint32_t bytes, uint32_t bar) {
  asm volatile("cp.async.bulk.shared::cta.global.mbarrier::complete_tx::bytes [%0], [%1], %2, [%3];"
    :: "r"(dst), "l"(src), "r"(bytes), "r"(bar) : "memory");
}
__device__ __forceinline__ void bulk_g2s_last(uint32_t dst, const void* src, uint32_t bytes, uint32_t bar) {
  asm volatile("{\n.reg .b64 p;\ncreatepolicy.fractional.L2::evict_first.b64 p;\n"
    "cp.async.bulk.shared::cta.global.mbarrier::complete_tx::bytes.L2::cache_hint [%0], [%1], %2, [%3], p;\n}\n"
    :: "r"(dst), "l"(src), "r"(bytes), "r"(bar) : "memory");
}
__device__ __forceinline__ void wg_fence() { asm volatile("wgmma.fence.sync.aligned;" ::: "memory"); }
__device__ __forceinline__ void wg_commit() { asm volatile("wgmma.commit_group.sync.aligned;" ::: "memory"); }
template<int N> __device__ __forceinline__ void wg_wait() { asm volatile("wgmma.wait_group.sync.aligned %0;" :: "n"(N) : "memory"); }
__device__ __forceinline__ void bar_sync(int id, int cnt) { asm volatile("bar.sync %0, %1;" :: "r"(id), "r"(cnt) : "memory"); }
__device__ __forceinline__ void fence_async_smem() { asm volatile("fence.proxy.async.shared::cta;" ::: "memory"); }
__device__ __forceinline__ void fence_async_gmem() { asm volatile("fence.proxy.async.global;" ::: "memory"); }
__device__ __forceinline__ void bar_arrive(int id, int cnt) { asm volatile("bar.arrive %0, %1;" :: "r"(id), "r"(cnt) : "memory"); }
__device__ __forceinline__ void red_release(uint32_t* p) { asm volatile("red.release.gpu.global.add.u32 [%0], 1;" :: "l"(p) : "memory"); }
__device__ __forceinline__ void red_release_w(uint32_t* p) {
  __syncwarp();
  asm volatile("{\n.reg .pred q;\n.reg .b32 l;\nmov.u32 l, %%laneid;\nsetp.eq.u32 q, l, 0;\n@q fence.release.gpu;\n@q red.relaxed.gpu.global.add.u32 [%0], 1;\n}\n" :: "l"(p) : "memory");
}
__device__ __forceinline__ void mbar_wait_w(uint32_t bar, uint32_t parity) {
#pragma unroll 1
  for (uint32_t it = 0; it < (1u << 25); it++) if (__all_sync(0xffffffffu, mbar_try_wait(bar, parity))) break;
}
#define flag_release_w(f) red_release_w(g_flag + (f))
#define flag_wait_w(f, target) poll_acquire_w(g_flag + (f), target)
#define flag_release(f) red_release(g_flag + (f))
__device__ __forceinline__ uint32_t ld_relaxed(const uint32_t* p) {
  uint32_t v; asm volatile("ld.relaxed.gpu.global.u32 %0, [%1];" : "=r"(v) : "l"(p) : "memory"); return v;
}
#define flag_wait(f, target) poll_acquire(g_flag + (f), target)
__device__ __forceinline__ void poll_acquire(const uint32_t* p, uint32_t target) {
#pragma unroll 1
  for (uint32_t it = 0; it < (1u << 23); it++) if ((int)(ld_relaxed(p) - target) >= 0) break;
  asm volatile("fence.acquire.gpu;" ::: "memory");
}
__device__ __forceinline__ void poll_acquire_w(const uint32_t* p, uint32_t target) {
#pragma unroll 1
  for (uint32_t it = 0; it < (1u << 23); it++) {
    if (__all_sync(0xffffffffu, (int)(ld_relaxed(p) - target) >= 0)) break;
    if (BACKOFF) __nanosleep(BACKOFF);
  }
  asm volatile("fence.acquire.gpu;" ::: "memory");
}
template<int N> __device__ __forceinline__ void reg_fence(float (&d)[N]) {
#pragma unroll
  for (int i = 0; i < N; i++) asm volatile("" : "+f"(d[i]) :: "memory");
}
template<int N> __device__ __forceinline__ void reg_fence(uint32_t (&d)[N]) {
#pragma unroll
  for (int i = 0; i < N; i++) asm volatile("" : "+r"(d[i]) :: "memory");
}
__device__ __forceinline__ float ex2(float x) { float y; asm("ex2.approx.ftz.f32 %0, %1;" : "=f"(y) : "f"(x)); return y; }
__device__ __forceinline__ uint32_t pack_bf16(float lo, float hi) { uint32_t r; asm("cvt.rn.bf16x2.f32 %0, %1, %2;" : "=r"(r) : "f"(hi), "f"(lo)); return r; }
__device__ __forceinline__ float bf_lo(uint32_t w) { return __uint_as_float(w << 16); }
__device__ __forceinline__ float bf_hi(uint32_t w) { return __uint_as_float(w & 0xffff0000u); }
__device__ __forceinline__ uint64_t desc_k(uint32_t addr, uint32_t add) { return (uint64_t)((((addr & 0x3FFFF) >> 4) | (1u << 16)) + add) | (0x40000100ull << 32); }
__device__ __forceinline__ uint64_t desc_mn(uint32_t addr, uint32_t add) { return (uint64_t)((((addr & 0x3FFFF) >> 4) | ((1024u >> 4) << 16)) + add) | (0x40000100ull << 32); }
__device__ __forceinline__ void sts128(uint32_t a, uint4 v) { asm volatile("st.shared.v4.u32 [%0], {%1,%2,%3,%4};" :: "r"(a), "r"(v.x), "r"(v.y), "r"(v.z), "r"(v.w) : "memory"); }
__device__ __forceinline__ uint4 lds128(uint32_t a) { uint4 v; asm volatile("ld.shared.v4.u32 {%0,%1,%2,%3}, [%4];" : "=r"(v.x), "=r"(v.y), "=r"(v.z), "=r"(v.w) : "r"(a) : "memory"); return v; }
__device__ __forceinline__ void mma16816(float (&c)[4], uint32_t a0, uint32_t a1, uint32_t a2, uint32_t a3, uint32_t b0, uint32_t b1) {
  asm volatile("mma.sync.aligned.m16n8k16.row.col.f32.bf16.bf16.f32 {%0,%1,%2,%3}, {%4,%5,%6,%7}, {%8,%9}, {%0,%1,%2,%3};"
    : "+f"(c[0]), "+f"(c[1]), "+f"(c[2]), "+f"(c[3]) : "r"(a0), "r"(a1), "r"(a2), "r"(a3), "r"(b0), "r"(b1));
}
__device__ __forceinline__ uint32_t sw_byte(int r, int c) {
  return (uint32_t)((r >> 3) * 4096 + (c >> 6) * 1024 + (r & 7) * 128 + ((((c >> 3) & 7) ^ (r & 7)) << 4) + (c & 7) * 2);
}
__device__ __forceinline__ int cta_id() { int c; asm volatile("mov.u32 %0, %%ctaid.x;" : "=r"(c)); return c; }
__device__ __forceinline__ bool tid_is(int v) { int t; asm volatile("mov.u32 %0, %%tid.x;" : "=r"(t)); return t == v; }
#define STAMP(cond, who, i)
#define CSTAMP(cond, who, i)
#define DUMP(cond, who, i0, i1)
#define XSTAMP(cond, i)
#define SSTAMP(i)

template <int OA, int OB> __device__ __forceinline__ void wgmma_ss_n256_tb(float (&d)[128], uint64_t da, uint64_t db, int scale_d) {
  asm volatile("{\n.reg .pred p;\n.reg .b64 a, b;\nsetp.ne.b32 p, %130, 0;\nadd.s64 a, %128, %131;\nadd.s64 b, %129, %132;\n"
    "wgmma.mma_async.sync.aligned.m64n256k16.f32.bf16.bf16 "
    "{%0, %1, %2, %3, %4, %5, %6, %7, %8, %9, %10, %11, %12, %13, %14, %15, %16, %17, %18, %19, %20, %21, %22, %23, %24, %25, %26, %27, %28, %29, %30, %31, %32, %33, %34, %35, %36, %37, %38, %39, %40, %41, %42, %43, %44, %45, %46, %47, %48, %49, %50, %51, %52, %53, %54, %55, %56, %57, %58, %59, %60, %61, %62, %63, %64, %65, %66, %67, %68, %69, %70, %71, %72, %73, %74, %75, %76, %77, %78, %79, %80, %81, %82, %83, %84, %85, %86, %87, %88, %89, %90, %91, %92, %93, %94, %95, %96, %97, %98, %99, %100, %101, %102, %103, %104, %105, %106, %107, %108, %109, %110, %111, %112, %113, %114, %115, %116, %117, %118, %119, %120, %121, %122, %123, %124, %125, %126, %127}, "
    "a, b, p, 1, 1, 0, 1;\n}\n"
    : "+f"(d[0]), "+f"(d[1]), "+f"(d[2]), "+f"(d[3]), "+f"(d[4]), "+f"(d[5]), "+f"(d[6]), "+f"(d[7]), "+f"(d[8]), "+f"(d[9]), "+f"(d[10]), "+f"(d[11]), "+f"(d[12]), "+f"(d[13]), "+f"(d[14]), "+f"(d[15]), "+f"(d[16]), "+f"(d[17]), "+f"(d[18]), "+f"(d[19]), "+f"(d[20]), "+f"(d[21]), "+f"(d[22]), "+f"(d[23]), "+f"(d[24]), "+f"(d[25]), "+f"(d[26]), "+f"(d[27]), "+f"(d[28]), "+f"(d[29]), "+f"(d[30]), "+f"(d[31]), "+f"(d[32]), "+f"(d[33]), "+f"(d[34]), "+f"(d[35]), "+f"(d[36]), "+f"(d[37]), "+f"(d[38]), "+f"(d[39]), "+f"(d[40]), "+f"(d[41]), "+f"(d[42]), "+f"(d[43]), "+f"(d[44]), "+f"(d[45]), "+f"(d[46]), "+f"(d[47]), "+f"(d[48]), "+f"(d[49]), "+f"(d[50]), "+f"(d[51]), "+f"(d[52]), "+f"(d[53]), "+f"(d[54]), "+f"(d[55]), "+f"(d[56]), "+f"(d[57]), "+f"(d[58]), "+f"(d[59]), "+f"(d[60]), "+f"(d[61]), "+f"(d[62]), "+f"(d[63]), "+f"(d[64]), "+f"(d[65]), "+f"(d[66]), "+f"(d[67]), "+f"(d[68]), "+f"(d[69]), "+f"(d[70]), "+f"(d[71]), "+f"(d[72]), "+f"(d[73]), "+f"(d[74]), "+f"(d[75]), "+f"(d[76]), "+f"(d[77]), "+f"(d[78]), "+f"(d[79]), "+f"(d[80]), "+f"(d[81]), "+f"(d[82]), "+f"(d[83]), "+f"(d[84]), "+f"(d[85]), "+f"(d[86]), "+f"(d[87]), "+f"(d[88]), "+f"(d[89]), "+f"(d[90]), "+f"(d[91]), "+f"(d[92]), "+f"(d[93]), "+f"(d[94]), "+f"(d[95]), "+f"(d[96]), "+f"(d[97]), "+f"(d[98]), "+f"(d[99]), "+f"(d[100]), "+f"(d[101]), "+f"(d[102]), "+f"(d[103]), "+f"(d[104]), "+f"(d[105]), "+f"(d[106]), "+f"(d[107]), "+f"(d[108]), "+f"(d[109]), "+f"(d[110]), "+f"(d[111]), "+f"(d[112]), "+f"(d[113]), "+f"(d[114]), "+f"(d[115]), "+f"(d[116]), "+f"(d[117]), "+f"(d[118]), "+f"(d[119]), "+f"(d[120]), "+f"(d[121]), "+f"(d[122]), "+f"(d[123]), "+f"(d[124]), "+f"(d[125]), "+f"(d[126]), "+f"(d[127])
    : "l"(da), "l"(db), "r"(scale_d), "n"(OA), "n"(OB));
}
template <int OA, int OB> __device__ __forceinline__ void wgmma_qk(float (&d)[64], uint64_t da, uint64_t db, int scale_d) {
  asm volatile("{\n.reg .pred p;\n.reg .b64 a, b;\nsetp.ne.b32 p, %66, 0;\nadd.s64 a, %64, %67;\nadd.s64 b, %65, %68;\n"
    "wgmma.mma_async.sync.aligned.m64n128k16.f32.bf16.bf16 "
    "{%0, %1, %2, %3, %4, %5, %6, %7, %8, %9, %10, %11, %12, %13, %14, %15, %16, %17, %18, %19, %20, %21, %22, %23, %24, %25, %26, %27, %28, %29, %30, %31, %32, %33, %34, %35, %36, %37, %38, %39, %40, %41, %42, %43, %44, %45, %46, %47, %48, %49, %50, %51, %52, %53, %54, %55, %56, %57, %58, %59, %60, %61, %62, %63}, "
    "a, b, p, 1, 1, 0, 0;\n}\n"
    : "+f"(d[0]), "+f"(d[1]), "+f"(d[2]), "+f"(d[3]), "+f"(d[4]), "+f"(d[5]), "+f"(d[6]), "+f"(d[7]), "+f"(d[8]), "+f"(d[9]), "+f"(d[10]), "+f"(d[11]), "+f"(d[12]), "+f"(d[13]), "+f"(d[14]), "+f"(d[15]), "+f"(d[16]), "+f"(d[17]), "+f"(d[18]), "+f"(d[19]), "+f"(d[20]), "+f"(d[21]), "+f"(d[22]), "+f"(d[23]), "+f"(d[24]), "+f"(d[25]), "+f"(d[26]), "+f"(d[27]), "+f"(d[28]), "+f"(d[29]), "+f"(d[30]), "+f"(d[31]), "+f"(d[32]), "+f"(d[33]), "+f"(d[34]), "+f"(d[35]), "+f"(d[36]), "+f"(d[37]), "+f"(d[38]), "+f"(d[39]), "+f"(d[40]), "+f"(d[41]), "+f"(d[42]), "+f"(d[43]), "+f"(d[44]), "+f"(d[45]), "+f"(d[46]), "+f"(d[47]), "+f"(d[48]), "+f"(d[49]), "+f"(d[50]), "+f"(d[51]), "+f"(d[52]), "+f"(d[53]), "+f"(d[54]), "+f"(d[55]), "+f"(d[56]), "+f"(d[57]), "+f"(d[58]), "+f"(d[59]), "+f"(d[60]), "+f"(d[61]), "+f"(d[62]), "+f"(d[63])
    : "l"(da), "l"(db), "r"(scale_d), "n"(OA), "n"(OB));
}
template <int OA, int OB> __device__ __forceinline__ void wgmma_qk(float (&d)[56], uint64_t da, uint64_t db, int scale_d) {
  asm volatile("{\n.reg .pred p;\n.reg .b64 a, b;\nsetp.ne.b32 p, %58, 0;\nadd.s64 a, %56, %59;\nadd.s64 b, %57, %60;\n"
    "wgmma.mma_async.sync.aligned.m64n112k16.f32.bf16.bf16 "
    "{%0, %1, %2, %3, %4, %5, %6, %7, %8, %9, %10, %11, %12, %13, %14, %15, %16, %17, %18, %19, %20, %21, %22, %23, %24, %25, %26, %27, %28, %29, %30, %31, %32, %33, %34, %35, %36, %37, %38, %39, %40, %41, %42, %43, %44, %45, %46, %47, %48, %49, %50, %51, %52, %53, %54, %55}, "
    "a, b, p, 1, 1, 0, 0;\n}\n"
    : "+f"(d[0]), "+f"(d[1]), "+f"(d[2]), "+f"(d[3]), "+f"(d[4]), "+f"(d[5]), "+f"(d[6]), "+f"(d[7]), "+f"(d[8]), "+f"(d[9]), "+f"(d[10]), "+f"(d[11]), "+f"(d[12]), "+f"(d[13]), "+f"(d[14]), "+f"(d[15]), "+f"(d[16]), "+f"(d[17]), "+f"(d[18]), "+f"(d[19]), "+f"(d[20]), "+f"(d[21]), "+f"(d[22]), "+f"(d[23]), "+f"(d[24]), "+f"(d[25]), "+f"(d[26]), "+f"(d[27]), "+f"(d[28]), "+f"(d[29]), "+f"(d[30]), "+f"(d[31]), "+f"(d[32]), "+f"(d[33]), "+f"(d[34]), "+f"(d[35]), "+f"(d[36]), "+f"(d[37]), "+f"(d[38]), "+f"(d[39]), "+f"(d[40]), "+f"(d[41]), "+f"(d[42]), "+f"(d[43]), "+f"(d[44]), "+f"(d[45]), "+f"(d[46]), "+f"(d[47]), "+f"(d[48]), "+f"(d[49]), "+f"(d[50]), "+f"(d[51]), "+f"(d[52]), "+f"(d[53]), "+f"(d[54]), "+f"(d[55])
    : "l"(da), "l"(db), "r"(scale_d), "n"(OA), "n"(OB));
}
template <int OB> __device__ __forceinline__ void wgmma_rs_n256_tb(float (&d)[128], uint32_t a0, uint32_t a1, uint32_t a2, uint32_t a3, uint64_t db, int scale_d) {
  asm volatile("{\n.reg .pred p;\n.reg .b64 b;\nsetp.ne.b32 p, %133, 0;\nadd.s64 b, %132, %134;\n"
    "wgmma.mma_async.sync.aligned.m64n256k16.f32.bf16.bf16 "
    "{%0, %1, %2, %3, %4, %5, %6, %7, %8, %9, %10, %11, %12, %13, %14, %15, %16, %17, %18, %19, %20, %21, %22, %23, %24, %25, %26, %27, %28, %29, %30, %31, %32, %33, %34, %35, %36, %37, %38, %39, %40, %41, %42, %43, %44, %45, %46, %47, %48, %49, %50, %51, %52, %53, %54, %55, %56, %57, %58, %59, %60, %61, %62, %63, %64, %65, %66, %67, %68, %69, %70, %71, %72, %73, %74, %75, %76, %77, %78, %79, %80, %81, %82, %83, %84, %85, %86, %87, %88, %89, %90, %91, %92, %93, %94, %95, %96, %97, %98, %99, %100, %101, %102, %103, %104, %105, %106, %107, %108, %109, %110, %111, %112, %113, %114, %115, %116, %117, %118, %119, %120, %121, %122, %123, %124, %125, %126, %127}, "
    "{%128, %129, %130, %131}, b, p, 1, 1, 1;\n}\n"
    : "+f"(d[0]), "+f"(d[1]), "+f"(d[2]), "+f"(d[3]), "+f"(d[4]), "+f"(d[5]), "+f"(d[6]), "+f"(d[7]), "+f"(d[8]), "+f"(d[9]), "+f"(d[10]), "+f"(d[11]), "+f"(d[12]), "+f"(d[13]), "+f"(d[14]), "+f"(d[15]), "+f"(d[16]), "+f"(d[17]), "+f"(d[18]), "+f"(d[19]), "+f"(d[20]), "+f"(d[21]), "+f"(d[22]), "+f"(d[23]), "+f"(d[24]), "+f"(d[25]), "+f"(d[26]), "+f"(d[27]), "+f"(d[28]), "+f"(d[29]), "+f"(d[30]), "+f"(d[31]), "+f"(d[32]), "+f"(d[33]), "+f"(d[34]), "+f"(d[35]), "+f"(d[36]), "+f"(d[37]), "+f"(d[38]), "+f"(d[39]), "+f"(d[40]), "+f"(d[41]), "+f"(d[42]), "+f"(d[43]), "+f"(d[44]), "+f"(d[45]), "+f"(d[46]), "+f"(d[47]), "+f"(d[48]), "+f"(d[49]), "+f"(d[50]), "+f"(d[51]), "+f"(d[52]), "+f"(d[53]), "+f"(d[54]), "+f"(d[55]), "+f"(d[56]), "+f"(d[57]), "+f"(d[58]), "+f"(d[59]), "+f"(d[60]), "+f"(d[61]), "+f"(d[62]), "+f"(d[63]), "+f"(d[64]), "+f"(d[65]), "+f"(d[66]), "+f"(d[67]), "+f"(d[68]), "+f"(d[69]), "+f"(d[70]), "+f"(d[71]), "+f"(d[72]), "+f"(d[73]), "+f"(d[74]), "+f"(d[75]), "+f"(d[76]), "+f"(d[77]), "+f"(d[78]), "+f"(d[79]), "+f"(d[80]), "+f"(d[81]), "+f"(d[82]), "+f"(d[83]), "+f"(d[84]), "+f"(d[85]), "+f"(d[86]), "+f"(d[87]), "+f"(d[88]), "+f"(d[89]), "+f"(d[90]), "+f"(d[91]), "+f"(d[92]), "+f"(d[93]), "+f"(d[94]), "+f"(d[95]), "+f"(d[96]), "+f"(d[97]), "+f"(d[98]), "+f"(d[99]), "+f"(d[100]), "+f"(d[101]), "+f"(d[102]), "+f"(d[103]), "+f"(d[104]), "+f"(d[105]), "+f"(d[106]), "+f"(d[107]), "+f"(d[108]), "+f"(d[109]), "+f"(d[110]), "+f"(d[111]), "+f"(d[112]), "+f"(d[113]), "+f"(d[114]), "+f"(d[115]), "+f"(d[116]), "+f"(d[117]), "+f"(d[118]), "+f"(d[119]), "+f"(d[120]), "+f"(d[121]), "+f"(d[122]), "+f"(d[123]), "+f"(d[124]), "+f"(d[125]), "+f"(d[126]), "+f"(d[127])
    : "r"(a0), "r"(a1), "r"(a2), "r"(a3), "l"(db), "r"(scale_d), "n"(OB));
}
template <int OB> __device__ __forceinline__ void wgmma_rs_n128_tb(float (&d)[64], uint32_t a0, uint32_t a1, uint32_t a2, uint32_t a3, uint64_t db, int scale_d) {
  asm volatile("{\n.reg .pred p;\n.reg .b64 b;\nsetp.ne.b32 p, %69, 0;\nadd.s64 b, %68, %70;\n"
    "wgmma.mma_async.sync.aligned.m64n128k16.f32.bf16.bf16 "
    "{%0, %1, %2, %3, %4, %5, %6, %7, %8, %9, %10, %11, %12, %13, %14, %15, %16, %17, %18, %19, %20, %21, %22, %23, %24, %25, %26, %27, %28, %29, %30, %31, %32, %33, %34, %35, %36, %37, %38, %39, %40, %41, %42, %43, %44, %45, %46, %47, %48, %49, %50, %51, %52, %53, %54, %55, %56, %57, %58, %59, %60, %61, %62, %63}, "
    "{%64, %65, %66, %67}, b, p, 1, 1, 1;\n}\n"
    : "+f"(d[0]), "+f"(d[1]), "+f"(d[2]), "+f"(d[3]), "+f"(d[4]), "+f"(d[5]), "+f"(d[6]), "+f"(d[7]), "+f"(d[8]), "+f"(d[9]), "+f"(d[10]), "+f"(d[11]), "+f"(d[12]), "+f"(d[13]), "+f"(d[14]), "+f"(d[15]), "+f"(d[16]), "+f"(d[17]), "+f"(d[18]), "+f"(d[19]), "+f"(d[20]), "+f"(d[21]), "+f"(d[22]), "+f"(d[23]), "+f"(d[24]), "+f"(d[25]), "+f"(d[26]), "+f"(d[27]), "+f"(d[28]), "+f"(d[29]), "+f"(d[30]), "+f"(d[31]), "+f"(d[32]), "+f"(d[33]), "+f"(d[34]), "+f"(d[35]), "+f"(d[36]), "+f"(d[37]), "+f"(d[38]), "+f"(d[39]), "+f"(d[40]), "+f"(d[41]), "+f"(d[42]), "+f"(d[43]), "+f"(d[44]), "+f"(d[45]), "+f"(d[46]), "+f"(d[47]), "+f"(d[48]), "+f"(d[49]), "+f"(d[50]), "+f"(d[51]), "+f"(d[52]), "+f"(d[53]), "+f"(d[54]), "+f"(d[55]), "+f"(d[56]), "+f"(d[57]), "+f"(d[58]), "+f"(d[59]), "+f"(d[60]), "+f"(d[61]), "+f"(d[62]), "+f"(d[63])
    : "r"(a0), "r"(a1), "r"(a2), "r"(a3), "l"(db), "r"(scale_d), "n"(OB));
}
template <int V> using IC = std::integral_constant<int, V>;
template <int I, int N, class F> __device__ __forceinline__ void static_for(F&& f) {
  if constexpr (I < N) { f(std::integral_constant<int, I>{}); static_for<I + 1, N>(f); }
}

constexpr uint32_t SM_Q = 0, SM_BAR = 7 * 32768;
constexpr uint32_t B_FULL = SM_BAR, B_EMPTY = B_FULL + 24, B_WF = B_EMPTY + 24, B_QFULL = B_WF + 32, B_QEMPTY = B_QFULL + 16,
                   B_EVH = B_QEMPTY + 16, B_EVQ = B_EVH + 8, B_EVP0 = B_EVQ + 8, B_BG = B_EVP0 + 16, B_M0 = B_BG + 8, B_HALF = B_M0 + 8,
                   SM_UNSAFE = B_HALF + 8, SM_TS = SM_UNSAFE + 8, SM_ML = (SM_TS + 192 + 15) / 16 * 16, SM_EPOCH = SM_ML + 1024, SM_END = SM_EPOCH + 16;
constexpr uint32_t POS_M = 0x5462;
constexpr int SMEM_BYTES = SM_END;

#define ROW0(u) make_uint4(pack_bf16(o[16 * u], o[16 * u + 1]), pack_bf16(o[16 * u + 4], o[16 * u + 5]), \
                           pack_bf16(o[16 * u + 8], o[16 * u + 9]), pack_bf16(o[16 * u + 12], o[16 * u + 13]))
#define ROW1(u) make_uint4(pack_bf16(o[16 * u + 2], o[16 * u + 3]), pack_bf16(o[16 * u + 6], o[16 * u + 7]), \
                           pack_bf16(o[16 * u + 10], o[16 * u + 11]), pack_bf16(o[16 * u + 14], o[16 * u + 15]))

__global__ void __launch_bounds__(384, 1) gps_kernel(const __grid_constant__ Params P) {
  extern __shared__ __align__(1024) uint8_t smem_raw[];
  constexpr uint32_t sb = 1024;
  if (smem_u32(smem_raw) != sb) return;
  const int cta = blockIdx.x;
  const int wg = __shfl_sync(0xffffffffu, (int)threadIdx.x >> 7, 0);
  const int warp = __shfl_sync(0xffffffffu, ((int)threadIdx.x >> 5) & 3, 0);
  const int lane = threadIdx.x & 31;
#define ROLE                                                                                       \
  const Work& W = P.w[cta_id()];                                                                   \
  [[maybe_unused]] const int n0 = W.nb0 + W.na0, n1 = W.nb1 + W.na1, total = n0 + n1;              \
  [[maybe_unused]] const bool fin = W.role & R_FIN, tail = W.role & R_TAIL;                        \
  [[maybe_unused]] const uint32_t posw = total == 0 || tail ? POS_M : ((total & 1) ? 0x2546 : 0x4326)
  const int g = lane >> 2, t = lane & 3;
  if (wg < 2) {
    const int tid = threadIdx.x & 127;
    ROLE;
    const uint32_t sQ = sb + SM_Q + wg * 32768;
#define st0 tid_is(wg * 128)
    STAMP(st0, wg, 0);
    const int rr = lane >> 3, j = lane & 7;
    const uint32_t c0 = clk();
    if (threadIdx.x == 0) {
      for (int i = 0; i < 3; i++) { mbar_init(sb + B_FULL + 8 * i, 1); mbar_init(sb + B_EMPTY + 8 * i, tail ? 4 : 8); }
      for (int i = 0; i < 4; i++) mbar_init(sb + B_WF + 8 * i, 1);
      for (int i = 0; i < 2; i++) { mbar_init(sb + B_QFULL + 8 * i, 1); mbar_init(sb + B_QEMPTY + 8 * i, 4); mbar_init(sb + B_EVP0 + 8 * i, 4); }
      mbar_init(sb + B_EVH, 8); mbar_init(sb + B_EVQ, 8); mbar_init(sb + B_HALF, 8); mbar_init(sb + B_BG, 1); mbar_init(sb + B_M0, 1);
      asm volatile("fence.mbarrier_init.release.cluster;" ::: "memory");
    }
    __syncwarp();
    while (clk() - c0 < XDELAY) {}
    auto x_load = [&](int p) {
      const int r = warp * 16 + p * 4 + rr;
      const uint4* px = (const uint4*)(P.x + (size_t)min(W.q0 * 128 + wg * 64 + r, NN - 1) * 256) + j;
      const uint32_t off = (r >> 3) * 4096 + (r & 7) * 128 + ((j ^ (r & 7)) << 4);
      if (p < 4) {
#pragma unroll
        for (int c = 0; c < 4; c++) cp_async16(sQ + off + c * 1024, px + c * 8);
      }
      cp_commit();
    };
    if (total > 0) {
#pragma unroll 1
      for (int p = 0; p < XD; p++) x_load(p);
    }
    bar_sync(4, 384);
    if (wg == 1) bar_arrive(5, 256);

    if (total > 0) {
      {
        const bool own = (W.own >> wg) & 1;
        uint8_t* gh = (uint8_t*)g_h + (size_t)W.q0 * 65536 + wg * 32768;
#pragma unroll 1
        for (int p = 0; p < 4; p++) {
          const int r = warp * 16 + p * 4 + rr;
          const uint32_t off = (r >> 3) * 4096 + (r & 7) * 128 + ((j ^ (r & 7)) << 4);
          asm volatile("cp.async.wait_group %0;" :: "n"(XD - 1) : "memory");
          x_load(p + XD);
          float f[32];
#pragma unroll
          for (int c = 0; c < 4; c++) {
            const uint4 v = lds128(sQ + off + c * 1024);
            f[c * 8 + 0] = bf_lo(v.x); f[c * 8 + 1] = bf_hi(v.x); f[c * 8 + 2] = bf_lo(v.y); f[c * 8 + 3] = bf_hi(v.y);
            f[c * 8 + 4] = bf_lo(v.z); f[c * 8 + 5] = bf_hi(v.z); f[c * 8 + 6] = bf_lo(v.w); f[c * 8 + 7] = bf_hi(v.w);
          }
          float s0 = 0.f, s1 = 0.f, s2 = 0.f, s3 = 0.f;
#pragma unroll
          for (int i = 0; i < 16; i++) { s0 += f[2 * i]; s1 += f[2 * i + 1]; s2 += f[2 * i] * f[2 * i]; s3 += f[2 * i + 1] * f[2 * i + 1]; }
          float sum = s0 + s1, ss = s2 + s3;
#pragma unroll
          for (int k = 1; k < 8; k *= 2) { sum += __shfl_xor_sync(0xffffffffu, sum, k); ss += __shfl_xor_sync(0xffffffffu, ss, k); }
          const float mean = sum * (1.0f / 256.0f);
          float var = ss * (1.0f / 256.0f) - mean * mean;
          if (__any_sync(0xffffffffu, !(mean * mean <= 16.f * var))) {
            s2 = s3 = 0.f;
#pragma unroll
            for (int i = 0; i < 16; i++) { s2 += (f[2 * i] - mean) * (f[2 * i] - mean); s3 += (f[2 * i + 1] - mean) * (f[2 * i + 1] - mean); }
            ss = s2 + s3;
#pragma unroll
            for (int k = 1; k < 8; k *= 2) ss += __shfl_xor_sync(0xffffffffu, ss, k);
            var = ss * (1.0f / 256.0f);
          }
          float rs;
          asm("rsqrt.approx.ftz.f32 %0, %1;" : "=f"(rs) : "f"(var + 1e-5f));
          if (W.q0 * 128 + wg * 64 + r >= NN) rs = 0.f;
          const float nb = -mean * rs;
          if (own && j == 0) g_stat[W.q0 * 128 + wg * 64 + r] = make_float2(rs, nb);
#pragma unroll
          for (int c = 0; c < 4; c++) {
            uint4 h4 = make_uint4(pack_bf16(fmaf(f[c * 8], rs, nb), fmaf(f[c * 8 + 1], rs, nb)), pack_bf16(fmaf(f[c * 8 + 2], rs, nb), fmaf(f[c * 8 + 3], rs, nb)),
                                  pack_bf16(fmaf(f[c * 8 + 4], rs, nb), fmaf(f[c * 8 + 5], rs, nb)), pack_bf16(fmaf(f[c * 8 + 6], rs, nb), fmaf(f[c * 8 + 7], rs, nb)));
            sts128(sQ + off + c * 1024, h4);
            if (c == 3) {
              const float rk = rs * KS, e = fmaf(j == 7 ? nb - 0.5f * fmaf(f[31], rs, nb) : nb, KS, KC);
              h4 = make_uint4(pack_bf16(fmaf(f[24], rk, e), fmaf(f[25], rk, e)), pack_bf16(fmaf(f[26], rk, e), fmaf(f[27], rk, e)),
                              pack_bf16(fmaf(f[28], rk, e), fmaf(f[29], rk, e)), pack_bf16(fmaf(f[30], rk, e), j == 7 ? KC : fmaf(f[31], rk, e)));
            } else {
              h4 = make_uint4(hfma2(h4.x, KS2, KC2), hfma2(h4.y, KS2, KC2), hfma2(h4.z, KS2, KC2), hfma2(h4.w, KS2, KC2));
            }
            if (own) *(uint4*)(gh + off + c * 1024) = h4;
          }
        }
        __syncwarp();
        if (lane == 0) mbar_arrive(sb + B_EVH);
        fence_async_smem();
        bar_sync(1 + wg, 128);
      }
    }
    asm volatile("setmaxnreg.inc.sync.aligned.u32 %0;" :: "n"(CREG));
    STAMP(st0, wg, 1);

    float o[128];
    int qph = 0, st = tail ? wg : 0, ph = 0;
    auto release = [&](int stg) { if (lane == 0) mbar_arrive(sb + B_EMPTY + 8 * stg); };
    int resume = total > 0 ? -1 : 0;
    auto run = [&](auto hot_) __attribute__((always_inline)) {
    constexpr bool HOT = hot_.value;
    const int nloc = P.w[cta_id()].nloc;
    if (!HOT && resume == 0) {
#pragma unroll 1
      for (int i = 0; i < 32; i++) {
        const int r = i * 8 + wg * 4 + warp;
        cp_async16(sb + ((POS_M >> (r >> 6) * 4) & 15) * 32768 + sw_byte(r & 63, lane * 8), (const uint4*)P.wout + r * 32 + lane);
      }
    }
#pragma unroll 1
    for (int step = HOT || resume ? -1 : -4; step < nloc; step++) {
      ROLE;
      const bool isq = HOT && step < 0, isw = !HOT && step < 0;
      bool wide = false;
      if (HOT || step >= 0 || resume == 0) {
      if (isw) {
        const uint4* src = (const uint4*)(step < -2 ? P.wmsg : P.wv) + ((step & 1) * 128 + wg * 64 + warp) * 32 + lane;
        float cw[8] = {0.f, 0.f, 0.f, 0.f, 0.f, 0.f, 0.f, 0.f};
#pragma unroll 1
        for (int i = 0; i < 16; i++) cp_async16(sQ + sw_byte(i * 4 + warp, lane * 8), src + i * 128);
        cp_commit();
#pragma unroll
        for (int i = 0; i < 8; i++) {
          const uint4 v = __ldg((const uint4*)(step < -2 ? P.wmsg : P.wv) + (248 + i) * 32 + lane);
          const float k = step < -2 ? 0.f : (i == 7 ? -1.0f / 4.5f : -0.5f / 4.5f);
          cw[0] += bf_lo(v.x) * k; cw[1] += bf_hi(v.x) * k; cw[2] += bf_lo(v.y) * k; cw[3] += bf_hi(v.y) * k;
          cw[4] += bf_lo(v.z) * k; cw[5] += bf_hi(v.z) * k; cw[6] += bf_lo(v.w) * k; cw[7] += bf_hi(v.w) * k;
        }
        asm volatile("cp.async.wait_group 0;" ::: "memory");
#pragma unroll 1
        for (int i = 0; i < 16; i++) {
          const uint32_t ad = sQ + sw_byte(i * 4 + warp, lane * 8);
          const uint4 v = lds128(ad);
          uint4 w4 = make_uint4(pack_bf16(bf_lo(v.x) + cw[0], bf_hi(v.x) + cw[1]), pack_bf16(bf_lo(v.y) + cw[2], bf_hi(v.y) + cw[3]),
                                pack_bf16(bf_lo(v.z) + cw[4], bf_hi(v.z) + cw[5]), pack_bf16(bf_lo(v.w) + cw[6], bf_hi(v.w) + cw[7]));
          if (step == -1 && wg * 64 + i * 4 + warp == 127) w4 = make_uint4(0, 0, 0, 0);
          sts128(ad, w4);
        }
        fence_async_smem();
        bar_sync(7, 256);
      } else {
        SSTAMP(0);
        if (!isq) { mbar_wait(sb + B_QFULL + 8 * wg, qph); qph ^= 1; }
        STAMP(st0 && step == 0, wg, 8);
        SSTAMP(1);
        bar_sync(5 + wg, 256);
        SSTAMP(2);
      }
#pragma unroll 1
      for (int c = 0; c < 4; c++) {
        if (isq || step == 0) mbar_wait(isq && c == 0 ? sb + B_M0 : sb + B_WF + 8 * c, !isq && (HOT || resume));
        const int turn2 = isq ? 1 : (HOT || resume ? 3 : 4);
        if (c == turn2) bar_sync(5 + wg, 256);
        wg_fence();
        const uint64_t dA = desc_k(sb + SM_Q, wg * 2048 + c * 64), dW = desc_mn(sb, (((isq ? POS_M : posw) >> c * 4) & 15) * 2048);
        static_for<0, 4>([&](auto k) {
          if (k.value == 1) { if (isq && c == 0) mbar_wait(sb + B_WF, 0); wg_fence(); }
          wgmma_ss_n256_tb<k.value * 2, k.value * 512>(o, dA, dW, k.value > 0 ? 1 : c);
        });
        wg_commit();
        if ((c == 3 || c == turn2 - 1) && !isw) bar_arrive(6 - wg, 256);
        if (c == 0 && isq) { wg_wait<0>(); if (!tail) release(0); }
        wg_wait<1>();
      }
      wg_wait<0>();
      reg_fence(o);
      if (!isq) {
        STAMP(st0 && step == 0, wg, 9);
        SSTAMP(3);
        if (isw) bar_sync(1 + wg, 128); else if (lane == 0) mbar_arrive(sb + B_QEMPTY + 8 * wg);
        uint8_t* dw = (uint8_t*)(step < -2 ? g_Wmo : g_Wvo) + ((step & 1) * 2 + wg) * 32768 + warp * 8192 + g * 128;
        const int row0 = (W.loc0 + step) * 128 + wg * 64 + warp * 16;
        uint4 r[16];
#pragma unroll
        for (int u = 0; u < 8; u++) { r[2 * u] = ROW0(u); r[2 * u + 1] = ROW1(u); }
        if (isw) {
#pragma unroll
          for (int u = 0; u < 16; u++) *(uint4*)(dw + (u >> 2) * 1024 + ((((u & 2) * 2 + t) ^ g) << 4) + (u & 1) * 4096) = r[u];
        } else if (row0 < NN) {
          uint4* po = (uint4*)(P.out + (size_t)(row0 + g) * 256) + t;
          uint32_t c1 = clk();
#pragma unroll
          for (int u = 0; u < 16; u++) {
            if (!(DBG & 1) || !HOT || P.zero) red_bf16x8(po + (u >> 1) * 4 + (u & 1) * 256, r[u]);
            if (!HOT) { c1 += PACE; while ((int)(clk() - c1) < 0) {} }
          }
        }
        if (!HOT && step == -1) { bar_sync(7, 256); if (tid_is(0)) flag_release(F_W); __syncwarp(); STAMP(st0, wg, 3); }
        continue;
      }
      if (!tail) release(1);
      STAMP(st0, wg, 2);
      float c0 = (o[124] + (t == 3 ? 2.f : 1.f) * o[125]) * (-0.5f / 4.5f), c1 = (o[126] + (t == 3 ? 2.f : 1.f) * o[127]) * (-0.5f / 4.5f);
      c0 += __shfl_xor_sync(0xffffffffu, c0, 1); c1 += __shfl_xor_sync(0xffffffffu, c1, 1);
      c0 += __shfl_xor_sync(0xffffffffu, c0, 2); c1 += __shfl_xor_sync(0xffffffffu, c1, 2);
      float r0 = t == 3 ? 0.f : o[125], r1 = t == 3 ? 0.f : o[127], r2 = o[124], r3 = o[126];
#pragma unroll
      for (int i = 0; i < 31; i++) { r2 += o[4 * i]; r0 += o[4 * i + 1]; r3 += o[4 * i + 2]; r1 += o[4 * i + 3]; }
      r0 += r2; r1 += r3;
      r0 += __shfl_xor_sync(0xffffffffu, r0, 1); r1 += __shfl_xor_sync(0xffffffffu, r1, 1);
      r0 += __shfl_xor_sync(0xffffffffu, r0, 2); r1 += __shfl_xor_sync(0xffffffffu, r1, 2);
      r0 = fmaf(c0, -255.f, PSH / KC - r0); r1 = fmaf(c1, -255.f, PSH / KC - r1);
      wide = !(fabsf(c0) <= SAFE_C / KS) || !(fabsf(c1) <= SAFE_C / KS);
      bar_sync(1 + wg, 128);
#pragma unroll
      for (int k = 0; k < 16; k++)
        stsm4(sQ + warp * 8192 + ((lane >> 3) & 1) * 4096 + (k >> 2) * 1024 + (lane & 7) * 128 + ((((k & 3) * 2 + (lane >> 4)) ^ (lane & 7)) << 4),
              pack_bf16(o[8 * k] + c0, o[8 * k + 1] + c0), pack_bf16(o[8 * k + 2] + c1, o[8 * k + 3] + c1),
              pack_bf16(o[8 * k + 4] + c0, k == 15 && t == 3 ? r0 : o[8 * k + 5] + c0), pack_bf16(o[8 * k + 6] + c1, k == 15 && t == 3 ? r1 : o[8 * k + 7] + c1));
      fence_async_smem();
      bar_sync(1 + wg, 128);
      STAMP(st0, wg, 3);
      if (tail) { bar_sync(7, 256); if (wg == 0) { release(0); release(1); release(2); } }
      }

      float m0, m1;
      const int qh = tail ? 0 : wg, tl = W.role >> 2;
      uint32_t qo = qh * 2048;
      const uint32_t ko = (2 - tl) * 2048, stop = 1 + tl + (uint32_t)P.zero;
      float l0, l1;
      auto row_sums = [&]() { l0 = __shfl_sync(0xffffffffu, o[125] + 0.f, lane | 3); l1 = __shfl_sync(0xffffffffu, o[127] + 0.f, lane | 3); };
#define PART(u) make_uint4(pack_bf16(o[8 * u] - l0, o[8 * u + 1] - l0), pack_bf16(o[8 * u + 2] - l1, o[8 * u + 3] - l1), \
                           pack_bf16(o[8 * u + 4] - l0, o[8 * u + 5] - l0), pack_bf16(o[8 * u + 6] - l1, o[8 * u + 7] - l1))
      bool unsafe = !HOT;
#pragma unroll 1
      for (int seg = HOT ? 0 : resume - 1;; seg++) {
        ROLE;
        const bool last = __any_sync(0xffffffffu, seg || n1 == 0);
        m0 = m1 = !HOT && unsafe ? -INFINITY : 0.f;
        int first = 1;
        auto tile = [&](auto n_, bool endseg) __attribute__((always_inline)) -> bool {
          constexpr int N = n_.value;
          float s[N / 2]; uint32_t p[N / 4];
          if (!mbar_try_wait(sb + B_FULL + 8 * st, ph)) mbar_wait(sb + B_FULL + 8 * st, ph);
          const bool again = !HOT && N == 112 && first && !seg;
          if (HOT || N == 128) bar_sync(5 + wg, 256);
          else asm volatile("{\n.reg .pred p;\nsetp.eq.u32 p, %1, 0;\n@p bar.sync %0, 256;\n}\n" :: "r"(5 + wg), "r"((uint32_t)again) : "memory");
          wg_fence();
          const uint64_t dQ = desc_k(sb + SM_Q, qo), dK = desc_k(sb, ko + st * 4096);
          qo += (uint32_t)P.zero;
          static_for<0, 16>([&](auto k) { constexpr int kk = (k.value + KROT) & 15, off = (kk >> 2) * 64 + (kk & 3) * 2; wgmma_qk<off, off>(s, dQ, dK, k.value > 0); });
          wg_commit();
          if (HOT || N == 128) bar_arrive(6 - wg, 256);
          else asm volatile("{\n.reg .pred p;\nsetp.eq.u32 p, %1, 0;\n@p bar.arrive %0, 256;\n}\n" :: "r"(6 - wg), "r"((uint32_t)again) : "memory");
          if (HOT && N == 112 && first && !seg) {
            float a0 = 0.f, a1 = 0.f, a2 = 0.f, a3 = 0.f;
#pragma unroll
            for (int i = 0; i < 32; i++) { a0 += o[4 * i] * o[4 * i]; a2 += o[4 * i + 1] * o[4 * i + 1]; a1 += o[4 * i + 2] * o[4 * i + 2]; a3 += o[4 * i + 3] * o[4 * i + 3]; }
            a0 += a2; a1 += a3;
            a0 += __shfl_xor_sync(0xffffffffu, a0, 1); a1 += __shfl_xor_sync(0xffffffffu, a1, 1);
            a0 += __shfl_xor_sync(0xffffffffu, a0, 2); a1 += __shfl_xor_sync(0xffffffffu, a1, 2);
            unsafe = __any_sync(0xffffffffu, bar_red_or(tail ? 7 : 1 + wg, tail ? 256 : 128, wide || !(a0 <= SAFE_N2 / (KS * KS)) || !(a1 <= SAFE_N2 / (KS * KS))));
            if (lane == 0) { asm volatile("st.shared.u8 [%0], %1;" :: "r"(sb + SM_UNSAFE + wg), "r"((uint32_t)unsafe) : "memory"); mbar_arrive(sb + B_EVQ); }
          }
          STAMP(N == 112 && first && !seg && st0, wg, 0);
          wg_wait<0>();
          reg_fence(s);
          if (HOT && N == 112 && unsafe) return true;
          if (endseg) { if (lane == 0) mbar_arrive(sb + B_QEMPTY + 8 * wg); }
          if (!HOT && unsafe) {
            float a0 = fmaxf(s[0], s[1]), a1 = fmaxf(s[2], s[3]);
#pragma unroll
            for (int i = 1; i < N / 8; i++) { a0 = fmaxf(a0, fmaxf(s[4 * i], s[4 * i + 1])); a1 = fmaxf(a1, fmaxf(s[4 * i + 2], s[4 * i + 3])); }
            if (__any_sync(0xffffffffu, (a0 > m0 + TAU) || (a1 > m1 + TAU))) {
              a0 = fmaxf(a0, __shfl_xor_sync(0xffffffffu, a0, 1)); a1 = fmaxf(a1, __shfl_xor_sync(0xffffffffu, a1, 1));
              a0 = fmaxf(a0, __shfl_xor_sync(0xffffffffu, a0, 2)); a1 = fmaxf(a1, __shfl_xor_sync(0xffffffffu, a1, 2));
              const float x0 = ceilf(fmaxf(m0, a0)), x1 = ceilf(fmaxf(m1, a1)), sc0 = ex2(m0 - x0), sc1 = ex2(m1 - x1);
              m0 = x0; m1 = x1;
#pragma unroll
              for (int i = 0; i < 32; i++) { o[4 * i] *= sc0; o[4 * i + 1] *= sc0; o[4 * i + 2] *= sc1; o[4 * i + 3] *= sc1; }
            }
#pragma unroll
            for (int i = 0; i < N / 8; i++) { s[4 * i] -= m0; s[4 * i + 1] -= m0; s[4 * i + 2] -= m1; s[4 * i + 3] -= m1; }
          }
          auto pv = [&](auto k) { wgmma_rs_n256_tb<k.value * 512 + (63 << 16)>(o, p[4 * k.value], p[4 * k.value + 1], p[4 * k.value + 2], p[4 * k.value + 3], dK, k.value > 0 || N == 128 ? 1 : !first); };
#pragma unroll
          for (int i = 0; i < 16; i++) { p[i] = pack_bf16(ex2(s[2 * i]), ex2(s[2 * i + 1])); asm volatile("" : "+r"(p[i]) :: "memory"); }
          reg_fence(o);
          do bar_sync(5 + wg, 256); while (P.zero);
          wg_fence();
          static_for<0, 4>(pv);
          wg_commit();
#pragma unroll
          for (int i = 16; i < N / 4; i++) { p[i] = pack_bf16(ex2(s[2 * i]), ex2(s[2 * i + 1])); asm volatile("" : "+r"(p[i]) :: "memory"); }
          wg_fence();
          static_for<4, N / 16>(pv);
          wg_commit();
          bar_arrive(6 - wg, 256);
          if (N == 128) { wg_wait<1>(); if (endseg && last) { if (lane == 0) mbar_arrive(sb + B_HALF); } }
          wg_wait<0>();
          reg_fence(o); reg_fence(p);
          release(st);
          if (st) { st--; ph ^= 1; } else st = stop;
          return false;
        };
#pragma unroll 1
        for (int left = tail ? 8 - wg : (seg ? W.nb1 : W.nb0); left > 0; left--) { if (tile(IC<112>{}, false)) { resume = 1; return; } STAMP(first && !seg && st0, wg, 4); first = 0; }
#pragma unroll 1
        for (int left = tail ? 32 + wg : (seg ? W.na1 : W.na0); left > 0; left--) tile(IC<128>{}, left == 1);
        STAMP(st0 && last, wg, 6);
        {
        ROLE;
        if (last && fin && !(tail && wg == 1)) break;
        row_sums();
        if (last) mbar_wait(sb + (tail ? B_QEMPTY : B_HALF), 0);
        const uint32_t sp = sb + (tail ? 0 : (last ? (posw >> 12) + wg : (wg ? 4 - 2 * st : 6))) * 32768, sm = sb + SM_ML + (tail ? 0 : wg) * 512;
#pragma unroll
        for (int u = 0; u < 16; u++) sts128(sp + (u * 128 + tid) * 16, PART(u));
        if (t == 0) {
          asm volatile("st.shared.v2.f32 [%0], {%1,%2};" :: "r"(sm + (warp * 16 + g) * 8), "f"(m0), "f"(l0) : "memory");
          asm volatile("st.shared.v2.f32 [%0], {%1,%2};" :: "r"(sm + (warp * 16 + g) * 8 + 64), "f"(m1), "f"(l1) : "memory");
        }
        __syncwarp();
        if (lane == 0) mbar_arrive(sb + B_EVP0 + 8 * wg);
        STAMP(st0 && last, wg, 7);
        if (last) break;
        mbar_wait(sb + B_QFULL + 8 * wg, qph); qph ^= 1;
        uint32_t u; asm volatile("ld.shared.u8 %0, [%1];" : "=r"(u) : "r"(sb + SM_UNSAFE + wg) : "memory");
        unsafe = __any_sync(0xffffffffu, u != 0);
        if (HOT && unsafe) { resume = 2; return; }
        }
      }

      if (P.w[cta_id()].role & R_FIN) {
        ROLE;
        if (tail && wg == 1) break;
        row_sums();
        const int rl = wg * 64 + warp * 16 + g;
        uint32_t a[64];
#pragma unroll
        for (int i = 0; i < 64; i++) a[i] = pack_bf16(o[2 * i] - (i & 1 ? l1 : l0), o[2 * i + 1] - (i & 1 ? l1 : l0));
        reg_fence(a);
        {
          float2 e0, e1;
          mbar_wait(sb + B_QFULL + 8 * wg, qph);
          asm volatile("ld.shared.v2.f32 {%0,%1}, [%2];" : "=f"(e0.x), "=f"(e0.y) : "r"(sb + SM_ML + rl * 8) : "memory");
          asm volatile("ld.shared.v2.f32 {%0,%1}, [%2];" : "=f"(e1.x), "=f"(e1.y) : "r"(sb + SM_ML + rl * 8 + 64) : "memory");
          STAMP(st0, wg, 7);
          uint4 v[16];
#pragma unroll
          for (int u = 0; u < 16; u++) v[u] = lds128(sQ + (u * 128 + tid) * 16);
          uint32_t fb0 = 0x3f803f80u, fb1 = 0x3f803f80u;
          const float s0 = l0 + e0.y, s1 = l1 + e1.y;
          if (__any_sync(0xffffffffu, m0 != e0.x || m1 != e1.x || !(fmaxf(s0, s1) < 0x1p40f) || !(fminf(s0, s1) > 0x1p-40f))) {
            const float x0 = fmaxf(m0, e0.x), x1 = fmaxf(m1, e1.x);
            const float d0 = fmaxf(m0 - x0, -1000.f), d1 = fmaxf(m1 - x1, -1000.f), f0 = fmaxf(e0.x - x0, -1000.f), f1 = fmaxf(e1.x - x1, -1000.f);
            l0 = l0 * ex2(d0) + e0.y * ex2(f0); l1 = l1 * ex2(d1) + e1.y * ex2(f1);
            const int E0 = fexp(l0), E1 = fexp(l1);
            const uint32_t fa0 = pow2_bf2((int)d0 - E0), fa1 = pow2_bf2((int)d1 - E1);
            fb0 = pow2_bf2((int)f0 - E0); fb1 = pow2_bf2((int)f1 - E1);
            l0 = __uint_as_float(__float_as_uint(l0) - (E0 << 23)); l1 = __uint_as_float(__float_as_uint(l1) - (E1 << 23));
#pragma unroll
            for (int i = 0; i < 32; i++) { a[2 * i] = hmul2(a[2 * i], fa0); a[2 * i + 1] = hmul2(a[2 * i + 1], fa1); }
          } else { l0 = s0; l1 = s1; }
#pragma unroll
          for (int u = 0; u < 16; u++) {
            a[4 * u] = hfma2(v[u].x, fb0, a[4 * u]); a[4 * u + 1] = hfma2(v[u].y, fb1, a[4 * u + 1]);
            a[4 * u + 2] = hfma2(v[u].z, fb0, a[4 * u + 2]); a[4 * u + 3] = hfma2(v[u].w, fb1, a[4 * u + 3]);
          }
        }
        float fs0, fs1;
        asm("rcp.approx.ftz.f32 %0, %1;" : "=f"(fs0) : "f"(l0 * (KS / KC))); asm("rcp.approx.ftz.f32 %0, %1;" : "=f"(fs1) : "f"(l1 * (KS / KC)));
        STAMP(st0, wg, 8);
        reg_fence(a);
        bar_sync(5 + wg, 256);
        uint64_t dW[4];
        float y0[64], y1[64];
        auto half0 = [&](auto u_) {
          constexpr int u = u_.value;
          if (u % 4 == 0) { mbar_wait(sb + B_WF + 2 * u, 1); wg_fence(); dW[u / 4] = desc_mn(sb, ((posw >> u) & 15) * 2048); }
          wgmma_rs_n128_tb<(u & 3) * 512>(y0, a[4 * u], a[4 * u + 1], a[4 * u + 2], a[4 * u + 3], dW[u / 4], u != 0);
        };
        auto half1 = [&](auto u_) {
          constexpr int u = u_.value;
          wgmma_rs_n128_tb<(u & 3) * 512 + 128>(y1, a[4 * u], a[4 * u + 1], a[4 * u + 2], a[4 * u + 3], dW[u / 4], u != 0);
        };
        const bool wr = W.q0 * 128 + wg * 64 + warp * 16 < NN;
        uint4* po = (uint4*)(P.out + (size_t)(W.q0 * 128 + rl) * 256) + t;
        auto emit = [&](const float* y, uint4* dst) {
          if (wr && (!(DBG & 2) || P.zero)) {
            OUTW(dst, make_uint4(pack_bf16(y[0] * fs0, y[1] * fs0), pack_bf16(y[4] * fs0, y[5] * fs0), pack_bf16(y[8] * fs0, y[9] * fs0), pack_bf16(y[12] * fs0, y[13] * fs0)));
            OUTW(dst + 8 * 32, make_uint4(pack_bf16(y[2] * fs1, y[3] * fs1), pack_bf16(y[6] * fs1, y[7] * fs1), pack_bf16(y[10] * fs1, y[11] * fs1), pack_bf16(y[14] * fs1, y[15] * fs1)));
          }
          wg_fence();
        };
        static_for<0, 16>(half0);
        wg_commit();
        static_for<0, 4>(half1);
        wg_commit();
        wg_wait<1>();
        reg_fence(y0);
        emit(y0, po); static_for<4, 8>(half1);
        emit(y0 + 16, po + 4); static_for<8, 12>(half1);
        emit(y0 + 32, po + 8); static_for<12, 16>(half1);
        wg_commit();
        bar_arrive(6 - wg, 256);
        emit(y0 + 48, po + 12);
        wg_wait<0>();
        reg_fence(a); reg_fence(y1);
        STAMP(st0, wg, 9);
#pragma unroll
        for (int u = 0; u < 4; u++) emit(y1 + 16 * u, po + 16 + 4 * u);
        break;
      }
    }
    STAMP(st0, wg, 11);
    DUMP(st0, wg, 0, 16);
    if (!P.zero) { asm volatile("exit;"); __builtin_unreachable(); }
#pragma unroll
    for (int i = 0; i < 32; i++)
      asm volatile("ld.volatile.shared.v4.f32 {%0,%1,%2,%3}, [%4];" : "=f"(o[4 * i]), "=f"(o[4 * i + 1]), "=f"(o[4 * i + 2]), "=f"(o[4 * i + 3]) : "r"(sb) : "memory");
    };
    if (resume < 0) run(std::true_type{});
    run(std::false_type{});
    asm volatile("setmaxnreg.dec.sync.aligned.u32 %0;" :: "n"(504 - 2 * CREG));
  } else {
    STAMP(lane == 0 && warp == 0, 2, 0);
        const int mi = cta >> 3;
    const uint32_t sW = sb + 3 * 32768;
    uint4 wa[4], wb[8];
    uint32_t epoch = 0;
    if (EPF && threadIdx.x == 256) epoch = ld_relaxed(g_flag + F_EPOCH);
    {
      const uint4* pq = (const uint4*)(P.wq + ((mi & 15) * 16 + g) * 256) + warp * 8 + t;
      const uint4* pk = (const uint4*)(P.wk + ((cta & 7) * 32 + g) * 256) + warp * 8 + t;
#pragma unroll
      for (int i = 0; i < 4; i++) wa[i] = __ldg(pq + (i >> 1) * 256 + (i & 1) * 4);
#pragma unroll
      for (int i = 0; i < 8; i++) wb[i] = __ldg(pk + (i >> 1) * 256 + (i & 1) * 4);
    }
    bar_sync(4, 384);
    {
#pragma unroll
      for (int n = 0; n < 4; n++) {
        float c[4] = {0.f, 0.f, 0.f, 0.f};
#pragma unroll
        for (int u = 0; u < 2; u++) {
          mma16816(c, wa[u].x, wa[2 + u].x, wa[u].y, wa[2 + u].y, wb[2 * n + u].x, wb[2 * n + u].y);
          mma16816(c, wa[u].z, wa[2 + u].z, wa[u].w, wa[2 + u].w, wb[2 * n + u].z, wb[2 * n + u].w);
        }
        asm volatile("st.shared.v2.f32 [%0], {%1,%2};" :: "r"(sW + ((warp * 16 + g) * 40 + n * 8 + 2 * t) * 4), "f"(c[0]), "f"(c[1]) : "memory");
        asm volatile("st.shared.v2.f32 [%0], {%1,%2};" :: "r"(sW + ((warp * 16 + g + 8) * 40 + n * 8 + 2 * t) * 4), "f"(c[2]), "f"(c[3]) : "memory");
      }
      STAMP(lane == 0 && warp == 0, 2, 7);
      bar_sync(3, 128);
      if (warp < 2) {
        float c[8] = {0.f, 0.f, 0.f, 0.f, 0.f, 0.f, 0.f, 0.f};
#pragma unroll
        for (int k = 0; k < 4; k++) {
          const uint4 v = lds128(sW + ((k * 16 + warp * 8 + g) * 40 + t * 8) * 4), w = lds128(sW + ((k * 16 + warp * 8 + g) * 40 + t * 8 + 4) * 4);
          c[0] += __uint_as_float(v.x); c[1] += __uint_as_float(v.y); c[2] += __uint_as_float(v.z); c[3] += __uint_as_float(v.w);
          c[4] += __uint_as_float(w.x); c[5] += __uint_as_float(w.y); c[6] += __uint_as_float(w.z); c[7] += __uint_as_float(w.w);
        }
        const float ms = 1.4426950408889634f / 16.0f / KS;
        if (cta < 128)
          *(uint4*)((uint8_t*)g_M + sw_byte(mi * 16 + warp * 8 + g, (cta & 7) * 32 + t * 8)) =
              make_uint4(pack_bf16(c[0] * ms, c[1] * ms), pack_bf16(c[2] * ms, c[3] * ms), pack_bf16(c[4] * ms, c[5] * ms), pack_bf16(c[6] * ms, c[7] * ms));
      }
    }
    asm volatile("setmaxnreg.dec.sync.aligned.u32 %0;" :: "n"(504 - 2 * CREG));
    STAMP(lane == 0 && warp == 0, 2, 13);
    bar_sync(3, 128);
#define ep1 (lds32(sb + SM_EPOCH) + 1)
    if (threadIdx.x == 256 && cta < 128) { if (DBG & 16) asm volatile("red.relaxed.gpu.global.add.u32 [%0], 1;" :: "l"(g_flag + F_M + (cta >> 5)) : "memory"); else flag_release(F_M + (cta >> 5)); }
    __syncwarp();
    ROLE;
    if (warp == 3 && W.own) { mbar_wait_w(sb + B_EVH, 0); if (DBG & 32) { if (lane == 0) asm volatile("red.relaxed.gpu.global.add.u32 [%0], 1;" :: "l"(g_flag + F_H) : "memory"); } else flag_release_w(F_H); STAMP(lane == 0, 2, 6); }
    if (warp == 0) {
      if (lane == 0) {
        STAMP(true, 2, 1);
        if (!EPF) epoch = ld_relaxed(g_flag + F_EPOCH);
        if (total > 0) {
#pragma unroll
          for (int c = 0; c < 3; c++) mbar_expect_tx(sb + B_WF + 8 * c, c == 0 ? WCH_B - 8192 : WCH_B);
          mbar_expect_tx(sb + B_M0, 8192);
          int c = 0;
#pragma unroll 1
          for (uint32_t it = 0; c < 4; it++) {
            uint4 f;
            asm volatile("ld.relaxed.gpu.global.v4.u32 {%0,%1,%2,%3}, [%4];" : "=r"(f.x), "=r"(f.y), "=r"(f.z), "=r"(f.w) : "l"(g_flag + F_M) : "memory");
            uint32_t tm;
            asm volatile("mad.lo.u32 %0, %1, 32, 32;" : "=r"(tm) : "r"(epoch));
            int ok = (int)(f.x - tm) < 0 ? 0 : (int)(f.y - tm) < 0 ? 1 : (int)(f.z - tm) < 0 ? 2 : (int)(f.w - tm) < 0 ? 3 : 4;
            if (it > (1u << 23)) ok = 4;
            if (ok > c) {
              asm volatile("fence.acquire.gpu;" ::: "memory"); fence_async_gmem();
              if (c == 0) bulk_g2s(sb + (POS_M & 15) * 32768, g_M, 8192, sb + B_M0);
            }
#pragma unroll 1
            for (; c < ok; c++) {
              const uint32_t skip = c == 0 ? 8192 : 0;
              bulk_g2s(sb + ((POS_M >> c * 4) & 15) * 32768 + skip, pofs<const uint8_t>(g_M, c * WCH_B + skip), WCH_B - skip, sb + B_WF + 8 * c);
              STAMP(c == 0, 2, 2);
            }
          }
        }
        asm volatile("st.shared.u32 [%0], %1;" :: "r"(sb + SM_EPOCH), "r"(epoch) : "memory");
        if (total > 0) mbar_expect_tx(sb + B_WF + 24, WCH_B);
        int st = 0, ph = 0, qph = 0;
        const int nsl = tail ? 3 : 2;
        auto next_slot = [&]() { mbar_wait(sb + B_EMPTY + 8 * st, ph); if (++st == nsl) { st = 0; ph ^= 1; } };
        auto w_load = [&](int c0, int c1) {
#pragma unroll 1
          for (int c = c0; c < c1; c++) {
            mbar_expect_tx(sb + B_WF + 8 * c, WCH_B);
            bulk_g2s(sb + ((posw >> c * 4) & 15) * 32768, pofs<const uint8_t>(fin ? g_Wvo : g_Wmo, c * WCH_B), WCH_B, sb + B_WF + 8 * c);
          }
        };
        auto q_load = [&](const uint4* src, bool wait_empty) {
#pragma unroll 1
          for (int h = 0; h < 2; h++) {
            if (wait_empty) mbar_wait(sb + B_QEMPTY + 8 * h, qph);
            mbar_expect_tx(sb + B_QFULL + 8 * h, 32768);
            (HINT & 2 ? bulk_g2s_last : bulk_g2s)(sb + SM_Q + h * 32768, src + h * 2048, 32768, sb + B_QFULL + 8 * h);
          }
          if (wait_empty) qph ^= 1;
        };
        auto part_out = [&](int slot, int h, uint32_t region, int parity) {
          mbar_wait(sb + B_EVP0 + 8 * h, parity);
          fence_async_smem();
          bulk_s2g(g_part + slot * 4096 + h * 2048, sb + region * 32768, 32768);
          bulk_s2g(g_ml + slot * 128 + h * 64, sb + SM_ML + h * 512, 512);
          bulk_commit();
        };
        auto announce = [&](int f) {
          if (RELF) { fence_async_gmem(); flag_release(f); }
          else asm volatile("red.relaxed.gpu.global.add.u32 [%0], 1;" :: "l"(g_flag + f) : "memory");
        };
        if (total > 0) {
          STAMP(true, 2, 3);
          flag_wait(F_H, ep1 * NHSIG); fence_async_gmem();
          STAMP(true, 2, 4);
          uint32_t ko = W.k0 * 8192;
#pragma unroll 1
          for (int j = 0; j < total; j++) {
            if (j == n0) {
              flag_wait(F_QP + W.q1 * LN_, ep1); fence_async_gmem();
              const uint32_t u = __ldcg(g_unsafe + W.q1);
              asm volatile("st.shared.u32 [%0], %1;" :: "r"(sb + SM_UNSAFE), "r"(u) : "memory");
              ko = W.k1 * 8192;
            }
            if (j == n0 + 1) q_load(g_qp + W.q1 * 4096, true);
            if (j == total - 1) { flag_wait(F_W, ep1); fence_async_gmem(); if (!tail) w_load(0, 1); }
            const uint32_t bytes = (j < n0 ? j < W.nb0 : j - n0 < W.nb1) ? 112 * 512 : 128 * 512, s0 = st;
            const uint32_t region = (tail ? 1 : 2) + 2 * s0, skip = j == n0 + 1 ? 32768 : 0;
            if (skip) part_out(W.slotA, 0, 6, 0);
            next_slot();
            mbar_expect_tx(sb + B_FULL + 8 * s0, bytes);
            bulk_g2s(sb + region * 32768 + skip, pofs<const uint8_t>(g_h, ko + skip), bytes - skip, sb + B_FULL + 8 * s0);
            if (skip) {
              part_out(W.slotA, 1, region, 0);
              bulk_wait_read();
              bulk_g2s(sb + region * 32768, pofs<const uint8_t>(g_h, ko), skip, sb + B_FULL + 8 * s0);
              bulk_wait_all();
              announce(F_PART + W.slotA * LN_);
            }
            ko += bytes;
          }
          next_slot();
          if (tail) { next_slot(); next_slot(); }
        } else { flag_wait(F_W, ep1); fence_async_gmem(); }
        STAMP(true, 2, 5);
        const bool staged = total > 0 && !tail;
        w_load(staged, staged ? (fin ? 2 : 3) : 4);
#pragma unroll 1
        for (int i = 0; i < W.nloc; i++) {
          const int tl = W.loc0 + i, last = tl * 128 + 127 < NN ? tl * 128 + 127 : NN - 1;
          flag_wait(F_AGG + ((last >= NGW) + (last >= 4 * NGW) + (last >= 9 * NGW)) * LN_, ep1 * NGW); fence_async_gmem();
          if (total == 0) g_flag[F_EPOCH] = epoch + 1;
          q_load(g_agg + tl * 4096, total > 0 || i > 0);
        }
        if (tail) { mbar_wait(sb + B_BG, 0); mbar_wait(sb + B_EVP0 + 8, 0); mbar_arrive(sb + B_QFULL); }
        else if (fin) {
          int h = 0, c = 2, have = W.slotB >= 0 || (DBG & 8) ? 2 : 0;
          mbar_wait(sb + B_BG, 0);
#pragma unroll 1
          for (uint32_t it = 0; (h < 2 || c < 4) && it < (1u << 23); it++) {
            if (have < 2) {
              uint2 f;
              asm volatile("ld.relaxed.gpu.global.v2.u32 {%0,%1}, [%2];" : "=r"(f.x), "=r"(f.y) : "l"(g_flag + F_PART + W.slotA * LN_) : "memory");
              have = (int)(f.x - (epoch + 1)) < 0 ? 0 : ((int)(f.y - (epoch + 1)) < 0 ? 1 : 2);
            }
            if (h < have && mbar_try_wait_nb(sb + B_QEMPTY + 8 * h, 0)) {
              asm volatile("fence.acquire.gpu;" ::: "memory"); fence_async_gmem();
              STAMP(true, 2, 14 + h);
              mbar_expect_tx(sb + B_QFULL + 8 * h, 32768 + 512);
              bulk_g2s(sb + SM_ML + h * 512, g_ml + W.slotA * 128 + h * 64, 512, sb + B_QFULL + 8 * h);
              bulk_g2s(sb + SM_Q + h * 32768, g_part + W.slotA * 4096 + h * 2048, 32768, sb + B_QFULL + 8 * h);
              h++;
            }
            const bool half = mbar_try_wait_nb(sb + B_HALF, 0);
            const int c1 = half ? 4 : (h > 0 ? 3 : 2);
            if (c < c1) { w_load(c, c1); c = c1; }
          }
        } else if (total > 0) {
#pragma unroll 1
          for (int h = 0; h < 2; h++) part_out(W.slotB, h, (posw >> 12) + h, 1);
          asm volatile("cp.async.bulk.wait_group.read 1;" ::: "memory");
          w_load(3, 4);
          asm volatile("cp.async.bulk.wait_group 1;" ::: "memory");
          announce(F_PART + W.slotB * LN_);
          STAMP(true, 2, 14);
          bulk_wait_all();
          announce(F_PART + W.slotB * LN_ + 1);
          STAMP(true, 2, 15);
        }
        DUMP(true, 2, 14, 16);
        DUMP(true, 2, 0, 8);
      }
      return;
    }
  }
    {
      const int gw = cta * 3 + warp - 1;
      ROLE;
      if (total > 0) {
        mbar_wait_w(sb + B_EVQ, 0);
        const uint32_t c0 = clk();
        if (warp == 1 && (W.role & R_PUB)) {
          g_unsafe[W.q0] = lds32(sb + SM_UNSAFE);
#pragma unroll 1
          for (int k = 0; k < 4; k++) {
            __nanosleep(2000);
            if (lane == 0) bulk_s2g(pofs<uint4>(g_qp, W.q0 * 65536 + k * 16384), sb + SM_Q + k * 16384, 16384);
            bulk_commit();
          }
          bulk_wait_all();
          flag_release_w(F_QP + W.q0 * LN_);
        }
        while (__any_sync(0xffffffffu, clk() - c0 < GSTART)) __nanosleep(500);
        STAMP(lane == 0 && warp == 1, 2, 8);
#define ovf_cnt pofs<uint32_t>(g_flag, (F_OVF + (ep1 & 1) * LN_) * 4)
        if (gw == 0) g_flag[F_OVF + ((ep1 + 1) & 1) * LN_] = 0;
#pragma unroll 1
        for (int e0 = gw * 32; e0 < NE; e0 += NGW * 32 * 7) {
          int d[7], s[7], pos[7];
          const int* pd = pofs<const int>(P.dst, (e0 + lane) * 4);
          const int* ps = pofs<const int>(P.src, (e0 + lane) * 4);
#pragma unroll
          for (int k = 0; k < 7; k++) { const bool ok = e0 + k * NGW * 32 < NE; d[k] = ok ? (HINT & 1 ? __ldcs(pd + k * NGW * 32) : __ldg(pd + k * NGW * 32)) : -1; s[k] = ok ? (HINT & 1 ? __ldcs(ps + k * NGW * 32) : __ldg(ps + k * NGW * 32)) : 0; }
          uint32_t ov = 0;
#pragma unroll
          for (int k = 0; k < 7; k++) {
            pos[k] = 0;
            if (d[k] >= 0) asm volatile("atom.relaxed.gpu.global.add.u32 %0, [%1], 1;" : "=r"(pos[k]) : "l"(pofs<int>(g_cnt, d[k] << 2)) : "memory");
            s[k] = (uint32_t)(uintptr_t)g_u + s[k] * 512;
            if (d[k] >= 0 && pos[k] < CAP) asm volatile("st.volatile.global.u32 [%0], %1;" :: "l"(pofs<int>(g_bin, (d[k] * CAPS + pos[k]) << 2)), "r"(s[k]) : "memory");
            ov |= (pos[k] >= CAP) << k;
          }
          if (__any_sync(0xffffffffu, ov != 0)) {
            uint32_t at;
            asm volatile("atom.relaxed.gpu.global.add.u32 %0, [%1], %2;" : "=r"(at) : "l"(ovf_cnt), "r"(__popc(ov)) : "memory");
#pragma unroll
            for (int k = 0; k < 7; k++) if ((ov >> k) & 1) g_ovf[at++] = make_int2(d[k], s[k]);
          }
        }
        flag_wait_w(F_H, ep1 * NHSIG);
#pragma unroll 1
        for (int n0 = gw; n0 < NN; n0 += 4 * NGW) {
          uint4 xv[4]; float2 st[4];
#pragma unroll
          for (int k = 0; k < 4; k++) {
            const int n = n0 + k * NGW < NN ? n0 + k * NGW : n0;
            xv[k] = (HINT & 1 ? ldcs_v : ldcg_v)(pofs<const uint4>(P.x, n * 512 + lane * 16));
            st[k] = __ldcg(pofs<const float2>(g_stat, n * 8));
          }
#pragma unroll
          for (int k = 3; k >= 0; k--) {
            const int n = n0 + k * NGW;
            const float a = st[k].x * US, c = fmaf(st[k].y, US, UB + 8388608.0f);
#define FIX(w) __byte_perm(__float_as_uint(fmaf(bf_lo(w), a, c)), __float_as_uint(fmaf(bf_hi(w), a, c)), 0x5410)
            if (n < NN) {
              *pofs<uint4>(P.out, n * 512 + lane * 16) = xv[k];
              *pofs<uint4>(g_u, n * 512 + lane * 16) = make_uint4(FIX(xv[k].x), FIX(xv[k].y), FIX(xv[k].z), FIX(xv[k].w));
            }
          }
        }
        flag_release_w(F_BIN);
        STAMP(lane == 0 && warp == 1, 2, 9);
        flag_wait_w(F_BIN, ep1 * NGW);
        STAMP(lane == 0 && warp == 1, 2, 10);
        const int myn = gw + lane * NGW < NN ? gw + lane * NGW : gw;
        int cnts = __ldcg(g_cnt + myn);
        cnts = gw + lane * NGW < NN ? (cnts > CAP ? CAP + 1 : cnts) | ((int)__ldg((const unsigned short*)P.dinv + myn) << 16) : 0;
        __syncwarp();
        g_cnt[myn] = 0;
        const uint32_t uhi = (uintptr_t)g_u >> 32, lx = lane * 16;
        uint32_t obin = gw * CAPS * 4;
        uint32_t ent = __ldcg(pofs<const uint32_t>(g_bin, obin + lane * 4)), entn = __ldcg(pofs<const uint32_t>(g_bin, obin + NGW * CAPS * 4 + lane * 4));
        int cd = __shfl_sync(0xffffffffu, cnts, 0), cb = min(cd & 0xffff, CAP), e = 0;
        uint32_t sa[4] = {0, 0, 0, 0}, sh[4] = {0, 0, 0, 0};
        auto add = [&](uint32_t x, uint32_t y, uint32_t z, uint32_t w) {
          sa[0] += x; sa[1] += y; sa[2] += z; sa[3] += w;
          sh[0] += x >> 16; sh[1] += y >> 16; sh[2] += z >> 16; sh[3] += w >> 16;
        };
        int rnd = -1, rows = -1, cdo = 0;
#pragma unroll 1
        for (;;) {
          const bool hold = rows >= 0 && rnd == 8;
          const int m = hold ? 0 : cb - e;
          uint4 v[8];
          if (m >= 8) {
#pragma unroll
            for (int k = 0; k < 8; k++) v[k] = ldcg_v(addr64(__shfl_sync(0xffffffffu, ent, k) + lx, uhi));
          } else {
#pragma unroll
            for (int k = 0; k < 8; k++) {
              v[k] = make_uint4(0, 0, 0, 0);
              if (k < 7) ldcg_if(v[k], addr64(__shfl_sync(0xffffffffu, ent, k) + lx, uhi), k < m);
            }
          }
          if (rows >= 0) {
            const int n = gw + rnd * NGW;
            if (n < NN) {
              const float di = __uint_as_float(cdo & 0xffff0000u) * (1.0f / US), nl = -di * UB * (float)rows;
#define AGG(k) pack_bf16(fmaf((float)(sa[k] - (sh[k] << 16)), di, nl), fmaf((float)sh[k], di, nl))
              *pofs<uint4>(g_agg, ((n >> 3) * 4096 + (n & 7) * 144) ^ ((lx & 0x70) | ((lx & 0x180) << 3))) = make_uint4(AGG(0), AGG(1), AGG(2), AGG(3));
            }
#pragma unroll
            for (int k = 0; k < 4; k++) sa[k] = sh[k] = 0;
            rows = -1;
            if (rnd == 0 || rnd == 3 || rnd == 8 || rnd == NRND - 1) flag_release_w(F_AGG + ((rnd > 0) + (rnd > 3) + (rnd > 8)) * LN_);
            if (rnd == NRND - 1) break;
            if (hold) {
              if (fin && W.slotB >= 0) {
        #pragma unroll 1
                for (int k = 0; k < 2; k++) flag_wait_w(F_PART + (k ? W.slotB : W.slotA) * LN_, ep1);
        #pragma unroll 1
                for (int b = warp - 1; b < 8; b += 3) {
                  float2* ma = g_ml + W.slotA * 128 + b * 16 + g;
                  const float2* mb = g_ml + W.slotB * 128 + b * 16 + g;
                  const float2 a0 = __ldcg(ma), a1 = __ldcg(ma + 8), b0 = __ldcg(mb), b1 = __ldcg(mb + 8);
                  const float x0 = fmaxf(a0.x, b0.x), x1 = fmaxf(a1.x, b1.x);
                  const float fa0 = ex2(a0.x - x0), fa1 = ex2(a1.x - x1), fb0 = ex2(b0.x - x0), fb1 = ex2(b1.x - x1);
                  __syncwarp();
                  if (t == 0) { ma[0] = make_float2(x0, a0.y * fa0 + b0.y * fb0); ma[8] = make_float2(x1, a1.y * fa1 + b1.y * fb1); }
                  const uint32_t ofs = ((b >> 2) * 2048 + (b & 3) * 32 + lane) * 16;
        #pragma unroll 1
                  for (int u = 0; u < 16; u += 4) {
                    uint4* pa = pofs<uint4>(g_part, W.slotA * 65536 + ofs + u * 2048);
                    const uint4* pb = pofs<const uint4>(g_part, W.slotB * 65536 + ofs + u * 2048);
                    uint4 va[4], vb[4];
        #pragma unroll
                    for (int k = 0; k < 4; k++) { va[k] = ldcg_v(pa + k * 128); vb[k] = (HINT & 2 ? ldcs_v : ldcg_v)(pb + k * 128); }
        #define FOLD(w, fa, fb) pack_bf16(bf_lo(va[k].w) * fa + bf_lo(vb[k].w) * fb, bf_hi(va[k].w) * fa + bf_hi(vb[k].w) * fb)
        #pragma unroll
                    for (int k = 3; k >= 0; k--) pa[k * 128] = make_uint4(FOLD(x, fa0, fb0), FOLD(y, fa1, fb1), FOLD(z, fa0, fb0), FOLD(w, fa1, fb1));
                  }
                }
                bar_sync(3, 96);
                if (warp == 1) asm volatile("fence.acq_rel.gpu;" ::: "memory");
              }
              if (fin && warp == 1 && lane == 0) mbar_arrive(sb + B_BG);
              while (__any_sync(0xffffffffu, clk() - c0 < GPAUSE)) __nanosleep(500);
              continue;
            }
          }
#define SUM8(f) (v[7].f + v[6].f + v[5].f + v[4].f + v[3].f + v[2].f + v[1].f + v[0].f)
          add(SUM8(x), SUM8(y), SUM8(z), SUM8(w));
          e += 8;
          if (e < cb) {
            ent = __shfl_down_sync(0xffffffffu, ent, 8);
            if (e == 32) ent = __ldcg(pofs<const uint32_t>(g_bin, obin + 128 + lx / 4));
            continue;
          }
          rnd++; rows = cb; cdo = cd;
          if ((cd & 0xffff) > CAP) {
            const int no = __shfl_sync(0xffffffffu, (int)ld_relaxed(ovf_cnt), 0);
#pragma unroll 1
            for (int i0 = 0; i0 < no; i0 += 32) {
              int2 en = __ldcg(g_ovf + min(i0 + lane, no - 1));
              uint32_t mk = __ballot_sync(0xffffffffu, en.x == gw + rnd * NGW && i0 + lane < no);
              rows += __popc(mk);
#pragma unroll 1
              while (mk) {
                const int bit = __ffs(mk) - 1; mk &= mk - 1;
                const uint4 r = ldcg_v(addr64((uint32_t)__shfl_sync(0xffffffffu, en.y, bit) + lx, uhi));
                add(r.x, r.y, r.z, r.w);
              }
            }
          }
          obin += NGW * CAPS * 4;
          ent = entn; entn = __ldcg(pofs<const uint32_t>(g_bin, obin + NGW * CAPS * 4 + lx / 4));
          cd = __shfl_sync(0xffffffffu, cnts, rnd + 1); cb = min(cd & 0xffff, CAP); e = 0;
        }
      }
      STAMP(lane == 0 && warp == 1, 2, 11);
      if ((HINT & 4) && warp == 2 && fin && lane == 0) {
        prefetch_l2(pofs<uint8_t>(P.out, W.q0 * 65536), tail ? 8192 : 65536);
        if (W.slotB >= 0) prefetch_l2(pofs<uint8_t>(g_part, W.slotA * 65536), 65536);
        prefetch_l2(pofs<uint8_t>(g_Wvo, (cta & 63) * 4096), 4096);
      }
      DUMP(warp == 1 && lane == 0, 2, 8, 14);
    }
}

}

extern "C" void kernel_launch(void* const* d_in, const int* in_sizes, int n_in, void* d_out, int out_size) {
  Params P;
  P.x = (const __nv_bfloat16*)d_in[0];
  P.src = (const int*)d_in[1];
  P.dst = (const int*)d_in[2];
  P.dinv = (const __nv_bfloat16*)d_in[3];
  P.wmsg = (const __nv_bfloat16*)d_in[4];
  P.wq = (const __nv_bfloat16*)d_in[5];
  P.wk = (const __nv_bfloat16*)d_in[6];
  P.wv = (const __nv_bfloat16*)d_in[7];
  P.wout = (const __nv_bfloat16*)d_in[8];
  P.out = (__nv_bfloat16*)d_out;
  P.zero = 0;
  for (int c = 0; c < NCTA; c++) P.w[c] = make_work(c);
  static void* scr = nullptr;
  if (!scr) {
    cudaFuncSetAttribute(gps_kernel, cudaFuncAttributeMaxDynamicSharedMemorySize, SMEM_BYTES);
    cudaGetSymbolAddress(&scr, g_scr);
  }
  P.s = (Scratch*)((((uintptr_t)scr + SCR_ALIGN - 1) & ~(uintptr_t)(SCR_ALIGN - 1)) + SCR_OFS);
  P.u = (uint4*)(((uintptr_t)P.s->u + 511) & ~(uintptr_t)511);
  if (((uintptr_t)P.u >> 32) != (((uintptr_t)(P.u + NN * 32) - 1) >> 32)) P.u += NN * 32;
  gps_kernel<<<NCTA, 384, SMEM_BYTES>>>(P);
}
```

```cpp
#include <cuda_runtime.h>
#include <cuda_bf16.h>
#include <stdint.h>
#include <stddef.h>
#include <type_traits>
#define FB 5
#define MB 5
#define GSTART 18000
#define HINT 7
#define RELF 0
#define DBG 0
#define OUTW red_bf16x8
#define XD 2
#define PACE 64
#define GPAUSE 120000
#define XDELAY 200
#define CREG 224
#define BACKOFF 1000

namespace {

constexpr int NN = 10000;
constexpr int NE = 160000;
constexpr int NQT = 79;
constexpr int NCTA = 132;
constexpr int CAP = 64;
constexpr int CAPS = 64;
constexpr int NHSIG = 105;
constexpr uint32_t WCH_B = 32768;
constexpr int NGW = (NCTA - 1) * 3;
constexpr float TAU = 16.0f;
constexpr float SAFE_N2 = 36.0f, SAFE_C = 0.6f;
#define KOFF 3
#define PSH -8.0f
#define KROT 15
constexpr float US = 256.0f, UB = 4095.0f;
constexpr float KS = 0.25f, KC = KOFF * KS;
constexpr uint32_t KS2 = 0x3e803e80u, KC2 = KOFF == 2 ? 0x3f003f00u : (KOFF == 1 ? 0x3e803e80u : 0x3f403f40u);

constexpr int NAGG = 4;
constexpr int NRND = (NN + NGW - 1) / NGW;
constexpr int NSLOT = 105;
constexpr int F_EPOCH = 0, F_H = 1, F_M = 4  , LN_ = 32;
constexpr int F_BIN = LN_, F_W = 2 * LN_, F_OVF = 3 * LN_  , F_QP = 5 * LN_, F_AGG = F_QP + NQT * LN_,
              F_PART = F_AGG + NAGG * LN_, F_END = F_PART + NSLOT * LN_;

struct Scratch {
  uint32_t flag[F_END];
  alignas(4096) uint4 M[8192];
  uint4 Wvo[8192], Wmo[8192];
  float2 ml[NSLOT * 128];
  uint32_t unsafe[96];
  int cnt[NN + 32];
  float2 stat[NQT * 128];
  alignas(4096) uint4 h[NQT * 4096];
  uint4 u[2 * NN * 32 + 32];
  uint4 qp[NQT * 4096];
  uint4 agg[NQT * 4096];
  uint4 part[NSLOT * 4096];
  int bin[(NRND + 2) * NGW * CAPS];
  int2 ovf[NE];
};
static_assert(offsetof(Scratch, h) % 128 == 0, "alignment");
#define SCR_ALIGN (2u << 20)
#define SCR_OFS 0
__device__ uint4 g_scr[(sizeof(Scratch) + SCR_ALIGN + SCR_OFS) / 16];
struct alignas(16) Work { short k0, k1; signed char q0, q1, nb0, na0, nb1, na1, slotA, slotB, loc0, nloc, own, role; };
constexpr int R_FIN = 1, R_PUB = 2, R_TAIL = 4;
struct Params {
  const __nv_bfloat16 *x, *wq, *wk;
  Scratch* s;
  uint4* u;
  __nv_bfloat16* out;
  const __nv_bfloat16 *wout, *wmsg, *wv, *dinv;
  const int *src, *dst;
  long long zero;
  Work w[NCTA];
};
constexpr int NSERV = NQT - 52;
inline Work make_work(int c) {
  Work w;
  const int gi = c / 5, r = c % 5, q = gi * 3;
  const bool helper = r & 1, mid = r == 2;
  w.q0 = helper ? q + 1 : q + (r >> 1);
  const int hb1 = (15 - MB) / 2, hb3 = 15 - MB - hb1;
  w.nb0 = helper ? (r == 1 ? hb1 : hb3) : (mid ? MB : FB);
  w.na0 = (helper ? 16 : 48) - w.nb0;
  w.k0 = helper ? (48 * 8 - MB) + (r >> 1) * (16 * 8 - hb1) : 0;
  w.q1 = q + (r & 2);
  w.k1 = 48 * 8 - FB;
  w.nb1 = helper ? (FB < 7 ? 7 : 15) - FB : 0;
  w.na1 = helper ? (FB < 7 ? 31 : 32) - w.nb1 : 0;
  w.slotA = 4 * gi + (helper ? r - 1 : (mid ? 0 : (r >> 1) + 1));
  w.slotB = helper ? 4 * gi + r : (mid ? 4 * gi + 2 : -1);
  w.loc0 = NSERV + gi * 2 + (r >> 1);
  w.nloc = helper;
  w.own = helper ? (r + 1) >> 1 : (mid ? 0 : 3);
  w.role = helper ? 0 : (mid ? R_FIN : R_FIN | R_PUB);
  if (c == 130) { w.nb0 = 15; w.na0 = 65; w.slotA = NSLOT - 1; w.own = 1; w.role = R_FIN | R_TAIL; }
  if (c == 131) { w.nb0 = w.na0 = w.nb1 = w.na1 = 0; w.loc0 = 0; w.nloc = NSERV; w.own = 0; }
  return w;
}
#define g_flag P.s->flag
#define g_M P.s->M
#define g_Wvo P.s->Wvo
#define g_Wmo P.s->Wmo
#define g_ml P.s->ml
#define g_unsafe P.s->unsafe
#define g_cnt P.s->cnt
#define g_h P.s->h
#define g_u P.u
#define g_stat P.s->stat
#define g_qp P.s->qp
#define g_agg P.s->agg
#define g_part P.s->part
#define g_bin P.s->bin
#define g_ovf P.s->ovf

__device__ __forceinline__ uint32_t smem_u32(const void* p) { return (uint32_t)__cvta_generic_to_shared(p); }
__device__ __forceinline__ void mbar_init(uint32_t bar, uint32_t cnt) { asm volatile("mbarrier.init.shared::cta.b64 [%0], %1;" :: "r"(bar), "r"(cnt) : "memory"); }
__device__ __forceinline__ void mbar_arrive(uint32_t bar) { asm volatile("mbarrier.arrive.shared::cta.b64 _, [%0];" :: "r"(bar) : "memory"); }
__device__ __forceinline__ void mbar_expect_tx(uint32_t bar, uint32_t bytes) { asm volatile("mbarrier.arrive.expect_tx.shared::cta.b64 _, [%0], %1;" :: "r"(bar), "r"(bytes) : "memory"); }
__device__ __forceinline__ bool mbar_try_wait(uint32_t bar, uint32_t parity) {
  uint32_t ok;
  asm volatile("{\n.reg .pred p;\nmbarrier.try_wait.parity.shared::cta.b64 p, [%1], %2;\nselp.b32 %0, 1, 0, p;\n}\n" : "=r"(ok) : "r"(bar), "r"(parity) : "memory");
  return ok;
}
__device__ __forceinline__ bool mbar_try_wait_nb(uint32_t bar, uint32_t parity) {
  uint32_t ok;
  asm volatile("{\n.reg .pred p;\nmbarrier.test_wait.parity.shared::cta.b64 p, [%1], %2;\nselp.b32 %0, 1, 0, p;\n}\n" : "=r"(ok) : "r"(bar), "r"(parity) : "memory");
  return ok;
}
__device__ __forceinline__ void mbar_wait(uint32_t bar, uint32_t parity) {
#pragma unroll 1
  for (uint32_t it = 0; it < (1u << 25); it++) if (mbar_try_wait(bar, parity)) break;
}
__device__ __forceinline__ void bulk_s2g(void* dst, uint32_t src, uint32_t bytes) {
  asm volatile("cp.async.bulk.global.shared::cta.bulk_group [%0], [%1], %2;" :: "l"(dst), "r"(src), "r"(bytes) : "memory");
}
__device__ __forceinline__ void bulk_commit() { asm volatile("cp.async.bulk.commit_group;" ::: "memory"); }
__device__ __forceinline__ void bulk_wait_read() { asm volatile("cp.async.bulk.wait_group.read 0;" ::: "memory"); }
__device__ __forceinline__ void bulk_wait_all() { asm volatile("cp.async.bulk.wait_group 0;" ::: "memory"); }
__device__ __forceinline__ bool bar_red_or(int id, int cnt, bool c) {
  uint32_t r;
  asm volatile("{\n.reg .pred p, q;\nsetp.ne.b32 q, %3, 0;\nbar.red.or.pred p, %1, %2, q;\nselp.b32 %0, 1, 0, p;\n}\n"
               : "=r"(r) : "r"(id), "r"(cnt), "r"((uint32_t)c) : "memory");
  return r != 0;
}
template <class T> __device__ __forceinline__ T* pofs(const void* base, uint32_t off) {
  asm volatile("" : "+r"(off));
  return (T*)((uint8_t*)base + off);
}
__device__ __forceinline__ const void* addr64(uint32_t lo, uint32_t hi) { uint64_t a; asm("mov.b64 %0, {%1, %2};" : "=l"(a) : "r"(lo), "r"(hi)); return (const void*)a; }
__device__ __forceinline__ uint4 ldcg_v(const void* a) {
  uint4 v;
  asm volatile("ld.volatile.global.v4.u32 {%0,%1,%2,%3}, [%4];" : "=r"(v.x), "=r"(v.y), "=r"(v.z), "=r"(v.w) : "l"(a) : "memory");
  return v;
}
__device__ __forceinline__ uint4 ldcs_v(const void* a) {
  uint4 v;
  asm volatile("ld.global.cs.v4.u32 {%0,%1,%2,%3}, [%4];" : "=r"(v.x), "=r"(v.y), "=r"(v.z), "=r"(v.w) : "l"(a) : "memory");
  return v;
}
__device__ __forceinline__ void prefetch_l2(const void* a, uint32_t bytes) { asm volatile("cp.async.bulk.prefetch.L2.global [%0], %1;" :: "l"(a), "r"(bytes) : "memory"); }
__device__ __forceinline__ void ldcg_if(uint4& v, const void* a, bool c) {
  asm volatile("{\n.reg .pred p;\nsetp.ne.b32 p, %5, 0;\n@p ld.volatile.global.v4.u32 {%0,%1,%2,%3}, [%4];\n}\n"
               : "+r"(v.x), "+r"(v.y), "+r"(v.z), "+r"(v.w) : "l"(a), "r"((uint32_t)c) : "memory");
}
__device__ __forceinline__ void cp_async16(uint32_t dst, const void* src) {
  asm volatile("cp.async.cg.shared.global [%0], [%1], 16;" :: "r"(dst), "l"(src) : "memory");
}
__device__ __forceinline__ void red_bf16x8(void* a, uint4 v) {
  asm volatile("red.global.add.noftz.v4.bf16x2 [%0], {%1,%2,%3,%4};" :: "l"(a), "r"(v.x), "r"(v.y), "r"(v.z), "r"(v.w) : "memory");
}
__device__ __forceinline__ uint32_t clk() { uint32_t c; asm volatile("mov.u32 %0, %%clock;" : "=r"(c) :: "memory"); return c; }
__device__ __forceinline__ void stsm4(uint32_t a, uint32_t r0, uint32_t r1, uint32_t r2, uint32_t r3) {
  asm volatile("stmatrix.sync.aligned.m8n8.x4.shared.b16 [%0], {%1,%2,%3,%4};" :: "r"(a), "r"(r0), "r"(r1), "r"(r2), "r"(r3) : "memory");
}
__device__ __forceinline__ void ldsm4(uint32_t a, uint32_t& r0, uint32_t& r1, uint32_t& r2, uint32_t& r3) {
  asm volatile("ldmatrix.sync.aligned.m8n8.x4.shared.b16 {%0,%1,%2,%3}, [%4];" : "=r"(r0), "=r"(r1), "=r"(r2), "=r"(r3) : "r"(a) : "memory");
}
__device__ __forceinline__ void red_relaxed(uint32_t* p) { asm volatile("red.relaxed.gpu.global.add.u32 [%0], 1;" :: "l"(p) : "memory"); }
__device__ __forceinline__ uint32_t lds32(uint32_t a) { uint32_t v; asm volatile("ld.shared.u32 %0, [%1];" : "=r"(v) : "r"(a) : "memory"); return v; }
__device__ __forceinline__ void cp_commit() { asm volatile("cp.async.commit_group;" ::: "memory"); }
__device__ __forceinline__ uint32_t hmul2(uint32_t a, uint32_t b) { uint32_t d; asm("mul.rn.bf16x2 %0, %1, %2;" : "=r"(d) : "r"(a), "r"(b)); return d; }
__device__ __forceinline__ uint32_t hfma2(uint32_t a, uint32_t b, uint32_t c) { uint32_t d; asm("fma.rn.bf16x2 %0, %1, %2, %3;" : "=r"(d) : "r"(a), "r"(b), "r"(c)); return d; }
__device__ __forceinline__ uint32_t pow2_bf2(int n) { return (uint32_t)max(n + 127, 0) * 0x00800080u; }
__device__ __forceinline__ int fexp(float x) { return (int)(__float_as_uint(x) >> 23) - 127; }
__device__ __forceinline__ void bulk_g2s(uint32_t dst, const void* src, uint32_t bytes, uint32_t bar) {
  asm volatile("cp.async.bulk.shared::cta.global.mbarrier::complete_tx::bytes [%0], [%1], %2, [%3];"
    :: "r"(dst), "l"(src), "r"(bytes), "r"(bar) : "memory");
}
__device__ __forceinline__ void bulk_g2s_last(uint32_t dst, const void* src, uint32_t bytes, uint32_t bar) {
  asm volatile("{\n.reg .b64 p;\ncreatepolicy.fractional.L2::evict_first.b64 p;\n"
    "cp.async.bulk.shared::cta.global.mbarrier::complete_tx::bytes.L2::cache_hint [%0], [%1], %2, [%3], p;\n}\n"
    :: "r"(dst), "l"(src), "r"(bytes), "r"(bar) : "memory");
}
__device__ __forceinline__ void wg_fence() { asm volatile("wgmma.fence.sync.aligned;" ::: "memory"); }
__device__ __forceinline__ void wg_commit() { asm volatile("wgmma.commit_group.sync.aligned;" ::: "memory"); }
template<int N> __device__ __forceinline__ void wg_wait() { asm volatile("wgmma.wait_group.sync.aligned %0;" :: "n"(N) : "memory"); }
__device__ __forceinline__ void bar_sync(int id, int cnt) { asm volatile("bar.sync %0, %1;" :: "r"(id), "r"(cnt) : "memory"); }
__device__ __forceinline__ void fence_async_smem() { asm volatile("fence.proxy.async.shared::cta;" ::: "memory"); }
__device__ __forceinline__ void fence_async_gmem() { asm volatile("fence.proxy.async.global;" ::: "memory"); }
__device__ __forceinline__ void bar_arrive(int id, int cnt) { asm volatile("bar.arrive %0, %1;" :: "r"(id), "r"(cnt) : "memory"); }
__device__ __forceinline__ void red_release(uint32_t* p) { asm volatile("red.release.gpu.global.add.u32 [%0], 1;" :: "l"(p) : "memory"); }
__device__ __forceinline__ void red_release_w(uint32_t* p) {
  __syncwarp();
  asm volatile("{\n.reg .pred q;\n.reg .b32 l;\nmov.u32 l, %%laneid;\nsetp.eq.u32 q, l, 0;\n@q fence.release.gpu;\n@q red.relaxed.gpu.global.add.u32 [%0], 1;\n}\n" :: "l"(p) : "memory");
}
__device__ __forceinline__ void mbar_wait_w(uint32_t bar, uint32_t parity) {
#pragma unroll 1
  for (uint32_t it = 0; it < (1u << 25); it++) if (__all_sync(0xffffffffu, mbar_try_wait(bar, parity))) break;
}
#define flag_release_w(f) red_release_w(g_flag + (f))
#define flag_wait_w(f, target) poll_acquire_w(g_flag + (f), target)
#define flag_release(f) red_release(g_flag + (f))
__device__ __forceinline__ uint32_t ld_relaxed(const uint32_t* p) {
  uint32_t v; asm volatile("ld.relaxed.gpu.global.u32 %0, [%1];" : "=r"(v) : "l"(p) : "memory"); return v;
}
#define flag_wait(f, target) poll_acquire(g_flag + (f), target)
__device__ __forceinline__ void poll_acquire(const uint32_t* p, uint32_t target) {
#pragma unroll 1
  for (uint32_t it = 0; it < (1u << 23); it++) if ((int)(ld_relaxed(p) - target) >= 0) break;
  asm volatile("fence.acquire.gpu;" ::: "memory");
}
__device__ __forceinline__ void poll_acquire_w(const uint32_t* p, uint32_t target) {
#pragma unroll 1
  for (uint32_t it = 0; it < (1u << 23); it++) {
    if (__all_sync(0xffffffffu, (int)(ld_relaxed(p) - target) >= 0)) break;
    if (BACKOFF) __nanosleep(BACKOFF);
  }
  asm volatile("fence.acquire.gpu;" ::: "memory");
}
template<int N> __device__ __forceinline__ void reg_fence(float (&d)[N]) {
#pragma unroll
  for (int i = 0; i < N; i++) asm volatile("" : "+f"(d[i]) :: "memory");
}
template<int N> __device__ __forceinline__ void reg_fence(uint32_t (&d)[N]) {
#pragma unroll
  for (int i = 0; i < N; i++) asm volatile("" : "+r"(d[i]) :: "memory");
}
__device__ __forceinline__ float ex2(float x) { float y; asm("ex2.approx.ftz.f32 %0, %1;" : "=f"(y) : "f"(x)); return y; }
__device__ __forceinline__ uint32_t pack_bf16(float lo, float hi) { uint32_t r; asm("cvt.rn.bf16x2.f32 %0, %1, %2;" : "=r"(r) : "f"(hi), "f"(lo)); return r; }
__device__ __forceinline__ float bf_lo(uint32_t w) { return __uint_as_float(w << 16); }
__device__ __forceinline__ float bf_hi(uint32_t w) { return __uint_as_float(w & 0xffff0000u); }
__device__ __forceinline__ uint64_t desc_k(uint32_t addr, uint32_t add) { return (uint64_t)((((addr & 0x3FFFF) >> 4) | (1u << 16)) + add) | (0x40000100ull << 32); }
__device__ __forceinline__ uint64_t desc_mn(uint32_t addr, uint32_t add) { return (uint64_t)((((addr & 0x3FFFF) >> 4) | ((1024u >> 4) << 16)) + add) | (0x40000100ull << 32); }
__device__ __forceinline__ void sts128(uint32_t a, uint4 v) { asm volatile("st.shared.v4.u32 [%0], {%1,%2,%3,%4};" :: "r"(a), "r"(v.x), "r"(v.y), "r"(v.z), "r"(v.w) : "memory"); }
__device__ __forceinline__ uint4 lds128(uint32_t a) { uint4 v; asm volatile("ld.shared.v4.u32 {%0,%1,%2,%3}, [%4];" : "=r"(v.x), "=r"(v.y), "=r"(v.z), "=r"(v.w) : "r"(a) : "memory"); return v; }
__device__ __forceinline__ void mma16816(float (&c)[4], uint32_t a0, uint32_t a1, uint32_t a2, uint32_t a3, uint32_t b0, uint32_t b1) {
  asm volatile("mma.sync.aligned.m16n8k16.row.col.f32.bf16.bf16.f32 {%0,%1,%2,%3}, {%4,%5,%6,%7}, {%8,%9}, {%0,%1,%2,%3};"
    : "+f"(c[0]), "+f"(c[1]), "+f"(c[2]), "+f"(c[3]) : "r"(a0), "r"(a1), "r"(a2), "r"(a3), "r"(b0), "r"(b1));
}
__device__ __forceinline__ uint32_t sw_byte(int r, int c) {
  return (uint32_t)((r >> 3) * 4096 + (c >> 6) * 1024 + (r & 7) * 128 + ((((c >> 3) & 7) ^ (r & 7)) << 4) + (c & 7) * 2);
}
__device__ __forceinline__ int cta_id() { int c; asm volatile("mov.u32 %0, %%ctaid.x;" : "=r"(c)); return c; }
__device__ __forceinline__ bool tid_is(int v) { int t; asm volatile("mov.u32 %0, %%tid.x;" : "=r"(t)); return t == v; }
#define STAMP(cond, who, i)
#define CSTAMP(cond, who, i)
#define DUMP(cond, who, i0, i1)
#define XSTAMP(cond, i)
#define SSTAMP(i)

template <int OA, int OB> __device__ __forceinline__ void wgmma_ss_n256_tb(float (&d)[128], uint64_t da, uint64_t db, int scale_d) {
  asm volatile("{\n.reg .pred p;\n.reg .b64 a, b;\nsetp.ne.b32 p, %130, 0;\nadd.s64 a, %128, %131;\nadd.s64 b, %129, %132;\n"
    "wgmma.mma_async.sync.aligned.m64n256k16.f32.bf16.bf16 "
    "{%0, %1, %2, %3, %4, %5, %6, %7, %8, %9, %10, %11, %12, %13, %14, %15, %16, %17, %18, %19, %20, %21, %22, %23, %24, %25, %26, %27, %28, %29, %30, %31, %32, %33, %34, %35, %36, %37, %38, %39, %40, %41, %42, %43, %44, %45, %46, %47, %48, %49, %50, %51, %52, %53, %54, %55, %56, %57, %58, %59, %60, %61, %62, %63, %64, %65, %66, %67, %68, %69, %70, %71, %72, %73, %74, %75, %76, %77, %78, %79, %80, %81, %82, %83, %84, %85, %86, %87, %88, %89, %90, %91, %92, %93, %94, %95, %96, %97, %98, %99, %100, %101, %102, %103, %104, %105, %106, %107, %108, %109, %110, %111, %112, %113, %114, %115, %116, %117, %118, %119, %120, %121, %122, %123, %124, %125, %126, %127}, "
    "a, b, p, 1, 1, 0, 1;\n}\n"
    : "+f"(d[0]), "+f"(d[1]), "+f"(d[2]), "+f"(d[3]), "+f"(d[4]), "+f"(d[5]), "+f"(d[6]), "+f"(d[7]), "+f"(d[8]), "+f"(d[9]), "+f"(d[10]), "+f"(d[11]), "+f"(d[12]), "+f"(d[13]), "+f"(d[14]), "+f"(d[15]), "+f"(d[16]), "+f"(d[17]), "+f"(d[18]), "+f"(d[19]), "+f"(d[20]), "+f"(d[21]), "+f"(d[22]), "+f"(d[23]), "+f"(d[24]), "+f"(d[25]), "+f"(d[26]), "+f"(d[27]), "+f"(d[28]), "+f"(d[29]), "+f"(d[30]), "+f"(d[31]), "+f"(d[32]), "+f"(d[33]), "+f"(d[34]), "+f"(d[35]), "+f"(d[36]), "+f"(d[37]), "+f"(d[38]), "+f"(d[39]), "+f"(d[40]), "+f"(d[41]), "+f"(d[42]), "+f"(d[43]), "+f"(d[44]), "+f"(d[45]), "+f"(d[46]), "+f"(d[47]), "+f"(d[48]), "+f"(d[49]), "+f"(d[50]), "+f"(d[51]), "+f"(d[52]), "+f"(d[53]), "+f"(d[54]), "+f"(d[55]), "+f"(d[56]), "+f"(d[57]), "+f"(d[58]), "+f"(d[59]), "+f"(d[60]), "+f"(d[61]), "+f"(d[62]), "+f"(d[63]), "+f"(d[64]), "+f"(d[65]), "+f"(d[66]), "+f"(d[67]), "+f"(d[68]), "+f"(d[69]), "+f"(d[70]), "+f"(d[71]), "+f"(d[72]), "+f"(d[73]), "+f"(d[74]), "+f"(d[75]), "+f"(d[76]), "+f"(d[77]), "+f"(d[78]), "+f"(d[79]), "+f"(d[80]), "+f"(d[81]), "+f"(d[82]), "+f"(d[83]), "+f"(d[84]), "+f"(d[85]), "+f"(d[86]), "+f"(d[87]), "+f"(d[88]), "+f"(d[89]), "+f"(d[90]), "+f"(d[91]), "+f"(d[92]), "+f"(d[93]), "+f"(d[94]), "+f"(d[95]), "+f"(d[96]), "+f"(d[97]), "+f"(d[98]), "+f"(d[99]), "+f"(d[100]), "+f"(d[101]), "+f"(d[102]), "+f"(d[103]), "+f"(d[104]), "+f"(d[105]), "+f"(d[106]), "+f"(d[107]), "+f"(d[108]), "+f"(d[109]), "+f"(d[110]), "+f"(d[111]), "+f"(d[112]), "+f"(d[113]), "+f"(d[114]), "+f"(d[115]), "+f"(d[116]), "+f"(d[117]), "+f"(d[118]), "+f"(d[119]), "+f"(d[120]), "+f"(d[121]), "+f"(d[122]), "+f"(d[123]), "+f"(d[124]), "+f"(d[125]), "+f"(d[126]), "+f"(d[127])
    : "l"(da), "l"(db), "r"(scale_d), "n"(OA), "n"(OB));
}
template <int OA, int OB> __device__ __forceinline__ void wgmma_qk(float (&d)[64], uint64_t da, uint64_t db, int scale_d) {
  asm volatile("{\n.reg .pred p;\n.reg .b64 a, b;\nsetp.ne.b32 p, %66, 0;\nadd.s64 a, %64, %67;\nadd.s64 b, %65, %68;\n"
    "wgmma.mma_async.sync.aligned.m64n128k16.f32.bf16.bf16 "
    "{%0, %1, %2, %3, %4, %5, %6, %7, %8, %9, %10, %11, %12, %13, %14, %15, %16, %17, %18, %19, %20, %21, %22, %23, %24, %25, %26, %27, %28, %29, %30, %31, %32, %33, %34, %35, %36, %37, %38, %39, %40, %41, %42, %43, %44, %45, %46, %47, %48, %49, %50, %51, %52, %53, %54, %55, %56, %57, %58, %59, %60, %61, %62, %63}, "
    "a, b, p, 1, 1, 0, 0;\n}\n"
    : "+f"(d[0]), "+f"(d[1]), "+f"(d[2]), "+f"(d[3]), "+f"(d[4]), "+f"(d[5]), "+f"(d[6]), "+f"(d[7]), "+f"(d[8]), "+f"(d[9]), "+f"(d[10]), "+f"(d[11]), "+f"(d[12]), "+f"(d[13]), "+f"(d[14]), "+f"(d[15]), "+f"(d[16]), "+f"(d[17]), "+f"(d[18]), "+f"(d[19]), "+f"(d[20]), "+f"(d[21]), "+f"(d[22]), "+f"(d[23]), "+f"(d[24]), "+f"(d[25]), "+f"(d[26]), "+f"(d[27]), "+f"(d[28]), "+f"(d[29]), "+f"(d[30]), "+f"(d[31]), "+f"(d[32]), "+f"(d[33]), "+f"(d[34]), "+f"(d[35]), "+f"(d[36]), "+f"(d[37]), "+f"(d[38]), "+f"(d[39]), "+f"(d[40]), "+f"(d[41]), "+f"(d[42]), "+f"(d[43]), "+f"(d[44]), "+f"(d[45]), "+f"(d[46]), "+f"(d[47]), "+f"(d[48]), "+f"(d[49]), "+f"(d[50]), "+f"(d[51]), "+f"(d[52]), "+f"(d[53]), "+f"(d[54]), "+f"(d[55]), "+f"(d[56]), "+f"(d[57]), "+f"(d[58]), "+f"(d[59]), "+f"(d[60]), "+f"(d[61]), "+f"(d[62]), "+f"(d[63])
    : "l"(da), "l"(db), "r"(scale_d), "n"(OA), "n"(OB));
}
template <int OA, int OB> __device__ __forceinline__ void wgmma_qk(float (&d)[56], uint64_t da, uint64_t db, int scale_d) {
  asm volatile("{\n.reg .pred p;\n.reg .b64 a, b;\nsetp.ne.b32 p, %58, 0;\nadd.s64 a, %56, %59;\nadd.s64 b, %57, %60;\n"
    "wgmma.mma_async.sync.aligned.m64n112k16.f32.bf16.bf16 "
    "{%0, %1, %2, %3, %4, %5, %6, %7, %8, %9, %10, %11, %12, %13, %14, %15, %16, %17, %18, %19, %20, %21, %22, %23, %24, %25, %26, %27, %28, %29, %30, %31, %32, %33, %34, %35, %36, %37, %38, %39, %40, %41, %42, %43, %44, %45, %46, %47, %48, %49, %50, %51, %52, %53, %54, %55}, "
    "a, b, p, 1, 1, 0, 0;\n}\n"
    : "+f"(d[0]), "+f"(d[1]), "+f"(d[2]), "+f"(d[3]), "+f"(d[4]), "+f"(d[5]), "+f"(d[6]), "+f"(d[7]), "+f"(d[8]), "+f"(d[9]), "+f"(d[10]), "+f"(d[11]), "+f"(d[12]), "+f"(d[13]), "+f"(d[14]), "+f"(d[15]), "+f"(d[16]), "+f"(d[17]), "+f"(d[18]), "+f"(d[19]), "+f"(d[20]), "+f"(d[21]), "+f"(d[22]), "+f"(d[23]), "+f"(d[24]), "+f"(d[25]), "+f"(d[26]), "+f"(d[27]), "+f"(d[28]), "+f"(d[29]), "+f"(d[30]), "+f"(d[31]), "+f"(d[32]), "+f"(d[33]), "+f"(d[34]), "+f"(d[35]), "+f"(d[36]), "+f"(d[37]), "+f"(d[38]), "+f"(d[39]), "+f"(d[40]), "+f"(d[41]), "+f"(d[42]), "+f"(d[43]), "+f"(d[44]), "+f"(d[45]), "+f"(d[46]), "+f"(d[47]), "+f"(d[48]), "+f"(d[49]), "+f"(d[50]), "+f"(d[51]), "+f"(d[52]), "+f"(d[53]), "+f"(d[54]), "+f"(d[55])
    : "l"(da), "l"(db), "r"(scale_d), "n"(OA), "n"(OB));
}
template <int OB> __device__ __forceinline__ void wgmma_rs_n256_tb(float (&d)[128], uint32_t a0, uint32_t a1, uint32_t a2, uint32_t a3, uint64_t db, int scale_d) {
  asm volatile("{\n.reg .pred p;\n.reg .b64 b;\nsetp.ne.b32 p, %133, 0;\nadd.s64 b, %132, %134;\n"
    "wgmma.mma_async.sync.aligned.m64n256k16.f32.bf16.bf16 "
    "{%0, %1, %2, %3, %4, %5, %6, %7, %8, %9, %10, %11, %12, %13, %14, %15, %16, %17, %18, %19, %20, %21, %22, %23, %24, %25, %26, %27, %28, %29, %30, %31, %32, %33, %34, %35, %36, %37, %38, %39, %40, %41, %42, %43, %44, %45, %46, %47, %48, %49, %50, %51, %52, %53, %54, %55, %56, %57, %58, %59, %60, %61, %62, %63, %64, %65, %66, %67, %68, %69, %70, %71, %72, %73, %74, %75, %76, %77, %78, %79, %80, %81, %82, %83, %84, %85, %86, %87, %88, %89, %90, %91, %92, %93, %94, %95, %96, %97, %98, %99, %100, %101, %102, %103, %104, %105, %106, %107, %108, %109, %110, %111, %112, %113, %114, %115, %116, %117, %118, %119, %120, %121, %122, %123, %124, %125, %126, %127}, "
    "{%128, %129, %130, %131}, b, p, 1, 1, 1;\n}\n"
    : "+f"(d[0]), "+f"(d[1]), "+f"(d[2]), "+f"(d[3]), "+f"(d[4]), "+f"(d[5]), "+f"(d[6]), "+f"(d[7]), "+f"(d[8]), "+f"(d[9]), "+f"(d[10]), "+f"(d[11]), "+f"(d[12]), "+f"(d[13]), "+f"(d[14]), "+f"(d[15]), "+f"(d[16]), "+f"(d[17]), "+f"(d[18]), "+f"(d[19]), "+f"(d[20]), "+f"(d[21]), "+f"(d[22]), "+f"(d[23]), "+f"(d[24]), "+f"(d[25]), "+f"(d[26]), "+f"(d[27]), "+f"(d[28]), "+f"(d[29]), "+f"(d[30]), "+f"(d[31]), "+f"(d[32]), "+f"(d[33]), "+f"(d[34]), "+f"(d[35]), "+f"(d[36]), "+f"(d[37]), "+f"(d[38]), "+f"(d[39]), "+f"(d[40]), "+f"(d[41]), "+f"(d[42]), "+f"(d[43]), "+f"(d[44]), "+f"(d[45]), "+f"(d[46]), "+f"(d[47]), "+f"(d[48]), "+f"(d[49]), "+f"(d[50]), "+f"(d[51]), "+f"(d[52]), "+f"(d[53]), "+f"(d[54]), "+f"(d[55]), "+f"(d[56]), "+f"(d[57]), "+f"(d[58]), "+f"(d[59]), "+f"(d[60]), "+f"(d[61]), "+f"(d[62]), "+f"(d[63]), "+f"(d[64]), "+f"(d[65]), "+f"(d[66]), "+f"(d[67]), "+f"(d[68]), "+f"(d[69]), "+f"(d[70]), "+f"(d[71]), "+f"(d[72]), "+f"(d[73]), "+f"(d[74]), "+f"(d[75]), "+f"(d[76]), "+f"(d[77]), "+f"(d[78]), "+f"(d[79]), "+f"(d[80]), "+f"(d[81]), "+f"(d[82]), "+f"(d[83]), "+f"(d[84]), "+f"(d[85]), "+f"(d[86]), "+f"(d[87]), "+f"(d[88]), "+f"(d[89]), "+f"(d[90]), "+f"(d[91]), "+f"(d[92]), "+f"(d[93]), "+f"(d[94]), "+f"(d[95]), "+f"(d[96]), "+f"(d[97]), "+f"(d[98]), "+f"(d[99]), "+f"(d[100]), "+f"(d[101]), "+f"(d[102]), "+f"(d[103]), "+f"(d[104]), "+f"(d[105]), "+f"(d[106]), "+f"(d[107]), "+f"(d[108]), "+f"(d[109]), "+f"(d[110]), "+f"(d[111]), "+f"(d[112]), "+f"(d[113]), "+f"(d[114]), "+f"(d[115]), "+f"(d[116]), "+f"(d[117]), "+f"(d[118]), "+f"(d[119]), "+f"(d[120]), "+f"(d[121]), "+f"(d[122]), "+f"(d[123]), "+f"(d[124]), "+f"(d[125]), "+f"(d[126]), "+f"(d[127])
    : "r"(a0), "r"(a1), "r"(a2), "r"(a3), "l"(db), "r"(scale_d), "n"(OB));
}
template <int OB> __device__ __forceinline__ void wgmma_rs_n256_tb_first(float (&d)[128], uint32_t a0, uint32_t a1, uint32_t a2, uint32_t a3, uint64_t db) {
  asm volatile("{\n.reg .pred p;\n.reg .b64 b;\nsetp.ne.b32 p, 0, 0;\nadd.s64 b, %132, %133;\n"
    "wgmma.mma_async.sync.aligned.m64n256k16.f32.bf16.bf16 "
    "{%0, %1, %2, %3, %4, %5, %6, %7, %8, %9, %10, %11, %12, %13, %14, %15, %16, %17, %18, %19, %20, %21, %22, %23, %24, %25, %26, %27, %28, %29, %30, %31, %32, %33, %34, %35, %36, %37, %38, %39, %40, %41, %42, %43, %44, %45, %46, %47, %48, %49, %50, %51, %52, %53, %54, %55, %56, %57, %58, %59, %60, %61, %62, %63, %64, %65, %66, %67, %68, %69, %70, %71, %72, %73, %74, %75, %76, %77, %78, %79, %80, %81, %82, %83, %84, %85, %86, %87, %88, %89, %90, %91, %92, %93, %94, %95, %96, %97, %98, %99, %100, %101, %102, %103, %104, %105, %106, %107, %108, %109, %110, %111, %112, %113, %114, %115, %116, %117, %118, %119, %120, %121, %122, %123, %124, %125, %126, %127}, "
    "{%128, %129, %130, %131}, b, p, 1, 1, 1;\n}\n"
    : "=f"(d[0]), "=f"(d[1]), "=f"(d[2]), "=f"(d[3]), "=f"(d[4]), "=f"(d[5]), "=f"(d[6]), "=f"(d[7]), "=f"(d[8]), "=f"(d[9]), "=f"(d[10]), "=f"(d[11]), "=f"(d[12]), "=f"(d[13]), "=f"(d[14]), "=f"(d[15]), "=f"(d[16]), "=f"(d[17]), "=f"(d[18]), "=f"(d[19]), "=f"(d[20]), "=f"(d[21]), "=f"(d[22]), "=f"(d[23]), "=f"(d[24]), "=f"(d[25]), "=f"(d[26]), "=f"(d[27]), "=f"(d[28]), "=f"(d[29]), "=f"(d[30]), "=f"(d[31]), "=f"(d[32]), "=f"(d[33]), "=f"(d[34]), "=f"(d[35]), "=f"(d[36]), "=f"(d[37]), "=f"(d[38]), "=f"(d[39]), "=f"(d[40]), "=f"(d[41]), "=f"(d[42]), "=f"(d[43]), "=f"(d[44]), "=f"(d[45]), "=f"(d[46]), "=f"(d[47]), "=f"(d[48]), "=f"(d[49]), "=f"(d[50]), "=f"(d[51]), "=f"(d[52]), "=f"(d[53]), "=f"(d[54]), "=f"(d[55]), "=f"(d[56]), "=f"(d[57]), "=f"(d[58]), "=f"(d[59]), "=f"(d[60]), "=f"(d[61]), "=f"(d[62]), "=f"(d[63]), "=f"(d[64]), "=f"(d[65]), "=f"(d[66]), "=f"(d[67]), "=f"(d[68]), "=f"(d[69]), "=f"(d[70]), "=f"(d[71]), "=f"(d[72]), "=f"(d[73]), "=f"(d[74]), "=f"(d[75]), "=f"(d[76]), "=f"(d[77]), "=f"(d[78]), "=f"(d[79]), "=f"(d[80]), "=f"(d[81]), "=f"(d[82]), "=f"(d[83]), "=f"(d[84]), "=f"(d[85]), "=f"(d[86]), "=f"(d[87]), "=f"(d[88]), "=f"(d[89]), "=f"(d[90]), "=f"(d[91]), "=f"(d[92]), "=f"(d[93]), "=f"(d[94]), "=f"(d[95]), "=f"(d[96]), "=f"(d[97]), "=f"(d[98]), "=f"(d[99]), "=f"(d[100]), "=f"(d[101]), "=f"(d[102]), "=f"(d[103]), "=f"(d[104]), "=f"(d[105]), "=f"(d[106]), "=f"(d[107]), "=f"(d[108]), "=f"(d[109]), "=f"(d[110]), "=f"(d[111]), "=f"(d[112]), "=f"(d[113]), "=f"(d[114]), "=f"(d[115]), "=f"(d[116]), "=f"(d[117]), "=f"(d[118]), "=f"(d[119]), "=f"(d[120]), "=f"(d[121]), "=f"(d[122]), "=f"(d[123]), "=f"(d[124]), "=f"(d[125]), "=f"(d[126]), "=f"(d[127])
    : "r"(a0), "r"(a1), "r"(a2), "r"(a3), "l"(db), "n"(OB));
}
template <int OB> __device__ __forceinline__ void wgmma_rs_n128_tb(float (&d)[64], uint32_t a0, uint32_t a1, uint32_t a2, uint32_t a3, uint64_t db, int scale_d) {
  asm volatile("{\n.reg .pred p;\n.reg .b64 b;\nsetp.ne.b32 p, %69, 0;\nadd.s64 b, %68, %70;\n"
    "wgmma.mma_async.sync.aligned.m64n128k16.f32.bf16.bf16 "
    "{%0, %1, %2, %3, %4, %5, %6, %7, %8, %9, %10, %11, %12, %13, %14, %15, %16, %17, %18, %19, %20, %21, %22, %23, %24, %25, %26, %27, %28, %29, %30, %31, %32, %33, %34, %35, %36, %37, %38, %39, %40, %41, %42, %43, %44, %45, %46, %47, %48, %49, %50, %51, %52, %53, %54, %55, %56, %57, %58, %59, %60, %61, %62, %63}, "
    "{%64, %65, %66, %67}, b, p, 1, 1, 1;\n}\n"
    : "+f"(d[0]), "+f"(d[1]), "+f"(d[2]), "+f"(d[3]), "+f"(d[4]), "+f"(d[5]), "+f"(d[6]), "+f"(d[7]), "+f"(d[8]), "+f"(d[9]), "+f"(d[10]), "+f"(d[11]), "+f"(d[12]), "+f"(d[13]), "+f"(d[14]), "+f"(d[15]), "+f"(d[16]), "+f"(d[17]), "+f"(d[18]), "+f"(d[19]), "+f"(d[20]), "+f"(d[21]), "+f"(d[22]), "+f"(d[23]), "+f"(d[24]), "+f"(d[25]), "+f"(d[26]), "+f"(d[27]), "+f"(d[28]), "+f"(d[29]), "+f"(d[30]), "+f"(d[31]), "+f"(d[32]), "+f"(d[33]), "+f"(d[34]), "+f"(d[35]), "+f"(d[36]), "+f"(d[37]), "+f"(d[38]), "+f"(d[39]), "+f"(d[40]), "+f"(d[41]), "+f"(d[42]), "+f"(d[43]), "+f"(d[44]), "+f"(d[45]), "+f"(d[46]), "+f"(d[47]), "+f"(d[48]), "+f"(d[49]), "+f"(d[50]), "+f"(d[51]), "+f"(d[52]), "+f"(d[53]), "+f"(d[54]), "+f"(d[55]), "+f"(d[56]), "+f"(d[57]), "+f"(d[58]), "+f"(d[59]), "+f"(d[60]), "+f"(d[61]), "+f"(d[62]), "+f"(d[63])
    : "r"(a0), "r"(a1), "r"(a2), "r"(a3), "l"(db), "r"(scale_d), "n"(OB));
}
template <int V> using IC = std::integral_constant<int, V>;
template <int I, int N, class F> __device__ __forceinline__ void static_for(F&& f) {
  if constexpr (I < N) { f(std::integral_constant<int, I>{}); static_for<I + 1, N>(f); }
}

constexpr uint32_t SM_Q = 0, SM_BAR = 7 * 32768;
constexpr uint32_t B_FULL = SM_BAR, B_EMPTY = B_FULL + 24, B_WF = B_EMPTY + 24, B_QFULL = B_WF + 32, B_QEMPTY = B_QFULL + 16,
                   B_EVH = B_QEMPTY + 16, B_EVQ = B_EVH + 8, B_EVP0 = B_EVQ + 8, B_BG = B_EVP0 + 16, B_M0 = B_BG + 8, B_HALF = B_M0 + 8,
                   B_HRD = B_HALF + 8, SM_UNSAFE = B_HRD + 8, SM_TS = SM_UNSAFE + 8, SM_ML = (SM_TS + 192 + 15) / 16 * 16, SM_EPOCH = SM_ML + 1024, SM_END = SM_EPOCH + 16;
constexpr uint32_t POS_M = 0x5462;
constexpr int SMEM_BYTES = SM_END;

#define ROW0(u) make_uint4(pack_bf16(o[16 * u], o[16 * u + 1]), pack_bf16(o[16 * u + 4], o[16 * u + 5]), \
                           pack_bf16(o[16 * u + 8], o[16 * u + 9]), pack_bf16(o[16 * u + 12], o[16 * u + 13]))
#define ROW1(u) make_uint4(pack_bf16(o[16 * u + 2], o[16 * u + 3]), pack_bf16(o[16 * u + 6], o[16 * u + 7]), \
                           pack_bf16(o[16 * u + 10], o[16 * u + 11]), pack_bf16(o[16 * u + 14], o[16 * u + 15]))

__global__ void __launch_bounds__(384, 1) gps_kernel(const __grid_constant__ Params P) {
  extern __shared__ __align__(1024) uint8_t smem_raw[];
  constexpr uint32_t sb = 1024;
  if (smem_u32(smem_raw) != sb) return;
  const int cta = blockIdx.x;
  const int wg = __shfl_sync(0xffffffffu, (int)threadIdx.x >> 7, 0);
  const int warp = __shfl_sync(0xffffffffu, ((int)threadIdx.x >> 5) & 3, 0);
  const int lane = threadIdx.x & 31;
#define ROLE                                                                                       \
  const Work& W = P.w[cta_id()];                                                                   \
  [[maybe_unused]] const int n0 = W.nb0 + W.na0, n1 = W.nb1 + W.na1, total = n0 + n1;              \
  [[maybe_unused]] const bool fin = W.role & R_FIN, tail = W.role & R_TAIL;                        \
  [[maybe_unused]] const uint32_t posw = total == 0 || tail ? POS_M : ((total & 1) ? 0x2546 : 0x4326)
  const int g = lane >> 2, t = lane & 3;
  if (wg < 2) {
    const int tid = threadIdx.x & 127;
    ROLE;
    const uint32_t sQ = sb + SM_Q + wg * 32768;
#define st0 tid_is(wg * 128)
    STAMP(st0, wg, 0);
    const int rr = lane >> 3, j = lane & 7;
    const uint32_t c0 = clk();
    if (threadIdx.x == 0) {
      for (int i = 0; i < 3; i++) { mbar_init(sb + B_FULL + 8 * i, 1); mbar_init(sb + B_EMPTY + 8 * i, tail ? 4 : 8); }
      for (int i = 0; i < 4; i++) mbar_init(sb + B_WF + 8 * i, 1);
      for (int i = 0; i < 2; i++) { mbar_init(sb + B_QFULL + 8 * i, 1); mbar_init(sb + B_QEMPTY + 8 * i, 4); mbar_init(sb + B_EVP0 + 8 * i, 4); }
      mbar_init(sb + B_EVH, 8); mbar_init(sb + B_EVQ, 8); mbar_init(sb + B_HALF, 8); mbar_init(sb + B_BG, 1); mbar_init(sb + B_M0, 1); mbar_init(sb + B_HRD, 1);
      asm volatile("fence.mbarrier_init.release.cluster;" ::: "memory");
    }
    __syncwarp();
    while (clk() - c0 < XDELAY) {}
    const uint4* px[4];
#pragma unroll
    for (int i = 0; i < 4; i++) px[i] = (const uint4*)(P.x + (size_t)min(W.q0 * 128 + wg * 64 + warp * 16 + i * 4 + rr, NN - 1) * 256) + j;
    auto x_load = [&](int c) {
      if (c < 4) {
#pragma unroll
        for (int i = 0; i < 4; i++)
          cp_async16(sQ + warp * 8192 + (i >> 1) * 4096 + c * 1024 + ((i & 1) * 4 + rr) * 128 + ((j ^ ((i & 1) * 4 + rr)) << 4), px[i] + c * 8);
      }
      cp_commit();
    };
    if (total > 0) {
#pragma unroll
      for (int c = 0; c < XD; c++) x_load(c);
    }
    bar_sync(4, 384);
    if (wg == 1) bar_arrive(5, 256);

    const uint32_t sF = sQ + warp * 8192 + ((lane >> 3) & 1) * 4096 + (lane & 7) * 128;
    auto frag = [&](int k) { return sF + (k >> 2) * 1024 + ((((k & 3) * 2 + (lane >> 4)) ^ (lane & 7)) << 4); };
    uint32_t hq[64];
    const bool own = (W.own >> wg) & 1;
    if (total > 0) {
      float c1[4] = {0.f, 0.f, 0.f, 0.f}, ca[4] = {0.f, 0.f, 0.f, 0.f}, cb[4] = {0.f, 0.f, 0.f, 0.f};
#pragma unroll
      for (int k = 0; k < 16; k++) {
        if ((k & 3) == 0) {
          asm volatile("cp.async.wait_group %0;" :: "n"(XD - 1) : "memory");
          __syncwarp();
          x_load(k / 4 + XD);
        }
        ldsm4(frag(k), hq[4 * k], hq[4 * k + 1], hq[4 * k + 2], hq[4 * k + 3]);
        mma16816(c1, hq[4 * k], hq[4 * k + 1], hq[4 * k + 2], hq[4 * k + 3], 0x3f803f80u, 0x3f803f80u);
        mma16816(ca, hq[4 * k], hq[4 * k + 1], hq[4 * k + 2], hq[4 * k + 3], hq[4 * k], hq[4 * k + 2]);
        mma16816(cb, hq[4 * k], hq[4 * k + 1], hq[4 * k + 2], hq[4 * k + 3], hq[4 * k + 1], hq[4 * k + 3]);
      }
      const float mu0 = c1[0] * (1.0f / 256.0f), mu1 = c1[2] * (1.0f / 256.0f);
      const float v0 = fmaf(__shfl_sync(0xffffffffu, g & 1 ? ca[1] : ca[0], g * 4 + (g >> 1)), 1.0f / 256.0f, 1e-5f - mu0 * mu0);
      const float v1 = fmaf(__shfl_sync(0xffffffffu, g & 1 ? cb[3] : cb[2], g * 4 + (g >> 1)), 1.0f / 256.0f, 1e-5f - mu1 * mu1);
      float rs0, rs1;
      asm("rsqrt.approx.ftz.f32 %0, %1;" : "=f"(rs0) : "f"(v0)); asm("rsqrt.approx.ftz.f32 %0, %1;" : "=f"(rs1) : "f"(v1));
      if (W.q0 * 128 + wg * 64 + warp * 16 >= NN) rs0 = rs1 = 0.f;
      float nb0 = -mu0 * rs0, nb1 = -mu1 * rs1;
      const uint32_t sS = sb + SM_ML + (wg * 64 + warp * 16) * 8;
      if (t == 0) {
        asm volatile("st.shared.v2.f32 [%0], {%1,%2};" :: "r"(sS + g * 8), "f"(rs0), "f"(nb0) : "memory");
        asm volatile("st.shared.v2.f32 [%0], {%1,%2};" :: "r"(sS + g * 8 + 64), "f"(rs1), "f"(nb1) : "memory");
      }
      if (__any_sync(0xffffffffu, !(4.f * mu0 * mu0 <= v0) || !(4.f * mu1 * mu1 <= v1))) {
#pragma unroll 1
        for (int r = 0; r < 16; r++) {
          const uint32_t ad = sQ + warp * 8192 + (r >> 3) * 4096 + rr * 1024 + (r & 7) * 128 + ((j ^ (r & 7)) << 4);
          const uint4 v = lds128(ad);
          float f[8] = {bf_lo(v.x), bf_hi(v.x), bf_lo(v.y), bf_hi(v.y), bf_lo(v.z), bf_hi(v.z), bf_lo(v.w), bf_hi(v.w)};
          float sum = 0.f, ss = 0.f, rs;
#pragma unroll
          for (int i = 0; i < 8; i++) sum += f[i];
#pragma unroll 1
          for (int k = 1; k < 32; k *= 2) sum += __shfl_xor_sync(0xffffffffu, sum, k);
          sum *= 1.0f / 256.0f;
#pragma unroll
          for (int i = 0; i < 8; i++) { f[i] -= sum; ss += f[i] * f[i]; }
#pragma unroll 1
          for (int k = 1; k < 32; k *= 2) ss += __shfl_xor_sync(0xffffffffu, ss, k);
          asm("rsqrt.approx.ftz.f32 %0, %1;" : "=f"(rs) : "f"(fmaf(ss, 1.0f / 256.0f, 1e-5f)));
          if (W.q0 * 128 + wg * 64 + warp * 16 >= NN) rs = 0.f;
          sts128(ad, make_uint4(pack_bf16(f[0] * rs, f[1] * rs), pack_bf16(f[2] * rs, f[3] * rs), pack_bf16(f[4] * rs, f[5] * rs), pack_bf16(f[6] * rs, f[7] * rs)));
          if (lane == 0) asm volatile("st.shared.v2.f32 [%0], {%1,%2};" :: "r"(sS + r * 8), "f"(rs), "f"(-sum * rs) : "memory");
        }
        __syncwarp();
#pragma unroll
        for (int k = 0; k < 16; k++) ldsm4(frag(k), hq[4 * k], hq[4 * k + 1], hq[4 * k + 2], hq[4 * k + 3]);
        rs0 = rs1 = 1.f; nb0 = nb1 = 0.f;
      }
      asm volatile("setmaxnreg.inc.sync.aligned.u32 %0;" :: "n"(CREG));
      const uint32_t ah0 = pack_bf16(rs0, rs0), ah1 = pack_bf16(rs1, rs1), n0_ = pack_bf16(nb0, nb0), n1_ = pack_bf16(nb1, nb1);
      const uint32_t al0 = pack_bf16(rs0 - bf_lo(ah0), rs0 - bf_lo(ah0)), al1 = pack_bf16(rs1 - bf_lo(ah1), rs1 - bf_lo(ah1));
#pragma unroll
      for (int i = 0; i < 32; i++) {
        hq[2 * i] = hfma2(hq[2 * i], ah0, hfma2(hq[2 * i], al0, n0_));
        hq[2 * i + 1] = hfma2(hq[2 * i + 1], ah1, hfma2(hq[2 * i + 1], al1, n1_));
      }
      if (own) {
        const float e0 = fmaf(bf_hi(__shfl_sync(0xffffffffu, hq[62], lane | 3)), -0.5f * KS, KC), e1 = fmaf(bf_hi(__shfl_sync(0xffffffffu, hq[63], lane | 3)), -0.5f * KS, KC);
#pragma unroll
        for (int k = 0; k < 16; k++)
          stsm4(frag(k), hfma2(hq[4 * k], KS2, KC2), hfma2(hq[4 * k + 1], KS2, KC2),
                k < 15 ? hfma2(hq[4 * k + 2], KS2, KC2) : pack_bf16(fmaf(bf_lo(hq[62]), KS, e0), t == 3 ? KC : fmaf(bf_hi(hq[62]), KS, e0)),
                k < 15 ? hfma2(hq[4 * k + 3], KS2, KC2) : pack_bf16(fmaf(bf_lo(hq[63]), KS, e1), t == 3 ? KC : fmaf(bf_hi(hq[63]), KS, e1)));
      }
      __syncwarp();
      if (lane == 0) mbar_arrive(sb + B_EVH);
    } else {
      asm volatile("setmaxnreg.inc.sync.aligned.u32 %0;" :: "n"(CREG));
    }
    STAMP(st0, wg, 1);

    float o[128];
    int qph = 0, st = tail ? wg : 0, ph = 0;
    auto release = [&](int stg) { if (lane == 0) mbar_arrive(sb + B_EMPTY + 8 * stg); };
    int resume = total > 0 ? -1 : 0;
    auto fill = [&]() __attribute__((always_inline)) {
#pragma unroll
      for (int i = 0; i < 32; i++)
        asm volatile("ld.volatile.shared.v4.f32 {%0,%1,%2,%3}, [%4];" : "=f"(o[4 * i]), "=f"(o[4 * i + 1]), "=f"(o[4 * i + 2]), "=f"(o[4 * i + 3]) : "r"(sb) : "memory");
    };
    auto finish = [&]() __attribute__((always_inline)) {
      STAMP(st0, wg, 11);
      DUMP(st0, wg, 0, 16);
      if (!P.zero) { asm volatile("exit;"); __builtin_unreachable(); }
      fill();
    };
    auto run = [&](auto hot_) __attribute__((always_inline)) {
    constexpr bool HOT = hot_.value;
    const int nloc = P.w[cta_id()].nloc;
    if (!HOT && resume == 0) {
#pragma unroll 1
      for (int i = 0; i < 32; i++) {
        const int r = i * 8 + wg * 4 + warp;
        cp_async16(sb + ((POS_M >> (r >> 6) * 4) & 15) * 32768 + sw_byte(r & 63, lane * 8), (const uint4*)P.wout + r * 32 + lane);
      }
    }
    bool wide = false;
    if (HOT) {
      reg_fence(hq);
      auto qstep = [&](auto k_) {
        constexpr int k = k_.value;
        if (k < 2 || k % 4 == 0) { mbar_wait(k == 0 ? sb + B_M0 : sb + B_WF + 2 * (k & ~3), 0); if (k == 0 || k == 4) bar_sync(5 + wg, 256); wg_fence(); }
        if constexpr (k == 0) wgmma_rs_n256_tb_first<0>(o, hq[0], hq[1], hq[2], hq[3], desc_mn(sb, (POS_M & 15) * 2048));
        else wgmma_rs_n256_tb<(k & 3) * 512>(o, hq[4 * k], hq[4 * k + 1], hq[4 * k + 2], hq[4 * k + 3], desc_mn(sb, ((POS_M >> (k & ~3)) & 15) * 2048), 1);
      };
      static_for<0, 4>(qstep);
      wg_commit();
      bar_arrive(6 - wg, 256);
      wg_wait<0>();
      if (!tail) release(0);
      static_for<4, 16>(qstep);
      wg_commit();
      bar_arrive(6 - wg, 256);
      wg_wait<0>();
      reg_fence(o); reg_fence(hq);
      if (!tail) release(1);
      STAMP(st0, wg, 2);
      float c0 = (o[124] + (t == 3 ? 2.f : 1.f) * o[125]) * (-0.5f / 4.5f), c1 = (o[126] + (t == 3 ? 2.f : 1.f) * o[127]) * (-0.5f / 4.5f);
      c0 += __shfl_xor_sync(0xffffffffu, c0, 1); c1 += __shfl_xor_sync(0xffffffffu, c1, 1);
      c0 += __shfl_xor_sync(0xffffffffu, c0, 2); c1 += __shfl_xor_sync(0xffffffffu, c1, 2);
      float r0 = t == 3 ? 0.f : o[125], r1 = t == 3 ? 0.f : o[127], r2 = o[124], r3 = o[126];
#pragma unroll
      for (int i = 0; i < 31; i++) { r2 += o[4 * i]; r0 += o[4 * i + 1]; r3 += o[4 * i + 2]; r1 += o[4 * i + 3]; }
      r0 += r2; r1 += r3;
      r0 += __shfl_xor_sync(0xffffffffu, r0, 1); r1 += __shfl_xor_sync(0xffffffffu, r1, 1);
      r0 += __shfl_xor_sync(0xffffffffu, r0, 2); r1 += __shfl_xor_sync(0xffffffffu, r1, 2);
      r0 = fmaf(c0, -255.f, PSH / KC - r0); r1 = fmaf(c1, -255.f, PSH / KC - r1);
      wide = !(fabsf(c0) <= SAFE_C / KS) || !(fabsf(c1) <= SAFE_C / KS);
      if (own) mbar_wait(sb + B_HRD, 0);
#pragma unroll
      for (int k = 0; k < 16; k++)
        stsm4(frag(k),
              pack_bf16(o[8 * k] + c0, o[8 * k + 1] + c0), pack_bf16(o[8 * k + 2] + c1, o[8 * k + 3] + c1),
              pack_bf16(o[8 * k + 4] + c0, k == 15 && t == 3 ? r0 : o[8 * k + 5] + c0), pack_bf16(o[8 * k + 6] + c1, k == 15 && t == 3 ? r1 : o[8 * k + 7] + c1));
      fence_async_smem();
      __syncwarp();
      STAMP(st0, wg, 3);
      if (tail) { bar_sync(7, 256); if (wg == 0) { release(0); release(1); release(2); } }
      }

    if (HOT || resume) {
      ROLE;
      float m0, m1;
      const int qh = tail ? 0 : wg, tl = W.role >> 2;
      uint32_t qo = qh * 2048;
      const uint32_t ko = (2 - tl) * 2048, stop = 1 + tl + (uint32_t)P.zero;
      float l0, l1;
      auto row_sums = [&]() { l0 = __shfl_sync(0xffffffffu, o[125] + 0.f, lane | 3); l1 = __shfl_sync(0xffffffffu, o[127] + 0.f, lane | 3); };
#define PART(u) make_uint4(pack_bf16(o[8 * u] - l0, o[8 * u + 1] - l0), pack_bf16(o[8 * u + 2] - l1, o[8 * u + 3] - l1), \
                           pack_bf16(o[8 * u + 4] - l0, o[8 * u + 5] - l0), pack_bf16(o[8 * u + 6] - l1, o[8 * u + 7] - l1))
      bool unsafe = !HOT;
#pragma unroll 1
      for (int seg = HOT ? 0 : resume - 1;; seg++) {
        ROLE;
        const bool last = __any_sync(0xffffffffu, seg || n1 == 0);
        m0 = m1 = !HOT && unsafe ? -INFINITY : 0.f;
        int first = 1;
        auto tile = [&](auto n_, bool endseg) __attribute__((always_inline)) -> bool {
          constexpr int N = n_.value;
          float s[N / 2]; uint32_t p[N / 4];
          if (!mbar_try_wait(sb + B_FULL + 8 * st, ph)) mbar_wait(sb + B_FULL + 8 * st, ph);
          const bool again = !HOT && N == 112 && first && !seg;
          if (HOT || N == 128) bar_sync(5 + wg, 256);
          else asm volatile("{\n.reg .pred p;\nsetp.eq.u32 p, %1, 0;\n@p bar.sync %0, 256;\n}\n" :: "r"(5 + wg), "r"((uint32_t)again) : "memory");
          wg_fence();
          const uint64_t dQ = desc_k(sb + SM_Q, qo), dK = desc_k(sb, ko + st * 4096);
          qo += (uint32_t)P.zero;
          static_for<0, 16>([&](auto k) { constexpr int kk = (k.value + KROT) & 15, off = (kk >> 2) * 64 + (kk & 3) * 2; wgmma_qk<off, off>(s, dQ, dK, k.value > 0); });
          wg_commit();
          if (HOT || N == 128) bar_arrive(6 - wg, 256);
          else asm volatile("{\n.reg .pred p;\nsetp.eq.u32 p, %1, 0;\n@p bar.arrive %0, 256;\n}\n" :: "r"(6 - wg), "r"((uint32_t)again) : "memory");
          if (HOT && N == 112 && first && !seg) {
            float a0 = 0.f, a1 = 0.f, a2 = 0.f, a3 = 0.f;
#pragma unroll
            for (int i = 0; i < 32; i++) { a0 += o[4 * i] * o[4 * i]; a2 += o[4 * i + 1] * o[4 * i + 1]; a1 += o[4 * i + 2] * o[4 * i + 2]; a3 += o[4 * i + 3] * o[4 * i + 3]; }
            a0 += a2; a1 += a3;
            a0 += __shfl_xor_sync(0xffffffffu, a0, 1); a1 += __shfl_xor_sync(0xffffffffu, a1, 1);
            a0 += __shfl_xor_sync(0xffffffffu, a0, 2); a1 += __shfl_xor_sync(0xffffffffu, a1, 2);
            unsafe = __any_sync(0xffffffffu, bar_red_or(tail ? 7 : 1 + wg, tail ? 256 : 128, wide || !(a0 <= SAFE_N2 / (KS * KS)) || !(a1 <= SAFE_N2 / (KS * KS))));
            if (lane == 0) { asm volatile("st.shared.u8 [%0], %1;" :: "r"(sb + SM_UNSAFE + wg), "r"((uint32_t)unsafe) : "memory"); mbar_arrive(sb + B_EVQ); }
          }
          STAMP(N == 112 && first && !seg && st0, wg, 0);
          wg_wait<0>();
          reg_fence(s);
          if (HOT && N == 112 && unsafe) return true;
          if (endseg) { if (lane == 0) mbar_arrive(sb + B_QEMPTY + 8 * wg); }
          if (!HOT && unsafe) {
            float a0 = fmaxf(s[0], s[1]), a1 = fmaxf(s[2], s[3]);
#pragma unroll
            for (int i = 1; i < N / 8; i++) { a0 = fmaxf(a0, fmaxf(s[4 * i], s[4 * i + 1])); a1 = fmaxf(a1, fmaxf(s[4 * i + 2], s[4 * i + 3])); }
            if (__any_sync(0xffffffffu, (a0 > m0 + TAU) || (a1 > m1 + TAU))) {
              a0 = fmaxf(a0, __shfl_xor_sync(0xffffffffu, a0, 1)); a1 = fmaxf(a1, __shfl_xor_sync(0xffffffffu, a1, 1));
              a0 = fmaxf(a0, __shfl_xor_sync(0xffffffffu, a0, 2)); a1 = fmaxf(a1, __shfl_xor_sync(0xffffffffu, a1, 2));
              const float x0 = ceilf(fmaxf(m0, a0)), x1 = ceilf(fmaxf(m1, a1)), sc0 = ex2(m0 - x0), sc1 = ex2(m1 - x1);
              m0 = x0; m1 = x1;
#pragma unroll
              for (int i = 0; i < 32; i++) { o[4 * i] *= sc0; o[4 * i + 1] *= sc0; o[4 * i + 2] *= sc1; o[4 * i + 3] *= sc1; }
            }
#pragma unroll
            for (int i = 0; i < N / 8; i++) { s[4 * i] -= m0; s[4 * i + 1] -= m0; s[4 * i + 2] -= m1; s[4 * i + 3] -= m1; }
          }
          auto pv = [&](auto k) { wgmma_rs_n256_tb<k.value * 512 + (63 << 16)>(o, p[4 * k.value], p[4 * k.value + 1], p[4 * k.value + 2], p[4 * k.value + 3], dK, k.value > 0 || N == 128 ? 1 : !first); };
#pragma unroll
          for (int i = 0; i < 16; i++) { p[i] = pack_bf16(ex2(s[2 * i]), ex2(s[2 * i + 1])); asm volatile("" : "+r"(p[i]) :: "memory"); }
          reg_fence(o);
          do bar_sync(5 + wg, 256); while (P.zero);
          wg_fence();
          static_for<0, 4>(pv);
          wg_commit();
#pragma unroll
          for (int i = 16; i < N / 4; i++) { p[i] = pack_bf16(ex2(s[2 * i]), ex2(s[2 * i + 1])); asm volatile("" : "+r"(p[i]) :: "memory"); }
          wg_fence();
          static_for<4, N / 16>(pv);
          wg_commit();
          bar_arrive(6 - wg, 256);
          if (N == 128) { wg_wait<1>(); if (endseg && last) { if (lane == 0) mbar_arrive(sb + B_HALF); } }
          wg_wait<0>();
          reg_fence(o); reg_fence(p);
          release(st);
          if (st) { st--; ph ^= 1; } else st = stop;
          return false;
        };
#pragma unroll 1
        for (int left = tail ? 8 - wg : (seg ? W.nb1 : W.nb0); left > 0; left--) { if (tile(IC<112>{}, false)) { resume = 1; return; } STAMP(first && !seg && st0, wg, 4); first = 0; }
#pragma unroll 1
        for (int left = tail ? 32 + wg : (seg ? W.na1 : W.na0); left > 0; left--) tile(IC<128>{}, left == 1);
        STAMP(st0 && last, wg, 6);
        {
        ROLE;
        if (last && fin && !(tail && wg == 1)) break;
        row_sums();
        if (last) mbar_wait(sb + (tail ? B_QEMPTY : B_HALF), 0);
        const uint32_t sp = sb + (tail ? 0 : (last ? (posw >> 12) + wg : (wg ? 4 - 2 * st : 6))) * 32768, sm = sb + SM_ML + (tail ? 0 : wg) * 512;
#pragma unroll
        for (int u = 0; u < 16; u++) sts128(sp + (u * 128 + tid) * 16, PART(u));
        if (t == 0) {
          asm volatile("st.shared.v2.f32 [%0], {%1,%2};" :: "r"(sm + (warp * 16 + g) * 8), "f"(m0), "f"(l0) : "memory");
          asm volatile("st.shared.v2.f32 [%0], {%1,%2};" :: "r"(sm + (warp * 16 + g) * 8 + 64), "f"(m1), "f"(l1) : "memory");
        }
        __syncwarp();
        if (lane == 0) mbar_arrive(sb + B_EVP0 + 8 * wg);
        STAMP(st0 && last, wg, 7);
        if (last) break;
        mbar_wait(sb + B_QFULL + 8 * wg, qph); qph ^= 1;
        uint32_t u; asm volatile("ld.shared.u8 %0, [%1];" : "=r"(u) : "r"(sb + SM_UNSAFE + wg) : "memory");
        unsafe = __any_sync(0xffffffffu, u != 0);
        if (HOT && unsafe) { resume = 2; return; }
        }
      }

      if (P.w[cta_id()].role & R_FIN) {
        ROLE;
        if (!(tail && wg == 1)) {
        row_sums();
        const int rl = wg * 64 + warp * 16 + g;
        uint32_t a[64];
#pragma unroll
        for (int i = 0; i < 64; i++) a[i] = pack_bf16(o[2 * i] - (i & 1 ? l1 : l0), o[2 * i + 1] - (i & 1 ? l1 : l0));
        reg_fence(a);
        {
          float2 e0, e1;
          mbar_wait(sb + B_QFULL + 8 * wg, qph);
          asm volatile("ld.shared.v2.f32 {%0,%1}, [%2];" : "=f"(e0.x), "=f"(e0.y) : "r"(sb + SM_ML + rl * 8) : "memory");
          asm volatile("ld.shared.v2.f32 {%0,%1}, [%2];" : "=f"(e1.x), "=f"(e1.y) : "r"(sb + SM_ML + rl * 8 + 64) : "memory");
          STAMP(st0, wg, 7);
          uint4 v[16];
#pragma unroll
          for (int u = 0; u < 16; u++) v[u] = lds128(sQ + (u * 128 + tid) * 16);
          uint32_t fb0 = 0x3f803f80u, fb1 = 0x3f803f80u;
          const float s0 = l0 + e0.y, s1 = l1 + e1.y;
          if (__any_sync(0xffffffffu, m0 != e0.x || m1 != e1.x || !(fmaxf(s0, s1) < 0x1p40f) || !(fminf(s0, s1) > 0x1p-40f))) {
            const float x0 = fmaxf(m0, e0.x), x1 = fmaxf(m1, e1.x);
            const float d0 = fmaxf(m0 - x0, -1000.f), d1 = fmaxf(m1 - x1, -1000.f), f0 = fmaxf(e0.x - x0, -1000.f), f1 = fmaxf(e1.x - x1, -1000.f);
            l0 = l0 * ex2(d0) + e0.y * ex2(f0); l1 = l1 * ex2(d1) + e1.y * ex2(f1);
            const int E0 = fexp(l0), E1 = fexp(l1);
            const uint32_t fa0 = pow2_bf2((int)d0 - E0), fa1 = pow2_bf2((int)d1 - E1);
            fb0 = pow2_bf2((int)f0 - E0); fb1 = pow2_bf2((int)f1 - E1);
            l0 = __uint_as_float(__float_as_uint(l0) - (E0 << 23)); l1 = __uint_as_float(__float_as_uint(l1) - (E1 << 23));
#pragma unroll
            for (int i = 0; i < 32; i++) { a[2 * i] = hmul2(a[2 * i], fa0); a[2 * i + 1] = hmul2(a[2 * i + 1], fa1); }
          } else { l0 = s0; l1 = s1; }
#pragma unroll
          for (int u = 0; u < 16; u++) {
            a[4 * u] = hfma2(v[u].x, fb0, a[4 * u]); a[4 * u + 1] = hfma2(v[u].y, fb1, a[4 * u + 1]);
            a[4 * u + 2] = hfma2(v[u].z, fb0, a[4 * u + 2]); a[4 * u + 3] = hfma2(v[u].w, fb1, a[4 * u + 3]);
          }
        }
        float fs0, fs1;
        asm("rcp.approx.ftz.f32 %0, %1;" : "=f"(fs0) : "f"(l0 * (KS / KC))); asm("rcp.approx.ftz.f32 %0, %1;" : "=f"(fs1) : "f"(l1 * (KS / KC)));
        STAMP(st0, wg, 8);
        reg_fence(a);
        bar_sync(5 + wg, 256);
        uint64_t dW[4];
        float y0[64], y1[64];
        auto half0 = [&](auto u_) {
          constexpr int u = u_.value;
          if (u % 4 == 0) { mbar_wait(sb + B_WF + 2 * u, 1); wg_fence(); dW[u / 4] = desc_mn(sb, ((posw >> u) & 15) * 2048); }
          wgmma_rs_n128_tb<(u & 3) * 512>(y0, a[4 * u], a[4 * u + 1], a[4 * u + 2], a[4 * u + 3], dW[u / 4], u != 0);
        };
        auto half1 = [&](auto u_) {
          constexpr int u = u_.value;
          wgmma_rs_n128_tb<(u & 3) * 512 + 128>(y1, a[4 * u], a[4 * u + 1], a[4 * u + 2], a[4 * u + 3], dW[u / 4], u != 0);
        };
        const bool wr = W.q0 * 128 + wg * 64 + warp * 16 < NN;
        uint4* po = (uint4*)(P.out + (size_t)(W.q0 * 128 + rl) * 256) + t;
        auto emit = [&](const float* y, uint4* dst) {
          if (wr && (!(DBG & 2) || P.zero)) {
            OUTW(dst, make_uint4(pack_bf16(y[0] * fs0, y[1] * fs0), pack_bf16(y[4] * fs0, y[5] * fs0), pack_bf16(y[8] * fs0, y[9] * fs0), pack_bf16(y[12] * fs0, y[13] * fs0)));
            OUTW(dst + 8 * 32, make_uint4(pack_bf16(y[2] * fs1, y[3] * fs1), pack_bf16(y[6] * fs1, y[7] * fs1), pack_bf16(y[10] * fs1, y[11] * fs1), pack_bf16(y[14] * fs1, y[15] * fs1)));
          }
          wg_fence();
        };
        static_for<0, 16>(half0);
        wg_commit();
        static_for<0, 4>(half1);
        wg_commit();
        wg_wait<1>();
        reg_fence(y0);
        emit(y0, po); static_for<4, 8>(half1);
        emit(y0 + 16, po + 4); static_for<8, 12>(half1);
        emit(y0 + 32, po + 8); static_for<12, 16>(half1);
        wg_commit();
        bar_arrive(6 - wg, 256);
        emit(y0 + 48, po + 12);
        wg_wait<0>();
        reg_fence(a); reg_fence(y1);
        STAMP(st0, wg, 9);
#pragma unroll
        for (int u = 0; u < 4; u++) emit(y1 + 16 * u, po + 16 + 4 * u);
        }
        finish();
      }
        }
#pragma unroll 1
    for (int step = HOT || resume ? 0 : -4; step < nloc; step++) {
      ROLE;
      const bool isw = !HOT && step < 0;
      if (isw) {
        const uint4* src = (const uint4*)(step < -2 ? P.wmsg : P.wv) + ((step & 1) * 128 + wg * 64 + warp) * 32 + lane;
        float cw[8] = {0.f, 0.f, 0.f, 0.f, 0.f, 0.f, 0.f, 0.f};
#pragma unroll 1
        for (int i = 0; i < 16; i++) cp_async16(sQ + sw_byte(i * 4 + warp, lane * 8), src + i * 128);
        cp_commit();
#pragma unroll
        for (int i = 0; i < 8; i++) {
          const uint4 v = __ldg((const uint4*)(step < -2 ? P.wmsg : P.wv) + (248 + i) * 32 + lane);
          const float k = step < -2 ? 0.f : (i == 7 ? -1.0f / 4.5f : -0.5f / 4.5f);
          cw[0] += bf_lo(v.x) * k; cw[1] += bf_hi(v.x) * k; cw[2] += bf_lo(v.y) * k; cw[3] += bf_hi(v.y) * k;
          cw[4] += bf_lo(v.z) * k; cw[5] += bf_hi(v.z) * k; cw[6] += bf_lo(v.w) * k; cw[7] += bf_hi(v.w) * k;
        }
        asm volatile("cp.async.wait_group 0;" ::: "memory");
#pragma unroll 1
        for (int i = 0; i < 16; i++) {
          const uint32_t ad = sQ + sw_byte(i * 4 + warp, lane * 8);
          const uint4 v = lds128(ad);
          uint4 w4 = make_uint4(pack_bf16(bf_lo(v.x) + cw[0], bf_hi(v.x) + cw[1]), pack_bf16(bf_lo(v.y) + cw[2], bf_hi(v.y) + cw[3]),
                                pack_bf16(bf_lo(v.z) + cw[4], bf_hi(v.z) + cw[5]), pack_bf16(bf_lo(v.w) + cw[6], bf_hi(v.w) + cw[7]));
          if (step == -1 && wg * 64 + i * 4 + warp == 127) w4 = make_uint4(0, 0, 0, 0);
          sts128(ad, w4);
        }
        fence_async_smem();
        bar_sync(7, 256);
      } else {
        SSTAMP(0);
        mbar_wait(sb + B_QFULL + 8 * wg, qph); qph ^= 1;
        STAMP(st0 && step == 0, wg, 8);
        SSTAMP(1);
        bar_sync(5 + wg, 256);
        SSTAMP(2);
      }
#pragma unroll 1
      for (int c = 0; c < 4; c++) {
        if (step == 0) mbar_wait(sb + B_WF + 8 * c, HOT || resume);
        const int turn2 = HOT || resume ? 3 : 4;
        if (c == turn2) bar_sync(5 + wg, 256);
        wg_fence();
        const uint64_t dA = desc_k(sb + SM_Q, wg * 2048 + c * 64), dW = desc_mn(sb, ((posw >> c * 4) & 15) * 2048);
        static_for<0, 4>([&](auto k) { wgmma_ss_n256_tb<k.value * 2, k.value * 512>(o, dA, dW, k.value > 0 ? 1 : c); });
        wg_commit();
        if ((c == 3 || c == turn2 - 1) && !isw) bar_arrive(6 - wg, 256);
        wg_wait<1>();
      }
      wg_wait<0>();
      reg_fence(o);
      {
        STAMP(st0 && step == 0, wg, 9);
        SSTAMP(3);
        if (isw) bar_sync(1 + wg, 128); else if (lane == 0) mbar_arrive(sb + B_QEMPTY + 8 * wg);
        uint8_t* dw = (uint8_t*)(step < -2 ? g_Wmo : g_Wvo) + ((step & 1) * 2 + wg) * 32768 + warp * 8192 + g * 128;
        const int row0 = (W.loc0 + step) * 128 + wg * 64 + warp * 16;
        uint4 r[16];
#pragma unroll
        for (int u = 0; u < 8; u++) { r[2 * u] = ROW0(u); r[2 * u + 1] = ROW1(u); }
        if (isw) {
#pragma unroll
          for (int u = 0; u < 16; u++) *(uint4*)(dw + (u >> 2) * 1024 + ((((u & 2) * 2 + t) ^ g) << 4) + (u & 1) * 4096) = r[u];
        } else if (row0 < NN) {
          uint4* po = (uint4*)(P.out + (size_t)(row0 + g) * 256) + t;
          uint32_t c1 = clk();
#pragma unroll
          for (int u = 0; u < 16; u++) {
            if (!(DBG & 1) || !HOT || P.zero) red_bf16x8(po + (u >> 1) * 4 + (u & 1) * 256, r[u]);
            if (!HOT) { c1 += PACE; while ((int)(clk() - c1) < 0) {} }
          }
        }
        if (!HOT && step == -1) { bar_sync(7, 256); if (tid_is(0)) flag_release(F_W); __syncwarp(); STAMP(st0, wg, 3); }
      }
    }
    finish();
    };
    if (resume < 0) run(std::true_type{});
    else fill();
    run(std::false_type{});
    asm volatile("setmaxnreg.dec.sync.aligned.u32 %0;" :: "n"(504 - 2 * CREG));
  } else {
    STAMP(lane == 0 && warp == 0, 2, 0);
        const int mi = cta >> 3;
    const uint32_t sW = sb + 3 * 32768;
    uint4 wa[4], wb[8];
    {
      const uint4* pq = (const uint4*)(P.wq + ((mi & 15) * 16 + g) * 256) + warp * 8 + t;
      const uint4* pk = (const uint4*)(P.wk + ((cta & 7) * 32 + g) * 256) + warp * 8 + t;
#pragma unroll
      for (int i = 0; i < 4; i++) wa[i] = __ldg(pq + (i >> 1) * 256 + (i & 1) * 4);
#pragma unroll
      for (int i = 0; i < 8; i++) wb[i] = __ldg(pk + (i >> 1) * 256 + (i & 1) * 4);
    }
    bar_sync(4, 384);
    {
#pragma unroll
      for (int n = 0; n < 4; n++) {
        float c[4] = {0.f, 0.f, 0.f, 0.f};
#pragma unroll
        for (int u = 0; u < 2; u++) {
          mma16816(c, wa[u].x, wa[2 + u].x, wa[u].y, wa[2 + u].y, wb[2 * n + u].x, wb[2 * n + u].y);
          mma16816(c, wa[u].z, wa[2 + u].z, wa[u].w, wa[2 + u].w, wb[2 * n + u].z, wb[2 * n + u].w);
        }
        asm volatile("st.shared.v2.f32 [%0], {%1,%2};" :: "r"(sW + ((warp * 16 + g) * 40 + n * 8 + 2 * t) * 4), "f"(c[0]), "f"(c[1]) : "memory");
        asm volatile("st.shared.v2.f32 [%0], {%1,%2};" :: "r"(sW + ((warp * 16 + g + 8) * 40 + n * 8 + 2 * t) * 4), "f"(c[2]), "f"(c[3]) : "memory");
      }
      STAMP(lane == 0 && warp == 0, 2, 7);
      bar_sync(3, 128);
      if (warp < 2) {
        float c[8] = {0.f, 0.f, 0.f, 0.f, 0.f, 0.f, 0.f, 0.f};
#pragma unroll
        for (int k = 0; k < 4; k++) {
          const uint4 v = lds128(sW + ((k * 16 + warp * 8 + g) * 40 + t * 8) * 4), w = lds128(sW + ((k * 16 + warp * 8 + g) * 40 + t * 8 + 4) * 4);
          c[0] += __uint_as_float(v.x); c[1] += __uint_as_float(v.y); c[2] += __uint_as_float(v.z); c[3] += __uint_as_float(v.w);
          c[4] += __uint_as_float(w.x); c[5] += __uint_as_float(w.y); c[6] += __uint_as_float(w.z); c[7] += __uint_as_float(w.w);
        }
        const float ms = 1.4426950408889634f / 16.0f / KS;
        if (cta < 128)
          *(uint4*)((uint8_t*)g_M + sw_byte(mi * 16 + warp * 8 + g, (cta & 7) * 32 + t * 8)) =
              make_uint4(pack_bf16(c[0] * ms, c[1] * ms), pack_bf16(c[2] * ms, c[3] * ms), pack_bf16(c[4] * ms, c[5] * ms), pack_bf16(c[6] * ms, c[7] * ms));
      }
    }
    asm volatile("setmaxnreg.dec.sync.aligned.u32 %0;" :: "n"(504 - 2 * CREG));
    STAMP(lane == 0 && warp == 0, 2, 13);
    bar_sync(3, 128);
#define ep1 (lds32(sb + SM_EPOCH) + 1)
    if (threadIdx.x == 256 && cta < 128) { if (DBG & 16) asm volatile("red.relaxed.gpu.global.add.u32 [%0], 1;" :: "l"(g_flag + F_M + (cta >> 5)) : "memory"); else flag_release(F_M + (cta >> 5)); }
    __syncwarp();
    ROLE;
    if (warp == 3 && W.own) {
      mbar_wait_w(sb + B_EVH, 0);
      if (lane == 0) {
        fence_async_smem();
        const int h0 = W.own == 2, nh = W.own == 3 ? 2 : 1;
        bulk_s2g(g_h + W.q0 * 4096 + h0 * 2048, sb + SM_Q + h0 * 32768, nh * 32768);
        bulk_s2g(g_stat + W.q0 * 128 + h0 * 64, sb + SM_ML + h0 * 512, nh * 512);
        bulk_commit();
        bulk_wait_read();
        mbar_arrive(sb + B_HRD);
        bulk_wait_all();
        red_relaxed(g_flag + F_H);
      }
      __syncwarp();
      STAMP(lane == 0, 2, 6);
    }
    if (warp == 0) {
      if (lane == 0) {
        STAMP(true, 2, 1);
        const uint32_t epoch = ld_relaxed(g_flag + F_EPOCH);
        if (total > 0) {
#pragma unroll
          for (int c = 0; c < 3; c++) mbar_expect_tx(sb + B_WF + 8 * c, c == 0 ? WCH_B - 8192 : WCH_B);
          mbar_expect_tx(sb + B_M0, 8192);
          int c = 0;
#pragma unroll 1
          for (uint32_t it = 0; c < 4; it++) {
            uint4 f;
            asm volatile("ld.relaxed.gpu.global.v4.u32 {%0,%1,%2,%3}, [%4];" : "=r"(f.x), "=r"(f.y), "=r"(f.z), "=r"(f.w) : "l"(g_flag + F_M) : "memory");
            uint32_t tm;
            asm volatile("mad.lo.u32 %0, %1, 32, 32;" : "=r"(tm) : "r"(epoch));
            int ok = (int)(f.x - tm) < 0 ? 0 : (int)(f.y - tm) < 0 ? 1 : (int)(f.z - tm) < 0 ? 2 : (int)(f.w - tm) < 0 ? 3 : 4;
            if (it > (1u << 23)) ok = 4;
            if (ok > c) {
              asm volatile("fence.acquire.gpu;" ::: "memory"); fence_async_gmem();
              if (c == 0) bulk_g2s(sb + (POS_M & 15) * 32768, g_M, 8192, sb + B_M0);
            }
#pragma unroll 1
            for (; c < ok; c++) {
              const uint32_t skip = c == 0 ? 8192 : 0;
              bulk_g2s(sb + ((POS_M >> c * 4) & 15) * 32768 + skip, pofs<const uint8_t>(g_M, c * WCH_B + skip), WCH_B - skip, sb + B_WF + 8 * c);
              STAMP(c == 0, 2, 2);
            }
          }
        }
        asm volatile("st.shared.u32 [%0], %1;" :: "r"(sb + SM_EPOCH), "r"(epoch) : "memory");
        if (total > 0) mbar_expect_tx(sb + B_WF + 24, WCH_B);
        int st = 0, ph = 0, qph = 0;
        const int nsl = tail ? 3 : 2;
        auto next_slot = [&]() { mbar_wait(sb + B_EMPTY + 8 * st, ph); if (++st == nsl) { st = 0; ph ^= 1; } };
        auto w_load = [&](int c0, int c1) {
#pragma unroll 1
          for (int c = c0; c < c1; c++) {
            mbar_expect_tx(sb + B_WF + 8 * c, WCH_B);
            bulk_g2s(sb + ((posw >> c * 4) & 15) * 32768, pofs<const uint8_t>(fin ? g_Wvo : g_Wmo, c * WCH_B), WCH_B, sb + B_WF + 8 * c);
          }
        };
        auto q_load = [&](const uint4* src, bool wait_empty) {
#pragma unroll 1
          for (int h = 0; h < 2; h++) {
            if (wait_empty) mbar_wait(sb + B_QEMPTY + 8 * h, qph);
            mbar_expect_tx(sb + B_QFULL + 8 * h, 32768);
            (HINT & 2 ? bulk_g2s_last : bulk_g2s)(sb + SM_Q + h * 32768, src + h * 2048, 32768, sb + B_QFULL + 8 * h);
          }
          if (wait_empty) qph ^= 1;
        };
        auto part_out = [&](int slot, int h, uint32_t region, int parity) {
          mbar_wait(sb + B_EVP0 + 8 * h, parity);
          fence_async_smem();
          bulk_s2g(g_part + slot * 4096 + h * 2048, sb + region * 32768, 32768);
          bulk_s2g(g_ml + slot * 128 + h * 64, sb + SM_ML + h * 512, 512);
          bulk_commit();
        };
        auto announce = [&](int f) {
          if (RELF) { fence_async_gmem(); flag_release(f); }
          else red_relaxed(g_flag + f);
        };
        if (total > 0) {
          STAMP(true, 2, 3);
          flag_wait(F_H, ep1 * NHSIG); fence_async_gmem();
          STAMP(true, 2, 4);
          uint32_t ko = W.k0 * 8192;
#pragma unroll 1
          for (int j = 0; j < total; j++) {
            if (j == n0) {
              flag_wait(F_QP + W.q1 * LN_, ep1); fence_async_gmem();
              const uint32_t u = __ldcg(g_unsafe + W.q1);
              asm volatile("st.shared.u32 [%0], %1;" :: "r"(sb + SM_UNSAFE), "r"(u) : "memory");
              ko = W.k1 * 8192;
            }
            if (j == n0 + 1) q_load(g_qp + W.q1 * 4096, true);
            if (j == total - 1) { flag_wait(F_W, ep1); fence_async_gmem(); if (!tail) w_load(0, 1); }
            const uint32_t bytes = (j < n0 ? j < W.nb0 : j - n0 < W.nb1) ? 112 * 512 : 128 * 512, s0 = st;
            const uint32_t region = (tail ? 1 : 2) + 2 * s0, skip = j == n0 + 1 ? 32768 : 0;
            if (skip) part_out(W.slotA, 0, 6, 0);
            next_slot();
            mbar_expect_tx(sb + B_FULL + 8 * s0, bytes);
            bulk_g2s(sb + region * 32768 + skip, pofs<const uint8_t>(g_h, ko + skip), bytes - skip, sb + B_FULL + 8 * s0);
            if (skip) {
              part_out(W.slotA, 1, region, 0);
              bulk_wait_read();
              bulk_g2s(sb + region * 32768, pofs<const uint8_t>(g_h, ko), skip, sb + B_FULL + 8 * s0);
              bulk_wait_all();
              announce(F_PART + W.slotA * LN_);
            }
            ko += bytes;
          }
          next_slot();
          if (tail) { next_slot(); next_slot(); }
        } else { flag_wait(F_W, ep1); fence_async_gmem(); }
        STAMP(true, 2, 5);
        const bool staged = total > 0 && !tail;
        w_load(staged, staged ? (fin ? 2 : 3) : 4);
#pragma unroll 1
        for (int i = 0; i < W.nloc; i++) {
          const int tl = W.loc0 + i, last = tl * 128 + 127 < NN ? tl * 128 + 127 : NN - 1;
          flag_wait(F_AGG + ((last >= NGW) + (last >= 4 * NGW) + (last >= 9 * NGW)) * LN_, ep1 * NGW); fence_async_gmem();
          if (total == 0) g_flag[F_EPOCH] = epoch + 1;
          q_load(g_agg + tl * 4096, total > 0 || i > 0);
        }
        if (tail) { mbar_wait(sb + B_BG, 0); mbar_wait(sb + B_EVP0 + 8, 0); mbar_arrive(sb + B_QFULL); }
        else if (fin) {
          int h = 0, c = 2, have = W.slotB >= 0 || (DBG & 8) ? 2 : 0;
          mbar_wait(sb + B_BG, 0);
#pragma unroll 1
          for (uint32_t it = 0; (h < 2 || c < 4) && it < (1u << 23); it++) {
            if (have < 2) {
              uint2 f;
              asm volatile("ld.relaxed.gpu.global.v2.u32 {%0,%1}, [%2];" : "=r"(f.x), "=r"(f.y) : "l"(g_flag + F_PART + W.slotA * LN_) : "memory");
              have = (int)(f.x - (epoch + 1)) < 0 ? 0 : ((int)(f.y - (epoch + 1)) < 0 ? 1 : 2);
            }
            if (h < have && mbar_try_wait_nb(sb + B_QEMPTY + 8 * h, 0)) {
              asm volatile("fence.acquire.gpu;" ::: "memory"); fence_async_gmem();
              STAMP(true, 2, 14 + h);
              mbar_expect_tx(sb + B_QFULL + 8 * h, 32768 + 512);
              bulk_g2s(sb + SM_ML + h * 512, g_ml + W.slotA * 128 + h * 64, 512, sb + B_QFULL + 8 * h);
              bulk_g2s(sb + SM_Q + h * 32768, g_part + W.slotA * 4096 + h * 2048, 32768, sb + B_QFULL + 8 * h);
              h++;
            }
            const bool half = mbar_try_wait_nb(sb + B_HALF, 0);
            const int c1 = half ? 4 : (h > 0 ? 3 : 2);
            if (c < c1) { w_load(c, c1); c = c1; }
          }
        } else if (total > 0) {
#pragma unroll 1
          for (int h = 0; h < 2; h++) part_out(W.slotB, h, (posw >> 12) + h, 1);
          asm volatile("cp.async.bulk.wait_group.read 1;" ::: "memory");
          w_load(3, 4);
          asm volatile("cp.async.bulk.wait_group 1;" ::: "memory");
          announce(F_PART + W.slotB * LN_);
          STAMP(true, 2, 14);
          bulk_wait_all();
          announce(F_PART + W.slotB * LN_ + 1);
          STAMP(true, 2, 15);
        }
        DUMP(true, 2, 14, 16);
        DUMP(true, 2, 0, 8);
      }
      return;
    }
  }
    {
      const int gw = cta * 3 + warp - 1;
      ROLE;
      if (total > 0) {
        mbar_wait_w(sb + B_EVQ, 0);
        const uint32_t c0 = clk();
        if (warp == 1 && (W.role & R_PUB)) {
          g_unsafe[W.q0] = lds32(sb + SM_UNSAFE);
#pragma unroll 1
          for (int k = 0; k < 4; k++) {
            __nanosleep(2000);
            if (lane == 0) bulk_s2g(pofs<uint4>(g_qp, W.q0 * 65536 + k * 16384), sb + SM_Q + k * 16384, 16384);
            bulk_commit();
          }
          bulk_wait_all();
          flag_release_w(F_QP + W.q0 * LN_);
        }
        while (__any_sync(0xffffffffu, clk() - c0 < GSTART)) __nanosleep(500);
        STAMP(lane == 0 && warp == 1, 2, 8);
#define ovf_cnt pofs<uint32_t>(g_flag, (F_OVF + (ep1 & 1) * LN_) * 4)
        if (gw == 0) g_flag[F_OVF + ((ep1 + 1) & 1) * LN_] = 0;
#pragma unroll 1
        for (int e0 = gw * 32; e0 < NE; e0 += NGW * 32 * 7) {
          int d[7], s[7], pos[7];
          const int* pd = pofs<const int>(P.dst, (e0 + lane) * 4);
          const int* ps = pofs<const int>(P.src, (e0 + lane) * 4);
#pragma unroll
          for (int k = 0; k < 7; k++) { const bool ok = e0 + k * NGW * 32 < NE; d[k] = ok ? (HINT & 1 ? __ldcs(pd + k * NGW * 32) : __ldg(pd + k * NGW * 32)) : -1; s[k] = ok ? (HINT & 1 ? __ldcs(ps + k * NGW * 32) : __ldg(ps + k * NGW * 32)) : 0; }
          uint32_t ov = 0;
#pragma unroll
          for (int k = 0; k < 7; k++) {
            pos[k] = 0;
            if (d[k] >= 0) asm volatile("atom.relaxed.gpu.global.add.u32 %0, [%1], 1;" : "=r"(pos[k]) : "l"(pofs<int>(g_cnt, d[k] << 2)) : "memory");
            s[k] = (uint32_t)(uintptr_t)g_u + s[k] * 512;
            if (d[k] >= 0 && pos[k] < CAP) asm volatile("st.volatile.global.u32 [%0], %1;" :: "l"(pofs<int>(g_bin, (d[k] * CAPS + pos[k]) << 2)), "r"(s[k]) : "memory");
            ov |= (pos[k] >= CAP) << k;
          }
          if (__any_sync(0xffffffffu, ov != 0)) {
            uint32_t at;
            asm volatile("atom.relaxed.gpu.global.add.u32 %0, [%1], %2;" : "=r"(at) : "l"(ovf_cnt), "r"(__popc(ov)) : "memory");
#pragma unroll
            for (int k = 0; k < 7; k++) if ((ov >> k) & 1) g_ovf[at++] = make_int2(d[k], s[k]);
          }
        }
        flag_wait_w(F_H, ep1 * NHSIG);
#pragma unroll 1
        for (int n0 = gw; n0 < NN; n0 += 4 * NGW) {
          uint4 xv[4]; float2 st[4];
#pragma unroll
          for (int k = 0; k < 4; k++) {
            const int n = n0 + k * NGW < NN ? n0 + k * NGW : n0;
            xv[k] = (HINT & 1 ? ldcs_v : ldcg_v)(pofs<const uint4>(P.x, n * 512 + lane * 16));
            st[k] = __ldcg(pofs<const float2>(g_stat, n * 8));
          }
#pragma unroll
          for (int k = 3; k >= 0; k--) {
            const int n = n0 + k * NGW;
            const float a = st[k].x * US, c = fmaf(st[k].y, US, UB + 8388608.0f);
#define FIX(w) __byte_perm(__float_as_uint(fmaf(bf_lo(w), a, c)), __float_as_uint(fmaf(bf_hi(w), a, c)), 0x5410)
            if (n < NN) {
              *pofs<uint4>(P.out, n * 512 + lane * 16) = xv[k];
              *pofs<uint4>(g_u, n * 512 + lane * 16) = make_uint4(FIX(xv[k].x), FIX(xv[k].y), FIX(xv[k].z), FIX(xv[k].w));
            }
          }
        }
        flag_release_w(F_BIN);
        STAMP(lane == 0 && warp == 1, 2, 9);
        flag_wait_w(F_BIN, ep1 * NGW);
        STAMP(lane == 0 && warp == 1, 2, 10);
        const int myn = gw + lane * NGW < NN ? gw + lane * NGW : gw;
        int cnts = __ldcg(g_cnt + myn);
        cnts = gw + lane * NGW < NN ? (cnts > CAP ? CAP + 1 : cnts) | ((int)__ldg((const unsigned short*)P.dinv + myn) << 16) : 0;
        __syncwarp();
        g_cnt[myn] = 0;
        const uint32_t uhi = (uintptr_t)g_u >> 32, lx = lane * 16;
        uint32_t obin = gw * CAPS * 4;
        uint32_t ent = __ldcg(pofs<const uint32_t>(g_bin, obin + lane * 4)), entn = __ldcg(pofs<const uint32_t>(g_bin, obin + NGW * CAPS * 4 + lane * 4));
        int cd = __shfl_sync(0xffffffffu, cnts, 0), cb = min(cd & 0xffff, CAP), e = 0;
        uint32_t sa[4] = {0, 0, 0, 0}, sh[4] = {0, 0, 0, 0};
        auto add = [&](uint32_t x, uint32_t y, uint32_t z, uint32_t w) {
          sa[0] += x; sa[1] += y; sa[2] += z; sa[3] += w;
          sh[0] += x >> 16; sh[1] += y >> 16; sh[2] += z >> 16; sh[3] += w >> 16;
        };
        int rnd = -1, rows = -1, cdo = 0;
#pragma unroll 1
        for (;;) {
          const bool hold = rows >= 0 && rnd == 8;
          const int m = hold ? 0 : cb - e;
          uint4 v[8];
          if (m >= 8) {
#pragma unroll
            for (int k = 0; k < 8; k++) v[k] = ldcg_v(addr64(__shfl_sync(0xffffffffu, ent, k) + lx, uhi));
          } else {
#pragma unroll
            for (int k = 0; k < 8; k++) {
              v[k] = make_uint4(0, 0, 0, 0);
              if (k < 7) ldcg_if(v[k], addr64(__shfl_sync(0xffffffffu, ent, k) + lx, uhi), k < m);
            }
          }
          if (rows >= 0) {
            const int n = gw + rnd * NGW;
            if (n < NN) {
              const float di = __uint_as_float(cdo & 0xffff0000u) * (1.0f / US), nl = -di * UB * (float)rows;
#define AGG(k) pack_bf16(fmaf((float)(sa[k] - (sh[k] << 16)), di, nl), fmaf((float)sh[k], di, nl))
              *pofs<uint4>(g_agg, ((n >> 3) * 4096 + (n & 7) * 144) ^ ((lx & 0x70) | ((lx & 0x180) << 3))) = make_uint4(AGG(0), AGG(1), AGG(2), AGG(3));
            }
#pragma unroll
            for (int k = 0; k < 4; k++) sa[k] = sh[k] = 0;
            rows = -1;
            if (rnd == 0 || rnd == 3 || rnd == 8 || rnd == NRND - 1) flag_release_w(F_AGG + ((rnd > 0) + (rnd > 3) + (rnd > 8)) * LN_);
            if (rnd == NRND - 1) break;
            if (hold) {
              if (fin && W.slotB >= 0) {
        #pragma unroll 1
                for (int k = 0; k < 2; k++) flag_wait_w(F_PART + (k ? W.slotB : W.slotA) * LN_, ep1);
        #pragma unroll 1
                for (int b = warp - 1; b < 8; b += 3) {
                  float2* ma = g_ml + W.slotA * 128 + b * 16 + g;
                  const float2* mb = g_ml + W.slotB * 128 + b * 16 + g;
                  const float2 a0 = __ldcg(ma), a1 = __ldcg(ma + 8), b0 = __ldcg(mb), b1 = __ldcg(mb + 8);
                  const float x0 = fmaxf(a0.x, b0.x), x1 = fmaxf(a1.x, b1.x);
                  const float fa0 = ex2(a0.x - x0), fa1 = ex2(a1.x - x1), fb0 = ex2(b0.x - x0), fb1 = ex2(b1.x - x1);
                  __syncwarp();
                  if (t == 0) { ma[0] = make_float2(x0, a0.y * fa0 + b0.y * fb0); ma[8] = make_float2(x1, a1.y * fa1 + b1.y * fb1); }
                  const uint32_t ofs = ((b >> 2) * 2048 + (b & 3) * 32 + lane) * 16;
        #pragma unroll 1
                  for (int u = 0; u < 16; u += 4) {
                    uint4* pa = pofs<uint4>(g_part, W.slotA * 65536 + ofs + u * 2048);
                    const uint4* pb = pofs<const uint4>(g_part, W.slotB * 65536 + ofs + u * 2048);
                    uint4 va[4], vb[4];
        #pragma unroll
                    for (int k = 0; k < 4; k++) { va[k] = ldcg_v(pa + k * 128); vb[k] = (HINT & 2 ? ldcs_v : ldcg_v)(pb + k * 128); }
        #define FOLD(w, fa, fb) pack_bf16(bf_lo(va[k].w) * fa + bf_lo(vb[k].w) * fb, bf_hi(va[k].w) * fa + bf_hi(vb[k].w) * fb)
        #pragma unroll
                    for (int k = 3; k >= 0; k--) pa[k * 128] = make_uint4(FOLD(x, fa0, fb0), FOLD(y, fa1, fb1), FOLD(z, fa0, fb0), FOLD(w, fa1, fb1));
                  }
                }
                bar_sync(3, 96);
                if (warp == 1) asm volatile("fence.acq_rel.gpu;" ::: "memory");
              }
              if (fin && warp == 1 && lane == 0) mbar_arrive(sb + B_BG);
              while (__any_sync(0xffffffffu, clk() - c0 < GPAUSE)) __nanosleep(500);
              continue;
            }
          }
#define SUM8(f) (v[7].f + v[6].f + v[5].f + v[4].f + v[3].f + v[2].f + v[1].f + v[0].f)
          add(SUM8(x), SUM8(y), SUM8(z), SUM8(w));
          e += 8;
          if (e < cb) {
            ent = __shfl_down_sync(0xffffffffu, ent, 8);
            if (e == 32) ent = __ldcg(pofs<const uint32_t>(g_bin, obin + 128 + lx / 4));
            continue;
          }
          rnd++; rows = cb; cdo = cd;
          if ((cd & 0xffff) > CAP) {
            const int no = __shfl_sync(0xffffffffu, (int)ld_relaxed(ovf_cnt), 0);
#pragma unroll 1
            for (int i0 = 0; i0 < no; i0 += 32) {
              int2 en = __ldcg(g_ovf + min(i0 + lane, no - 1));
              uint32_t mk = __ballot_sync(0xffffffffu, en.x == gw + rnd * NGW && i0 + lane < no);
              rows += __popc(mk);
#pragma unroll 1
              while (mk) {
                const int bit = __ffs(mk) - 1; mk &= mk - 1;
                const uint4 r = ldcg_v(addr64((uint32_t)__shfl_sync(0xffffffffu, en.y, bit) + lx, uhi));
                add(r.x, r.y, r.z, r.w);
              }
            }
          }
          obin += NGW * CAPS * 4;
          ent = entn; entn = __ldcg(pofs<const uint32_t>(g_bin, obin + NGW * CAPS * 4 + lx / 4));
          cd = __shfl_sync(0xffffffffu, cnts, rnd + 1); cb = min(cd & 0xffff, CAP); e = 0;
        }
      }
      STAMP(lane == 0 && warp == 1, 2, 11);
      if ((HINT & 4) && warp == 2 && fin && lane == 0) {
        prefetch_l2(pofs<uint8_t>(P.out, W.q0 * 65536), tail ? 8192 : 65536);
        if (W.slotB >= 0) prefetch_l2(pofs<uint8_t>(g_part, W.slotA * 65536), 65536);
        prefetch_l2(pofs<uint8_t>(g_Wvo, (cta & 63) * 4096), 4096);
      }
      DUMP(warp == 1 && lane == 0, 2, 8, 14);
    }
}

}

extern "C" void kernel_launch(void* const* d_in, const int* in_sizes, int n_in, void* d_out, int out_size) {
  Params P;
  P.x = (const __nv_bfloat16*)d_in[0];
  P.src = (const int*)d_in[1];
  P.dst = (const int*)d_in[2];
  P.dinv = (const __nv_bfloat16*)d_in[3];
  P.wmsg = (const __nv_bfloat16*)d_in[4];
  P.wq = (const __nv_bfloat16*)d_in[5];
  P.wk = (const __nv_bfloat16*)d_in[6];
  P.wv = (const __nv_bfloat16*)d_in[7];
  P.wout = (const __nv_bfloat16*)d_in[8];
  P.out = (__nv_bfloat16*)d_out;
  P.zero = 0;
  for (int c = 0; c < NCTA; c++) P.w[c] = make_work(c);
  static void* scr = nullptr;
  if (!scr) {
    cudaFuncSetAttribute(gps_kernel, cudaFuncAttributeMaxDynamicSharedMemorySize, SMEM_BYTES);
    cudaGetSymbolAddress(&scr, g_scr);
  }
  P.s = (Scratch*)((((uintptr_t)scr + SCR_ALIGN - 1) & ~(uintptr_t)(SCR_ALIGN - 1)) + SCR_OFS);
  P.u = (uint4*)(((uintptr_t)P.s->u + 511) & ~(uintptr_t)511);
  if (((uintptr_t)P.u >> 32) != (((uintptr_t)(P.u + NN * 32) - 1) >> 32)) P.u += NN * 32;
  gps_kernel<<<NCTA, 384, SMEM_BYTES>>>(P);
}
```

```cpp
#include <cuda_runtime.h>
#include <cuda_bf16.h>
#include <stdint.h>
#include <stddef.h>
#include <type_traits>
#define FB 5
#define MB 5
#define GSTART 18000
#define HINT 7
#define RELF 0
#define DBG 0
#define OUTW red_bf16x8
#define XD 2
#define PACE 64
#define GPAUSE 120000
#define XDELAY 200
#define CREG 224
#define BACKOFF 1000

namespace {

constexpr int NN = 10000;
constexpr int NE = 160000;
constexpr int NQT = 79;
constexpr int NCTA = 132;
constexpr int CAP = 64;
constexpr int CAPS = 64;
constexpr int NHSIG = 105;
constexpr uint32_t WCH_B = 32768;
constexpr int NGW = (NCTA - 1) * 3;
constexpr float TAU = 16.0f;
constexpr float SAFE_N2 = 36.0f, SAFE_C = 0.6f;
#define KOFF 3
#define PSH -8.0f
#define KROT 15
constexpr float US = 256.0f, UB = 4095.0f;
constexpr float KS = 0.25f, KC = KOFF * KS;
constexpr uint32_t KS2 = 0x3e803e80u, KC2 = KOFF == 2 ? 0x3f003f00u : (KOFF == 1 ? 0x3e803e80u : 0x3f403f40u);

constexpr int NAGG = 4;
constexpr int NRND = (NN + NGW - 1) / NGW;
constexpr int NSLOT = 105;
constexpr int F_EPOCH = 0, F_H = 1, F_M = 4  , F_H1 = 8  , LN_ = 32;
constexpr int F_BIN = LN_, F_W = 2 * LN_, F_OVF = 3 * LN_  , F_QP = 5 * LN_, F_AGG = F_QP + NQT * LN_,
              F_PART = F_AGG + NAGG * LN_, F_END = F_PART + NSLOT * LN_;

struct Scratch {
  uint32_t flag[F_END];
  alignas(4096) uint4 M[8192];
  uint4 Wvo[8192], Wmo[8192];
  float2 ml[NSLOT * 128];
  uint32_t unsafe[96];
  int cnt[NN + 32];
  float2 stat[NQT * 128];
  alignas(4096) uint4 h[NQT * 4096];
  uint4 u[2 * NN * 32 + 32];
  uint4 qp[NQT * 4096];
  uint4 agg[NQT * 4096];
  uint4 part[NSLOT * 4096];
  int bin[(NRND + 2) * NGW * CAPS];
  int2 ovf[NE];
};
static_assert(offsetof(Scratch, h) % 128 == 0, "alignment");
#define SCR_ALIGN (2u << 20)
#define SCR_OFS 0
__device__ uint4 g_scr[(sizeof(Scratch) + SCR_ALIGN + SCR_OFS) / 16];
struct alignas(16) Work { short k0, k1; signed char q0, hp, nb0, na0, nb1, na1, slotA, slotB, loc0, nloc, own, role; };
constexpr int R_FIN = 1, R_PUB = 2, R_TAIL = 4, R_SIG = 8  ;
struct Params {
  const __nv_bfloat16 *x, *wq, *wk;
  Scratch* s;
  uint4* u;
  __nv_bfloat16* out;
  const __nv_bfloat16 *wout, *wmsg, *wv, *dinv;
  const int *src, *dst;
  long long zero;
  Work w[NCTA];
};
constexpr int first_cnt(int k) { return 2 * ((k + 6) / 8 - k / 8 + 1); }
constexpr int NH1_0 = 2, NH1_1 = first_cnt(48 * 8 - MB), NH1_2 = first_cnt(48 * 8 - MB + 16 * 8 - (15 - MB) / 2);
constexpr int NSERV = NQT - 52;
inline Work make_work(int c) {
  Work w;
  const int gi = c / 5, r = c % 5, q = gi * 3;
  const bool helper = r & 1, mid = r == 2;
  w.q0 = helper ? q + 1 : q + (r >> 1);
  const int hb1 = (15 - MB) / 2, hb3 = 15 - MB - hb1;
  w.nb0 = helper ? (r == 1 ? hb1 : hb3) : (mid ? MB : FB);
  w.na0 = (helper ? 16 : 48) - w.nb0;
  w.k0 = helper ? (48 * 8 - MB) + (r >> 1) * (16 * 8 - hb1) : 0;
  w.k1 = 48 * 8 - FB;
  w.nb1 = helper ? (FB < 7 ? 7 : 15) - FB : 0;
  w.na1 = helper ? (FB < 7 ? 31 : 32) - w.nb1 : 0;
  w.slotA = 4 * gi + (helper ? r - 1 : (mid ? 0 : (r >> 1) + 1));
  w.slotB = helper ? 4 * gi + r : (mid ? 4 * gi + 2 : -1);
  w.loc0 = NSERV + gi * 2 + (r >> 1);
  w.nloc = helper;
  w.own = helper ? (r + 1) >> 1 : (mid ? 0 : 3);
  w.role = helper ? 0 : (mid ? R_FIN : R_FIN | R_PUB);
  const int k1st[3] = {0, 48 * 8 - MB, 48 * 8 - MB + 16 * 8 - hb1};
  int pos[NQT], sig[NQT];
  for (int i = 0; i < NQT; i++) { pos[i] = i; sig[i] = 0; }
  for (int i = 0; i < 3; i++)
    for (int p = k1st[i] / 8; p <= (k1st[i] + 6) / 8; p++) {
      int m = 1, at = 0;
      while (sig[m]) m += 3;
      while (pos[at] != p) at++;
      pos[at] = pos[m]; pos[m] = p; sig[m] = 1 + i;
    }
  w.hp = c < 131 ? pos[w.q0] : 0;
  if (helper && c < 130) w.role |= sig[w.q0] * R_SIG;
  if (c == 130) { w.nb0 = 15; w.na0 = 65; w.slotA = NSLOT - 1; w.own = 1; w.role = R_FIN | R_TAIL; }
  if (c == 131) { w.nb0 = w.na0 = w.nb1 = w.na1 = 0; w.loc0 = 0; w.nloc = NSERV; w.own = 0; }
  return w;
}
#define g_flag P.s->flag
#define g_M P.s->M
#define g_Wvo P.s->Wvo
#define g_Wmo P.s->Wmo
#define g_ml P.s->ml
#define g_unsafe P.s->unsafe
#define g_cnt P.s->cnt
#define g_h P.s->h
#define g_u P.u
#define g_stat P.s->stat
#define g_qp P.s->qp
#define g_agg P.s->agg
#define g_part P.s->part
#define g_bin P.s->bin
#define g_ovf P.s->ovf

__device__ __forceinline__ uint32_t smem_u32(const void* p) { return (uint32_t)__cvta_generic_to_shared(p); }
__device__ __forceinline__ void mbar_init(uint32_t bar, uint32_t cnt) { asm volatile("mbarrier.init.shared::cta.b64 [%0], %1;" :: "r"(bar), "r"(cnt) : "memory"); }
__device__ __forceinline__ void mbar_arrive(uint32_t bar) { asm volatile("mbarrier.arrive.shared::cta.b64 _, [%0];" :: "r"(bar) : "memory"); }
__device__ __forceinline__ void mbar_expect_tx(uint32_t bar, uint32_t bytes) { asm volatile("mbarrier.arrive.expect_tx.shared::cta.b64 _, [%0], %1;" :: "r"(bar), "r"(bytes) : "memory"); }
__device__ __forceinline__ bool mbar_try_wait(uint32_t bar, uint32_t parity) {
  uint32_t ok;
  asm volatile("{\n.reg .pred p;\nmbarrier.try_wait.parity.shared::cta.b64 p, [%1], %2;\nselp.b32 %0, 1, 0, p;\n}\n" : "=r"(ok) : "r"(bar), "r"(parity) : "memory");
  return ok;
}
__device__ __forceinline__ bool mbar_try_wait_nb(uint32_t bar, uint32_t parity) {
  uint32_t ok;
  asm volatile("{\n.reg .pred p;\nmbarrier.test_wait.parity.shared::cta.b64 p, [%1], %2;\nselp.b32 %0, 1, 0, p;\n}\n" : "=r"(ok) : "r"(bar), "r"(parity) : "memory");
  return ok;
}
__device__ __forceinline__ void mbar_wait(uint32_t bar, uint32_t parity) {
#pragma unroll 1
  for (uint32_t it = 0; it < (1u << 25); it++) if (mbar_try_wait(bar, parity)) break;
}
__device__ __forceinline__ void bulk_s2g(void* dst, uint32_t src, uint32_t bytes) {
  asm volatile("cp.async.bulk.global.shared::cta.bulk_group [%0], [%1], %2;" :: "l"(dst), "r"(src), "r"(bytes) : "memory");
}
__device__ __forceinline__ void bulk_commit() { asm volatile("cp.async.bulk.commit_group;" ::: "memory"); }
__device__ __forceinline__ void bulk_wait_read() { asm volatile("cp.async.bulk.wait_group.read 0;" ::: "memory"); }
__device__ __forceinline__ void bulk_wait_all() { asm volatile("cp.async.bulk.wait_group 0;" ::: "memory"); }
__device__ __forceinline__ bool bar_red_or(int id, int cnt, bool c) {
  uint32_t r;
  asm volatile("{\n.reg .pred p, q;\nsetp.ne.b32 q, %3, 0;\nbar.red.or.pred p, %1, %2, q;\nselp.b32 %0, 1, 0, p;\n}\n"
               : "=r"(r) : "r"(id), "r"(cnt), "r"((uint32_t)c) : "memory");
  return r != 0;
}
template <class T> __device__ __forceinline__ T* pofs(const void* base, uint32_t off) {
  asm volatile("" : "+r"(off));
  return (T*)((uint8_t*)base + off);
}
__device__ __forceinline__ const void* addr64(uint32_t lo, uint32_t hi) { uint64_t a; asm("mov.b64 %0, {%1, %2};" : "=l"(a) : "r"(lo), "r"(hi)); return (const void*)a; }
__device__ __forceinline__ uint4 ldcg_v(const void* a) {
  uint4 v;
  asm volatile("ld.volatile.global.v4.u32 {%0,%1,%2,%3}, [%4];" : "=r"(v.x), "=r"(v.y), "=r"(v.z), "=r"(v.w) : "l"(a) : "memory");
  return v;
}
__device__ __forceinline__ uint4 ldcs_v(const void* a) {
  uint4 v;
  asm volatile("ld.global.cs.v4.u32 {%0,%1,%2,%3}, [%4];" : "=r"(v.x), "=r"(v.y), "=r"(v.z), "=r"(v.w) : "l"(a) : "memory");
  return v;
}
__device__ __forceinline__ void prefetch_l2(const void* a, uint32_t bytes) { asm volatile("cp.async.bulk.prefetch.L2.global [%0], %1;" :: "l"(a), "r"(bytes) : "memory"); }
__device__ __forceinline__ void ldcg_if(uint4& v, const void* a, bool c) {
  asm volatile("{\n.reg .pred p;\nsetp.ne.b32 p, %5, 0;\n@p ld.volatile.global.v4.u32 {%0,%1,%2,%3}, [%4];\n}\n"
               : "+r"(v.x), "+r"(v.y), "+r"(v.z), "+r"(v.w) : "l"(a), "r"((uint32_t)c) : "memory");
}
__device__ __forceinline__ void cp_async16(uint32_t dst, const void* src) {
  asm volatile("cp.async.cg.shared.global [%0], [%1], 16;" :: "r"(dst), "l"(src) : "memory");
}
__device__ __forceinline__ void red_bf16x8(void* a, uint4 v) {
  asm volatile("red.global.add.noftz.v4.bf16x2 [%0], {%1,%2,%3,%4};" :: "l"(a), "r"(v.x), "r"(v.y), "r"(v.z), "r"(v.w) : "memory");
}
__device__ __forceinline__ uint32_t clk() { uint32_t c; asm volatile("mov.u32 %0, %%clock;" : "=r"(c) :: "memory"); return c; }
__device__ __forceinline__ void stsm4(uint32_t a, uint32_t r0, uint32_t r1, uint32_t r2, uint32_t r3) {
  asm volatile("stmatrix.sync.aligned.m8n8.x4.shared.b16 [%0], {%1,%2,%3,%4};" :: "r"(a), "r"(r0), "r"(r1), "r"(r2), "r"(r3) : "memory");
}
__device__ __forceinline__ void ldsm4(uint32_t a, uint32_t& r0, uint32_t& r1, uint32_t& r2, uint32_t& r3) {
  asm volatile("ldmatrix.sync.aligned.m8n8.x4.shared.b16 {%0,%1,%2,%3}, [%4];" : "=r"(r0), "=r"(r1), "=r"(r2), "=r"(r3) : "r"(a) : "memory");
}
__device__ __forceinline__ void red_relaxed(uint32_t* p) { asm volatile("red.relaxed.gpu.global.add.u32 [%0], 1;" :: "l"(p) : "memory"); }
__device__ __forceinline__ uint32_t lds32(uint32_t a) { uint32_t v; asm volatile("ld.shared.u32 %0, [%1];" : "=r"(v) : "r"(a) : "memory"); return v; }
__device__ __forceinline__ void cp_commit() { asm volatile("cp.async.commit_group;" ::: "memory"); }
__device__ __forceinline__ uint32_t hmul2(uint32_t a, uint32_t b) { uint32_t d; asm("mul.rn.bf16x2 %0, %1, %2;" : "=r"(d) : "r"(a), "r"(b)); return d; }
__device__ __forceinline__ uint32_t hfma2(uint32_t a, uint32_t b, uint32_t c) { uint32_t d; asm("fma.rn.bf16x2 %0, %1, %2, %3;" : "=r"(d) : "r"(a), "r"(b), "r"(c)); return d; }
__device__ __forceinline__ uint32_t pow2_bf2(int n) { return (uint32_t)max(n + 127, 0) * 0x00800080u; }
__device__ __forceinline__ int fexp(float x) { return (int)(__float_as_uint(x) >> 23) - 127; }
__device__ __forceinline__ void bulk_g2s(uint32_t dst, const void* src, uint32_t bytes, uint32_t bar) {
  asm volatile("cp.async.bulk.shared::cta.global.mbarrier::complete_tx::bytes [%0], [%1], %2, [%3];"
    :: "r"(dst), "l"(src), "r"(bytes), "r"(bar) : "memory");
}
__device__ __forceinline__ void bulk_g2s_last(uint32_t dst, const void* src, uint32_t bytes, uint32_t bar) {
  asm volatile("{\n.reg .b64 p;\ncreatepolicy.fractional.L2::evict_first.b64 p;\n"
    "cp.async.bulk.shared::cta.global.mbarrier::complete_tx::bytes.L2::cache_hint [%0], [%1], %2, [%3], p;\n}\n"
    :: "r"(dst), "l"(src), "r"(bytes), "r"(bar) : "memory");
}
__device__ __forceinline__ void wg_fence() { asm volatile("wgmma.fence.sync.aligned;" ::: "memory"); }
__device__ __forceinline__ void wg_commit() { asm volatile("wgmma.commit_group.sync.aligned;" ::: "memory"); }
template<int N> __device__ __forceinline__ void wg_wait() { asm volatile("wgmma.wait_group.sync.aligned %0;" :: "n"(N) : "memory"); }
__device__ __forceinline__ void bar_sync(int id, int cnt) { asm volatile("bar.sync %0, %1;" :: "r"(id), "r"(cnt) : "memory"); }
__device__ __forceinline__ void fence_async_smem() { asm volatile("fence.proxy.async.shared::cta;" ::: "memory"); }
__device__ __forceinline__ void fence_async_gmem() { asm volatile("fence.proxy.async.global;" ::: "memory"); }
__device__ __forceinline__ void bar_arrive(int id, int cnt) { asm volatile("bar.arrive %0, %1;" :: "r"(id), "r"(cnt) : "memory"); }
__device__ __forceinline__ void red_release(uint32_t* p) { asm volatile("red.release.gpu.global.add.u32 [%0], 1;" :: "l"(p) : "memory"); }
__device__ __forceinline__ void red_release_w(uint32_t* p) {
  __syncwarp();
  asm volatile("{\n.reg .pred q;\n.reg .b32 l;\nmov.u32 l, %%laneid;\nsetp.eq.u32 q, l, 0;\n@q fence.release.gpu;\n@q red.relaxed.gpu.global.add.u32 [%0], 1;\n}\n" :: "l"(p) : "memory");
}
__device__ __forceinline__ void mbar_wait_w(uint32_t bar, uint32_t parity) {
#pragma unroll 1
  for (uint32_t it = 0; it < (1u << 25); it++) if (__all_sync(0xffffffffu, mbar_try_wait(bar, parity))) break;
}
#define flag_release_w(f) red_release_w(g_flag + (f))
#define flag_wait_w(f, target) poll_acquire_w(g_flag + (f), target)
#define flag_release(f) red_release(g_flag + (f))
__device__ __forceinline__ uint32_t ld_relaxed(const uint32_t* p) {
  uint32_t v; asm volatile("ld.relaxed.gpu.global.u32 %0, [%1];" : "=r"(v) : "l"(p) : "memory"); return v;
}
#define flag_wait(f, target) poll_acquire(g_flag + (f), target)
__device__ __forceinline__ void poll_acquire(const uint32_t* p, uint32_t target) {
#pragma unroll 1
  for (uint32_t it = 0; it < (1u << 23); it++) if ((int)(ld_relaxed(p) - target) >= 0) break;
  asm volatile("fence.acquire.gpu;" ::: "memory");
}
__device__ __forceinline__ void poll_acquire_w(const uint32_t* p, uint32_t target) {
#pragma unroll 1
  for (uint32_t it = 0; it < (1u << 23); it++) {
    if (__all_sync(0xffffffffu, (int)(ld_relaxed(p) - target) >= 0)) break;
    if (BACKOFF) __nanosleep(BACKOFF);
  }
  asm volatile("fence.acquire.gpu;" ::: "memory");
}
template<int N> __device__ __forceinline__ void reg_fence(float (&d)[N]) {
#pragma unroll
  for (int i = 0; i < N; i++) asm volatile("" : "+f"(d[i]) :: "memory");
}
template<int N> __device__ __forceinline__ void reg_fence(uint32_t (&d)[N]) {
#pragma unroll
  for (int i = 0; i < N; i++) asm volatile("" : "+r"(d[i]) :: "memory");
}
__device__ __forceinline__ float ex2(float x) { float y; asm("ex2.approx.ftz.f32 %0, %1;" : "=f"(y) : "f"(x)); return y; }
__device__ __forceinline__ uint32_t pack_bf16(float lo, float hi) { uint32_t r; asm("cvt.rn.bf16x2.f32 %0, %1, %2;" : "=r"(r) : "f"(hi), "f"(lo)); return r; }
__device__ __forceinline__ float bf_lo(uint32_t w) { return __uint_as_float(w << 16); }
__device__ __forceinline__ float bf_hi(uint32_t w) { return __uint_as_float(w & 0xffff0000u); }
__device__ __forceinline__ uint64_t desc_k(uint32_t addr, uint32_t add) { return (uint64_t)((((addr & 0x3FFFF) >> 4) | (1u << 16)) + add) | (0x40000100ull << 32); }
__device__ __forceinline__ uint64_t desc_mn(uint32_t addr, uint32_t add) { return (uint64_t)((((addr & 0x3FFFF) >> 4) | ((1024u >> 4) << 16)) + add) | (0x40000100ull << 32); }
__device__ __forceinline__ void sts128(uint32_t a, uint4 v) { asm volatile("st.shared.v4.u32 [%0], {%1,%2,%3,%4};" :: "r"(a), "r"(v.x), "r"(v.y), "r"(v.z), "r"(v.w) : "memory"); }
__device__ __forceinline__ uint4 lds128(uint32_t a) { uint4 v; asm volatile("ld.shared.v4.u32 {%0,%1,%2,%3}, [%4];" : "=r"(v.x), "=r"(v.y), "=r"(v.z), "=r"(v.w) : "r"(a) : "memory"); return v; }
__device__ __forceinline__ void mma16816(float (&c)[4], uint32_t a0, uint32_t a1, uint32_t a2, uint32_t a3, uint32_t b0, uint32_t b1) {
  asm volatile("mma.sync.aligned.m16n8k16.row.col.f32.bf16.bf16.f32 {%0,%1,%2,%3}, {%4,%5,%6,%7}, {%8,%9}, {%0,%1,%2,%3};"
    : "+f"(c[0]), "+f"(c[1]), "+f"(c[2]), "+f"(c[3]) : "r"(a0), "r"(a1), "r"(a2), "r"(a3), "r"(b0), "r"(b1));
}
__device__ __forceinline__ uint32_t sw_byte(int r, int c) {
  return (uint32_t)((r >> 3) * 4096 + (c >> 6) * 1024 + (r & 7) * 128 + ((((c >> 3) & 7) ^ (r & 7)) << 4) + (c & 7) * 2);
}
__device__ __forceinline__ int cta_id() { int c; asm volatile("mov.u32 %0, %%ctaid.x;" : "=r"(c)); return c; }
__device__ __forceinline__ bool tid_is(int v) { int t; asm volatile("mov.u32 %0, %%tid.x;" : "=r"(t)); return t == v; }
#define STAMP(cond, who, i)
#define CSTAMP(cond, who, i)
#define DUMP(cond, who, i0, i1)
#define XSTAMP(cond, i)
#define SSTAMP(i)

template <int OA, int OB> __device__ __forceinline__ void wgmma_ss_n256_tb(float (&d)[128], uint64_t da, uint64_t db, int scale_d) {
  asm volatile("{\n.reg .pred p;\n.reg .b64 a, b;\nsetp.ne.b32 p, %130, 0;\nadd.s64 a, %128, %131;\nadd.s64 b, %129, %132;\n"
    "wgmma.mma_async.sync.aligned.m64n256k16.f32.bf16.bf16 "
    "{%0, %1, %2, %3, %4, %5, %6, %7, %8, %9, %10, %11, %12, %13, %14, %15, %16, %17, %18, %19, %20, %21, %22, %23, %24, %25, %26, %27, %28, %29, %30, %31, %32, %33, %34, %35, %36, %37, %38, %39, %40, %41, %42, %43, %44, %45, %46, %47, %48, %49, %50, %51, %52, %53, %54, %55, %56, %57, %58, %59, %60, %61, %62, %63, %64, %65, %66, %67, %68, %69, %70, %71, %72, %73, %74, %75, %76, %77, %78, %79, %80, %81, %82, %83, %84, %85, %86, %87, %88, %89, %90, %91, %92, %93, %94, %95, %96, %97, %98, %99, %100, %101, %102, %103, %104, %105, %106, %107, %108, %109, %110, %111, %112, %113, %114, %115, %116, %117, %118, %119, %120, %121, %122, %123, %124, %125, %126, %127}, "
    "a, b, p, 1, 1, 0, 1;\n}\n"
    : "+f"(d[0]), "+f"(d[1]), "+f"(d[2]), "+f"(d[3]), "+f"(d[4]), "+f"(d[5]), "+f"(d[6]), "+f"(d[7]), "+f"(d[8]), "+f"(d[9]), "+f"(d[10]), "+f"(d[11]), "+f"(d[12]), "+f"(d[13]), "+f"(d[14]), "+f"(d[15]), "+f"(d[16]), "+f"(d[17]), "+f"(d[18]), "+f"(d[19]), "+f"(d[20]), "+f"(d[21]), "+f"(d[22]), "+f"(d[23]), "+f"(d[24]), "+f"(d[25]), "+f"(d[26]), "+f"(d[27]), "+f"(d[28]), "+f"(d[29]), "+f"(d[30]), "+f"(d[31]), "+f"(d[32]), "+f"(d[33]), "+f"(d[34]), "+f"(d[35]), "+f"(d[36]), "+f"(d[37]), "+f"(d[38]), "+f"(d[39]), "+f"(d[40]), "+f"(d[41]), "+f"(d[42]), "+f"(d[43]), "+f"(d[44]), "+f"(d[45]), "+f"(d[46]), "+f"(d[47]), "+f"(d[48]), "+f"(d[49]), "+f"(d[50]), "+f"(d[51]), "+f"(d[52]), "+f"(d[53]), "+f"(d[54]), "+f"(d[55]), "+f"(d[56]), "+f"(d[57]), "+f"(d[58]), "+f"(d[59]), "+f"(d[60]), "+f"(d[61]), "+f"(d[62]), "+f"(d[63]), "+f"(d[64]), "+f"(d[65]), "+f"(d[66]), "+f"(d[67]), "+f"(d[68]), "+f"(d[69]), "+f"(d[70]), "+f"(d[71]), "+f"(d[72]), "+f"(d[73]), "+f"(d[74]), "+f"(d[75]), "+f"(d[76]), "+f"(d[77]), "+f"(d[78]), "+f"(d[79]), "+f"(d[80]), "+f"(d[81]), "+f"(d[82]), "+f"(d[83]), "+f"(d[84]), "+f"(d[85]), "+f"(d[86]), "+f"(d[87]), "+f"(d[88]), "+f"(d[89]), "+f"(d[90]), "+f"(d[91]), "+f"(d[92]), "+f"(d[93]), "+f"(d[94]), "+f"(d[95]), "+f"(d[96]), "+f"(d[97]), "+f"(d[98]), "+f"(d[99]), "+f"(d[100]), "+f"(d[101]), "+f"(d[102]), "+f"(d[103]), "+f"(d[104]), "+f"(d[105]), "+f"(d[106]), "+f"(d[107]), "+f"(d[108]), "+f"(d[109]), "+f"(d[110]), "+f"(d[111]), "+f"(d[112]), "+f"(d[113]), "+f"(d[114]), "+f"(d[115]), "+f"(d[116]), "+f"(d[117]), "+f"(d[118]), "+f"(d[119]), "+f"(d[120]), "+f"(d[121]), "+f"(d[122]), "+f"(d[123]), "+f"(d[124]), "+f"(d[125]), "+f"(d[126]), "+f"(d[127])
    : "l"(da), "l"(db), "r"(scale_d), "n"(OA), "n"(OB));
}
template <int OA, int OB> __device__ __forceinline__ void wgmma_qk(float (&d)[64], uint64_t da, uint64_t db, int scale_d) {
  asm volatile("{\n.reg .pred p;\n.reg .b64 a, b;\nsetp.ne.b32 p, %66, 0;\nadd.s64 a, %64, %67;\nadd.s64 b, %65, %68;\n"
    "wgmma.mma_async.sync.aligned.m64n128k16.f32.bf16.bf16 "
    "{%0, %1, %2, %3, %4, %5, %6, %7, %8, %9, %10, %11, %12, %13, %14, %15, %16, %17, %18, %19, %20, %21, %22, %23, %24, %25, %26, %27, %28, %29, %30, %31, %32, %33, %34, %35, %36, %37, %38, %39, %40, %41, %42, %43, %44, %45, %46, %47, %48, %49, %50, %51, %52, %53, %54, %55, %56, %57, %58, %59, %60, %61, %62, %63}, "
    "a, b, p, 1, 1, 0, 0;\n}\n"
    : "+f"(d[0]), "+f"(d[1]), "+f"(d[2]), "+f"(d[3]), "+f"(d[4]), "+f"(d[5]), "+f"(d[6]), "+f"(d[7]), "+f"(d[8]), "+f"(d[9]), "+f"(d[10]), "+f"(d[11]), "+f"(d[12]), "+f"(d[13]), "+f"(d[14]), "+f"(d[15]), "+f"(d[16]), "+f"(d[17]), "+f"(d[18]), "+f"(d[19]), "+f"(d[20]), "+f"(d[21]), "+f"(d[22]), "+f"(d[23]), "+f"(d[24]), "+f"(d[25]), "+f"(d[26]), "+f"(d[27]), "+f"(d[28]), "+f"(d[29]), "+f"(d[30]), "+f"(d[31]), "+f"(d[32]), "+f"(d[33]), "+f"(d[34]), "+f"(d[35]), "+f"(d[36]), "+f"(d[37]), "+f"(d[38]), "+f"(d[39]), "+f"(d[40]), "+f"(d[41]), "+f"(d[42]), "+f"(d[43]), "+f"(d[44]), "+f"(d[45]), "+f"(d[46]), "+f"(d[47]), "+f"(d[48]), "+f"(d[49]), "+f"(d[50]), "+f"(d[51]), "+f"(d[52]), "+f"(d[53]), "+f"(d[54]), "+f"(d[55]), "+f"(d[56]), "+f"(d[57]), "+f"(d[58]), "+f"(d[59]), "+f"(d[60]), "+f"(d[61]), "+f"(d[62]), "+f"(d[63])
    : "l"(da), "l"(db), "r"(scale_d), "n"(OA), "n"(OB));
}
template <int OA, int OB> __device__ __forceinline__ void wgmma_qk(float (&d)[56], uint64_t da, uint64_t db, int scale_d) {
  asm volatile("{\n.reg .pred p;\n.reg .b64 a, b;\nsetp.ne.b32 p, %58, 0;\nadd.s64 a, %56, %59;\nadd.s64 b, %57, %60;\n"
    "wgmma.mma_async.sync.aligned.m64n112k16.f32.bf16.bf16 "
    "{%0, %1, %2, %3, %4, %5, %6, %7, %8, %9, %10, %11, %12, %13, %14, %15, %16, %17, %18, %19, %20, %21, %22, %23, %24, %25, %26, %27, %28, %29, %30, %31, %32, %33, %34, %35, %36, %37, %38, %39, %40, %41, %42, %43, %44, %45, %46, %47, %48, %49, %50, %51, %52, %53, %54, %55}, "
    "a, b, p, 1, 1, 0, 0;\n}\n"
    : "+f"(d[0]), "+f"(d[1]), "+f"(d[2]), "+f"(d[3]), "+f"(d[4]), "+f"(d[5]), "+f"(d[6]), "+f"(d[7]), "+f"(d[8]), "+f"(d[9]), "+f"(d[10]), "+f"(d[11]), "+f"(d[12]), "+f"(d[13]), "+f"(d[14]), "+f"(d[15]), "+f"(d[16]), "+f"(d[17]), "+f"(d[18]), "+f"(d[19]), "+f"(d[20]), "+f"(d[21]), "+f"(d[22]), "+f"(d[23]), "+f"(d[24]), "+f"(d[25]), "+f"(d[26]), "+f"(d[27]), "+f"(d[28]), "+f"(d[29]), "+f"(d[30]), "+f"(d[31]), "+f"(d[32]), "+f"(d[33]), "+f"(d[34]), "+f"(d[35]), "+f"(d[36]), "+f"(d[37]), "+f"(d[38]), "+f"(d[39]), "+f"(d[40]), "+f"(d[41]), "+f"(d[42]), "+f"(d[43]), "+f"(d[44]), "+f"(d[45]), "+f"(d[46]), "+f"(d[47]), "+f"(d[48]), "+f"(d[49]), "+f"(d[50]), "+f"(d[51]), "+f"(d[52]), "+f"(d[53]), "+f"(d[54]), "+f"(d[55])
    : "l"(da), "l"(db), "r"(scale_d), "n"(OA), "n"(OB));
}
template <int OB> __device__ __forceinline__ void wgmma_rs_n256_tb(float (&d)[128], uint32_t a0, uint32_t a1, uint32_t a2, uint32_t a3, uint64_t db, int scale_d) {
  asm volatile("{\n.reg .pred p;\n.reg .b64 b;\nsetp.ne.b32 p, %133, 0;\nadd.s64 b, %132, %134;\n"
    "wgmma.mma_async.sync.aligned.m64n256k16.f32.bf16.bf16 "
    "{%0, %1, %2, %3, %4, %5, %6, %7, %8, %9, %10, %11, %12, %13, %14, %15, %16, %17, %18, %19, %20, %21, %22, %23, %24, %25, %26, %27, %28, %29, %30, %31, %32, %33, %34, %35, %36, %37, %38, %39, %40, %41, %42, %43, %44, %45, %46, %47, %48, %49, %50, %51, %52, %53, %54, %55, %56, %57, %58, %59, %60, %61, %62, %63, %64, %65, %66, %67, %68, %69, %70, %71, %72, %73, %74, %75, %76, %77, %78, %79, %80, %81, %82, %83, %84, %85, %86, %87, %88, %89, %90, %91, %92, %93, %94, %95, %96, %97, %98, %99, %100, %101, %102, %103, %104, %105, %106, %107, %108, %109, %110, %111, %112, %113, %114, %115, %116, %117, %118, %119, %120, %121, %122, %123, %124, %125, %126, %127}, "
    "{%128, %129, %130, %131}, b, p, 1, 1, 1;\n}\n"
    : "+f"(d[0]), "+f"(d[1]), "+f"(d[2]), "+f"(d[3]), "+f"(d[4]), "+f"(d[5]), "+f"(d[6]), "+f"(d[7]), "+f"(d[8]), "+f"(d[9]), "+f"(d[10]), "+f"(d[11]), "+f"(d[12]), "+f"(d[13]), "+f"(d[14]), "+f"(d[15]), "+f"(d[16]), "+f"(d[17]), "+f"(d[18]), "+f"(d[19]), "+f"(d[20]), "+f"(d[21]), "+f"(d[22]), "+f"(d[23]), "+f"(d[24]), "+f"(d[25]), "+f"(d[26]), "+f"(d[27]), "+f"(d[28]), "+f"(d[29]), "+f"(d[30]), "+f"(d[31]), "+f"(d[32]), "+f"(d[33]), "+f"(d[34]), "+f"(d[35]), "+f"(d[36]), "+f"(d[37]), "+f"(d[38]), "+f"(d[39]), "+f"(d[40]), "+f"(d[41]), "+f"(d[42]), "+f"(d[43]), "+f"(d[44]), "+f"(d[45]), "+f"(d[46]), "+f"(d[47]), "+f"(d[48]), "+f"(d[49]), "+f"(d[50]), "+f"(d[51]), "+f"(d[52]), "+f"(d[53]), "+f"(d[54]), "+f"(d[55]), "+f"(d[56]), "+f"(d[57]), "+f"(d[58]), "+f"(d[59]), "+f"(d[60]), "+f"(d[61]), "+f"(d[62]), "+f"(d[63]), "+f"(d[64]), "+f"(d[65]), "+f"(d[66]), "+f"(d[67]), "+f"(d[68]), "+f"(d[69]), "+f"(d[70]), "+f"(d[71]), "+f"(d[72]), "+f"(d[73]), "+f"(d[74]), "+f"(d[75]), "+f"(d[76]), "+f"(d[77]), "+f"(d[78]), "+f"(d[79]), "+f"(d[80]), "+f"(d[81]), "+f"(d[82]), "+f"(d[83]), "+f"(d[84]), "+f"(d[85]), "+f"(d[86]), "+f"(d[87]), "+f"(d[88]), "+f"(d[89]), "+f"(d[90]), "+f"(d[91]), "+f"(d[92]), "+f"(d[93]), "+f"(d[94]), "+f"(d[95]), "+f"(d[96]), "+f"(d[97]), "+f"(d[98]), "+f"(d[99]), "+f"(d[100]), "+f"(d[101]), "+f"(d[102]), "+f"(d[103]), "+f"(d[104]), "+f"(d[105]), "+f"(d[106]), "+f"(d[107]), "+f"(d[108]), "+f"(d[109]), "+f"(d[110]), "+f"(d[111]), "+f"(d[112]), "+f"(d[113]), "+f"(d[114]), "+f"(d[115]), "+f"(d[116]), "+f"(d[117]), "+f"(d[118]), "+f"(d[119]), "+f"(d[120]), "+f"(d[121]), "+f"(d[122]), "+f"(d[123]), "+f"(d[124]), "+f"(d[125]), "+f"(d[126]), "+f"(d[127])
    : "r"(a0), "r"(a1), "r"(a2), "r"(a3), "l"(db), "r"(scale_d), "n"(OB));
}
template <int OB> __device__ __forceinline__ void wgmma_rs_n256_tb_first(float (&d)[128], uint32_t a0, uint32_t a1, uint32_t a2, uint32_t a3, uint64_t db) {
  asm volatile("{\n.reg .pred p;\n.reg .b64 b;\nsetp.ne.b32 p, 0, 0;\nadd.s64 b, %132, %133;\n"
    "wgmma.mma_async.sync.aligned.m64n256k16.f32.bf16.bf16 "
    "{%0, %1, %2, %3, %4, %5, %6, %7, %8, %9, %10, %11, %12, %13, %14, %15, %16, %17, %18, %19, %20, %21, %22, %23, %24, %25, %26, %27, %28, %29, %30, %31, %32, %33, %34, %35, %36, %37, %38, %39, %40, %41, %42, %43, %44, %45, %46, %47, %48, %49, %50, %51, %52, %53, %54, %55, %56, %57, %58, %59, %60, %61, %62, %63, %64, %65, %66, %67, %68, %69, %70, %71, %72, %73, %74, %75, %76, %77, %78, %79, %80, %81, %82, %83, %84, %85, %86, %87, %88, %89, %90, %91, %92, %93, %94, %95, %96, %97, %98, %99, %100, %101, %102, %103, %104, %105, %106, %107, %108, %109, %110, %111, %112, %113, %114, %115, %116, %117, %118, %119, %120, %121, %122, %123, %124, %125, %126, %127}, "
    "{%128, %129, %130, %131}, b, p, 1, 1, 1;\n}\n"
    : "=f"(d[0]), "=f"(d[1]), "=f"(d[2]), "=f"(d[3]), "=f"(d[4]), "=f"(d[5]), "=f"(d[6]), "=f"(d[7]), "=f"(d[8]), "=f"(d[9]), "=f"(d[10]), "=f"(d[11]), "=f"(d[12]), "=f"(d[13]), "=f"(d[14]), "=f"(d[15]), "=f"(d[16]), "=f"(d[17]), "=f"(d[18]), "=f"(d[19]), "=f"(d[20]), "=f"(d[21]), "=f"(d[22]), "=f"(d[23]), "=f"(d[24]), "=f"(d[25]), "=f"(d[26]), "=f"(d[27]), "=f"(d[28]), "=f"(d[29]), "=f"(d[30]), "=f"(d[31]), "=f"(d[32]), "=f"(d[33]), "=f"(d[34]), "=f"(d[35]), "=f"(d[36]), "=f"(d[37]), "=f"(d[38]), "=f"(d[39]), "=f"(d[40]), "=f"(d[41]), "=f"(d[42]), "=f"(d[43]), "=f"(d[44]), "=f"(d[45]), "=f"(d[46]), "=f"(d[47]), "=f"(d[48]), "=f"(d[49]), "=f"(d[50]), "=f"(d[51]), "=f"(d[52]), "=f"(d[53]), "=f"(d[54]), "=f"(d[55]), "=f"(d[56]), "=f"(d[57]), "=f"(d[58]), "=f"(d[59]), "=f"(d[60]), "=f"(d[61]), "=f"(d[62]), "=f"(d[63]), "=f"(d[64]), "=f"(d[65]), "=f"(d[66]), "=f"(d[67]), "=f"(d[68]), "=f"(d[69]), "=f"(d[70]), "=f"(d[71]), "=f"(d[72]), "=f"(d[73]), "=f"(d[74]), "=f"(d[75]), "=f"(d[76]), "=f"(d[77]), "=f"(d[78]), "=f"(d[79]), "=f"(d[80]), "=f"(d[81]), "=f"(d[82]), "=f"(d[83]), "=f"(d[84]), "=f"(d[85]), "=f"(d[86]), "=f"(d[87]), "=f"(d[88]), "=f"(d[89]), "=f"(d[90]), "=f"(d[91]), "=f"(d[92]), "=f"(d[93]), "=f"(d[94]), "=f"(d[95]), "=f"(d[96]), "=f"(d[97]), "=f"(d[98]), "=f"(d[99]), "=f"(d[100]), "=f"(d[101]), "=f"(d[102]), "=f"(d[103]), "=f"(d[104]), "=f"(d[105]), "=f"(d[106]), "=f"(d[107]), "=f"(d[108]), "=f"(d[109]), "=f"(d[110]), "=f"(d[111]), "=f"(d[112]), "=f"(d[113]), "=f"(d[114]), "=f"(d[115]), "=f"(d[116]), "=f"(d[117]), "=f"(d[118]), "=f"(d[119]), "=f"(d[120]), "=f"(d[121]), "=f"(d[122]), "=f"(d[123]), "=f"(d[124]), "=f"(d[125]), "=f"(d[126]), "=f"(d[127])
    : "r"(a0), "r"(a1), "r"(a2), "r"(a3), "l"(db), "n"(OB));
}
template <int OB> __device__ __forceinline__ void wgmma_rs_n128_tb(float (&d)[64], uint32_t a0, uint32_t a1, uint32_t a2, uint32_t a3, uint64_t db, int scale_d) {
  asm volatile("{\n.reg .pred p;\n.reg .b64 b;\nsetp.ne.b32 p, %69, 0;\nadd.s64 b, %68, %70;\n"
    "wgmma.mma_async.sync.aligned.m64n128k16.f32.bf16.bf16 "
    "{%0, %1, %2, %3, %4, %5, %6, %7, %8, %9, %10, %11, %12, %13, %14, %15, %16, %17, %18, %19, %20, %21, %22, %23, %24, %25, %26, %27, %28, %29, %30, %31, %32, %33, %34, %35, %36, %37, %38, %39, %40, %41, %42, %43, %44, %45, %46, %47, %48, %49, %50, %51, %52, %53, %54, %55, %56, %57, %58, %59, %60, %61, %62, %63}, "
    "{%64, %65, %66, %67}, b, p, 1, 1, 1;\n}\n"
    : "+f"(d[0]), "+f"(d[1]), "+f"(d[2]), "+f"(d[3]), "+f"(d[4]), "+f"(d[5]), "+f"(d[6]), "+f"(d[7]), "+f"(d[8]), "+f"(d[9]), "+f"(d[10]), "+f"(d[11]), "+f"(d[12]), "+f"(d[13]), "+f"(d[14]), "+f"(d[15]), "+f"(d[16]), "+f"(d[17]), "+f"(d[18]), "+f"(d[19]), "+f"(d[20]), "+f"(d[21]), "+f"(d[22]), "+f"(d[23]), "+f"(d[24]), "+f"(d[25]), "+f"(d[26]), "+f"(d[27]), "+f"(d[28]), "+f"(d[29]), "+f"(d[30]), "+f"(d[31]), "+f"(d[32]), "+f"(d[33]), "+f"(d[34]), "+f"(d[35]), "+f"(d[36]), "+f"(d[37]), "+f"(d[38]), "+f"(d[39]), "+f"(d[40]), "+f"(d[41]), "+f"(d[42]), "+f"(d[43]), "+f"(d[44]), "+f"(d[45]), "+f"(d[46]), "+f"(d[47]), "+f"(d[48]), "+f"(d[49]), "+f"(d[50]), "+f"(d[51]), "+f"(d[52]), "+f"(d[53]), "+f"(d[54]), "+f"(d[55]), "+f"(d[56]), "+f"(d[57]), "+f"(d[58]), "+f"(d[59]), "+f"(d[60]), "+f"(d[61]), "+f"(d[62]), "+f"(d[63])
    : "r"(a0), "r"(a1), "r"(a2), "r"(a3), "l"(db), "r"(scale_d), "n"(OB));
}
template <int V> using IC = std::integral_constant<int, V>;
template <int I, int N, class F> __device__ __forceinline__ void static_for(F&& f) {
  if constexpr (I < N) { f(std::integral_constant<int, I>{}); static_for<I + 1, N>(f); }
}

constexpr uint32_t SM_Q = 0, SM_BAR = 7 * 32768;
constexpr uint32_t B_FULL = SM_BAR, B_EMPTY = B_FULL + 24, B_WF = B_EMPTY + 24, B_QFULL = B_WF + 32, B_QEMPTY = B_QFULL + 16,
                   B_EVH = B_QEMPTY + 16, B_EVQ = B_EVH + 8, B_EVP0 = B_EVQ + 8, B_BG = B_EVP0 + 16, B_M0 = B_BG + 8, B_HALF = B_M0 + 8,
                   B_HRD = B_HALF + 8, SM_UNSAFE = B_HRD + 8, SM_TS = SM_UNSAFE + 8, SM_ML = (SM_TS + 192 + 15) / 16 * 16, SM_EPOCH = SM_ML + 1024, SM_END = SM_EPOCH + 16;
constexpr uint32_t POS_M = 0x5462;
constexpr int SMEM_BYTES = SM_END;

#define ROW0(u) make_uint4(pack_bf16(o[16 * u], o[16 * u + 1]), pack_bf16(o[16 * u + 4], o[16 * u + 5]), \
                           pack_bf16(o[16 * u + 8], o[16 * u + 9]), pack_bf16(o[16 * u + 12], o[16 * u + 13]))
#define ROW1(u) make_uint4(pack_bf16(o[16 * u + 2], o[16 * u + 3]), pack_bf16(o[16 * u + 6], o[16 * u + 7]), \
                           pack_bf16(o[16 * u + 10], o[16 * u + 11]), pack_bf16(o[16 * u + 14], o[16 * u + 15]))

__global__ void __launch_bounds__(384, 1) gps_kernel(const __grid_constant__ Params P) {
  extern __shared__ __align__(1024) uint8_t smem_raw[];
  constexpr uint32_t sb = 1024;
  if (smem_u32(smem_raw) != sb) return;
  const int cta = blockIdx.x;
  const int wg = __shfl_sync(0xffffffffu, (int)threadIdx.x >> 7, 0);
  const int warp = __shfl_sync(0xffffffffu, ((int)threadIdx.x >> 5) & 3, 0);
  const int lane = threadIdx.x & 31;
#define ROLE                                                                                       \
  const Work& W = P.w[cta_id()];                                                                   \
  [[maybe_unused]] const int n0 = W.nb0 + W.na0, n1 = W.nb1 + W.na1, total = n0 + n1;              \
  [[maybe_unused]] const bool fin = W.role & R_FIN, tail = W.role & R_TAIL;                        \
  [[maybe_unused]] const uint32_t posw = total == 0 || tail ? POS_M : ((total & 1) ? 0x2546 : 0x4326)
  const int g = lane >> 2, t = lane & 3;
  if (wg < 2) {
    const int tid = threadIdx.x & 127;
    ROLE;
    const uint32_t sQ = sb + SM_Q + wg * 32768;
#define st0 tid_is(wg * 128)
    STAMP(st0, wg, 0);
    const int rr = lane >> 3, j = lane & 7;
    const uint32_t c0 = clk();
    while (clk() - c0 < XDELAY) {}
    const uint4* px[4];
#pragma unroll
    for (int i = 0; i < 4; i++) px[i] = (const uint4*)(P.x + (size_t)min(W.q0 * 128 + wg * 64 + warp * 16 + i * 4 + rr, NN - 1) * 256) + j;
    auto x_load = [&](int c) {
      if (c < 4) {
#pragma unroll
        for (int i = 0; i < 4; i++)
          cp_async16(sQ + warp * 8192 + (i >> 1) * 4096 + c * 1024 + ((i & 1) * 4 + rr) * 128 + ((j ^ ((i & 1) * 4 + rr)) << 4), px[i] + c * 8);
      }
      cp_commit();
    };
    if (total > 0) {
#pragma unroll
      for (int c = 0; c < XD; c++) x_load(c);
    }
    bar_sync(4, 384);
    if (wg == 1) bar_arrive(5, 256);

    const uint32_t sF = sQ + warp * 8192 + ((lane >> 3) & 1) * 4096 + (lane & 7) * 128;
    auto frag = [&](int k) { return sF + (k >> 2) * 1024 + ((((k & 3) * 2 + (lane >> 4)) ^ (lane & 7)) << 4); };
    uint32_t hq[64];
    const bool own = (W.own >> wg) & 1;
    if (total > 0) {
      float c1[4] = {0.f, 0.f, 0.f, 0.f}, ca[4] = {0.f, 0.f, 0.f, 0.f}, cb[4] = {0.f, 0.f, 0.f, 0.f};
#pragma unroll
      for (int k = 0; k < 16; k++) {
        if ((k & 3) == 0) {
          asm volatile("cp.async.wait_group %0;" :: "n"(XD - 1) : "memory");
          __syncwarp();
          x_load(k / 4 + XD);
        }
        ldsm4(frag(k), hq[4 * k], hq[4 * k + 1], hq[4 * k + 2], hq[4 * k + 3]);
        mma16816(c1, hq[4 * k], hq[4 * k + 1], hq[4 * k + 2], hq[4 * k + 3], 0x3f803f80u, 0x3f803f80u);
        mma16816(ca, hq[4 * k], hq[4 * k + 1], hq[4 * k + 2], hq[4 * k + 3], hq[4 * k], hq[4 * k + 2]);
        mma16816(cb, hq[4 * k], hq[4 * k + 1], hq[4 * k + 2], hq[4 * k + 3], hq[4 * k + 1], hq[4 * k + 3]);
      }
      const float mu0 = c1[0] * (1.0f / 256.0f), mu1 = c1[2] * (1.0f / 256.0f);
      const float v0 = fmaf(__shfl_sync(0xffffffffu, g & 1 ? ca[1] : ca[0], g * 4 + (g >> 1)), 1.0f / 256.0f, 1e-5f - mu0 * mu0);
      const float v1 = fmaf(__shfl_sync(0xffffffffu, g & 1 ? cb[3] : cb[2], g * 4 + (g >> 1)), 1.0f / 256.0f, 1e-5f - mu1 * mu1);
      float rs0, rs1;
      asm("rsqrt.approx.ftz.f32 %0, %1;" : "=f"(rs0) : "f"(v0)); asm("rsqrt.approx.ftz.f32 %0, %1;" : "=f"(rs1) : "f"(v1));
      if (W.q0 * 128 + wg * 64 + warp * 16 >= NN) rs0 = rs1 = 0.f;
      float nb0 = -mu0 * rs0, nb1 = -mu1 * rs1;
      const uint32_t sS = sb + SM_ML + (wg * 64 + warp * 16) * 8;
      if (t == 0) {
        asm volatile("st.shared.v2.f32 [%0], {%1,%2};" :: "r"(sS + g * 8), "f"(rs0), "f"(nb0) : "memory");
        asm volatile("st.shared.v2.f32 [%0], {%1,%2};" :: "r"(sS + g * 8 + 64), "f"(rs1), "f"(nb1) : "memory");
      }
      if (__any_sync(0xffffffffu, !(4.f * mu0 * mu0 <= v0) || !(4.f * mu1 * mu1 <= v1))) {
#pragma unroll 1
        for (int r = 0; r < 16; r++) {
          const uint32_t ad = sQ + warp * 8192 + (r >> 3) * 4096 + rr * 1024 + (r & 7) * 128 + ((j ^ (r & 7)) << 4);
          const uint4 v = lds128(ad);
          float f[8] = {bf_lo(v.x), bf_hi(v.x), bf_lo(v.y), bf_hi(v.y), bf_lo(v.z), bf_hi(v.z), bf_lo(v.w), bf_hi(v.w)};
          float sum = 0.f, ss = 0.f, rs;
#pragma unroll
          for (int i = 0; i < 8; i++) sum += f[i];
#pragma unroll 1
          for (int k = 1; k < 32; k *= 2) sum += __shfl_xor_sync(0xffffffffu, sum, k);
          sum *= 1.0f / 256.0f;
#pragma unroll
          for (int i = 0; i < 8; i++) { f[i] -= sum; ss += f[i] * f[i]; }
#pragma unroll 1
          for (int k = 1; k < 32; k *= 2) ss += __shfl_xor_sync(0xffffffffu, ss, k);
          asm("rsqrt.approx.ftz.f32 %0, %1;" : "=f"(rs) : "f"(fmaf(ss, 1.0f / 256.0f, 1e-5f)));
          if (W.q0 * 128 + wg * 64 + warp * 16 >= NN) rs = 0.f;
          sts128(ad, make_uint4(pack_bf16(f[0] * rs, f[1] * rs), pack_bf16(f[2] * rs, f[3] * rs), pack_bf16(f[4] * rs, f[5] * rs), pack_bf16(f[6] * rs, f[7] * rs)));
          if (lane == 0) asm volatile("st.shared.v2.f32 [%0], {%1,%2};" :: "r"(sS + r * 8), "f"(rs), "f"(-sum * rs) : "memory");
        }
        __syncwarp();
#pragma unroll
        for (int k = 0; k < 16; k++) ldsm4(frag(k), hq[4 * k], hq[4 * k + 1], hq[4 * k + 2], hq[4 * k + 3]);
        rs0 = rs1 = 1.f; nb0 = nb1 = 0.f;
      }
      asm volatile("setmaxnreg.inc.sync.aligned.u32 %0;" :: "n"(CREG));
      const uint32_t ah0 = pack_bf16(rs0, rs0), ah1 = pack_bf16(rs1, rs1), n0_ = pack_bf16(nb0, nb0), n1_ = pack_bf16(nb1, nb1);
      const uint32_t al0 = pack_bf16(rs0 - bf_lo(ah0), rs0 - bf_lo(ah0)), al1 = pack_bf16(rs1 - bf_lo(ah1), rs1 - bf_lo(ah1));
#pragma unroll
      for (int i = 0; i < 32; i++) {
        hq[2 * i] = hfma2(hq[2 * i], ah0, hfma2(hq[2 * i], al0, n0_));
        hq[2 * i + 1] = hfma2(hq[2 * i + 1], ah1, hfma2(hq[2 * i + 1], al1, n1_));
      }
      if (own) {
        const float e0 = fmaf(bf_hi(__shfl_sync(0xffffffffu, hq[62], lane | 3)), -0.5f * KS, KC), e1 = fmaf(bf_hi(__shfl_sync(0xffffffffu, hq[63], lane | 3)), -0.5f * KS, KC);
#pragma unroll
        for (int k = 0; k < 16; k++)
          stsm4(frag(k), hfma2(hq[4 * k], KS2, KC2), hfma2(hq[4 * k + 1], KS2, KC2),
                k < 15 ? hfma2(hq[4 * k + 2], KS2, KC2) : pack_bf16(fmaf(bf_lo(hq[62]), KS, e0), t == 3 ? KC : fmaf(bf_hi(hq[62]), KS, e0)),
                k < 15 ? hfma2(hq[4 * k + 3], KS2, KC2) : pack_bf16(fmaf(bf_lo(hq[63]), KS, e1), t == 3 ? KC : fmaf(bf_hi(hq[63]), KS, e1)));
      }
      __syncwarp();
      if (lane == 0) mbar_arrive(sb + B_EVH);
    } else {
      asm volatile("setmaxnreg.inc.sync.aligned.u32 %0;" :: "n"(CREG));
    }
    STAMP(st0, wg, 1);

    float o[128];
    int qph = 0, st = tail ? wg : 0, ph = 0;
    auto release = [&](int stg) { if (lane == 0) mbar_arrive(sb + B_EMPTY + 8 * stg); };
    int resume = total > 0 ? -1 : 0;
    auto fill = [&]() __attribute__((always_inline)) {
#pragma unroll
      for (int i = 0; i < 32; i++)
        asm volatile("ld.volatile.shared.v4.f32 {%0,%1,%2,%3}, [%4];" : "=f"(o[4 * i]), "=f"(o[4 * i + 1]), "=f"(o[4 * i + 2]), "=f"(o[4 * i + 3]) : "r"(sb) : "memory");
    };
    auto finish = [&]() __attribute__((always_inline)) {
      STAMP(st0, wg, 11);
      DUMP(st0, wg, 0, 16);
      if (!P.zero) { asm volatile("exit;"); __builtin_unreachable(); }
      fill();
    };
    auto run = [&](auto hot_) __attribute__((always_inline)) {
    constexpr bool HOT = hot_.value;
    const int nloc = P.w[cta_id()].nloc;
    if (!HOT && resume == 0) {
#pragma unroll 1
      for (int i = 0; i < 32; i++) {
        const int r = i * 8 + wg * 4 + warp;
        cp_async16(sb + ((POS_M >> (r >> 6) * 4) & 15) * 32768 + sw_byte(r & 63, lane * 8), (const uint4*)P.wout + r * 32 + lane);
      }
    }
    bool wide = false;
    if (HOT) {
      reg_fence(hq);
      auto qstep = [&](auto k_) {
        constexpr int k = k_.value;
        if (k < 2 || k % 4 == 0) { mbar_wait(k == 0 ? sb + B_M0 : sb + B_WF + 2 * (k & ~3), 0); if (k == 0 || k == 4) bar_sync(5 + wg, 256); wg_fence(); }
        if constexpr (k == 0) wgmma_rs_n256_tb_first<0>(o, hq[0], hq[1], hq[2], hq[3], desc_mn(sb, (POS_M & 15) * 2048));
        else wgmma_rs_n256_tb<(k & 3) * 512>(o, hq[4 * k], hq[4 * k + 1], hq[4 * k + 2], hq[4 * k + 3], desc_mn(sb, ((POS_M >> (k & ~3)) & 15) * 2048), 1);
      };
      static_for<0, 4>(qstep);
      wg_commit();
      bar_arrive(6 - wg, 256);
      wg_wait<0>();
      if (!tail) release(0);
      static_for<4, 16>(qstep);
      wg_commit();
      bar_arrive(6 - wg, 256);
      wg_wait<0>();
      reg_fence(o); reg_fence(hq);
      if (!tail) release(1);
      STAMP(st0, wg, 2);
      float c0 = (o[124] + (t == 3 ? 2.f : 1.f) * o[125]) * (-0.5f / 4.5f), c1 = (o[126] + (t == 3 ? 2.f : 1.f) * o[127]) * (-0.5f / 4.5f);
      c0 += __shfl_xor_sync(0xffffffffu, c0, 1); c1 += __shfl_xor_sync(0xffffffffu, c1, 1);
      c0 += __shfl_xor_sync(0xffffffffu, c0, 2); c1 += __shfl_xor_sync(0xffffffffu, c1, 2);
      float r0 = t == 3 ? 0.f : o[125], r1 = t == 3 ? 0.f : o[127], r2 = o[124], r3 = o[126];
#pragma unroll
      for (int i = 0; i < 31; i++) { r2 += o[4 * i]; r0 += o[4 * i + 1]; r3 += o[4 * i + 2]; r1 += o[4 * i + 3]; }
      r0 += r2; r1 += r3;
      r0 += __shfl_xor_sync(0xffffffffu, r0, 1); r1 += __shfl_xor_sync(0xffffffffu, r1, 1);
      r0 += __shfl_xor_sync(0xffffffffu, r0, 2); r1 += __shfl_xor_sync(0xffffffffu, r1, 2);
      r0 = fmaf(c0, -255.f, PSH / KC - r0); r1 = fmaf(c1, -255.f, PSH / KC - r1);
      wide = !(fabsf(c0) <= SAFE_C / KS) || !(fabsf(c1) <= SAFE_C / KS);
      if (own) mbar_wait(sb + B_HRD, 0);
#pragma unroll
      for (int k = 0; k < 16; k++)
        stsm4(frag(k),
              pack_bf16(o[8 * k] + c0, o[8 * k + 1] + c0), pack_bf16(o[8 * k + 2] + c1, o[8 * k + 3] + c1),
              pack_bf16(o[8 * k + 4] + c0, k == 15 && t == 3 ? r0 : o[8 * k + 5] + c0), pack_bf16(o[8 * k + 6] + c1, k == 15 && t == 3 ? r1 : o[8 * k + 7] + c1));
      fence_async_smem();
      __syncwarp();
      STAMP(st0, wg, 3);
      if (tail) { bar_sync(7, 256); if (wg == 0) { release(0); release(1); release(2); } }
      }

    if (HOT || resume) {
      ROLE;
      float m0, m1;
      const int qh = tail ? 0 : wg, tl = tail;
      uint32_t qo = qh * 2048;
      const uint32_t ko = (2 - tl) * 2048, stop = 1 + tl + (uint32_t)P.zero;
      float l0, l1;
      auto row_sums = [&]() { l0 = __shfl_sync(0xffffffffu, o[125] + 0.f, lane | 3); l1 = __shfl_sync(0xffffffffu, o[127] + 0.f, lane | 3); };
#define PART(u) make_uint4(pack_bf16(o[8 * u] - l0, o[8 * u + 1] - l0), pack_bf16(o[8 * u + 2] - l1, o[8 * u + 3] - l1), \
                           pack_bf16(o[8 * u + 4] - l0, o[8 * u + 5] - l0), pack_bf16(o[8 * u + 6] - l1, o[8 * u + 7] - l1))
      bool unsafe = !HOT;
      m0 = m1 = 0.f;
#pragma unroll 1
      for (int seg = HOT ? 0 : resume - 1; seg < 2; seg++) {
        ROLE;
        const bool last = __any_sync(0xffffffffu, seg || n1 == 0);
        m0 = m1 = !HOT && unsafe ? -INFINITY : 0.f;
        int first = 1;
        auto tile = [&](auto n_, bool endseg) __attribute__((always_inline)) -> bool {
          constexpr int N = n_.value;
          float s[N / 2]; uint32_t p[N / 4];
          if (!mbar_try_wait(sb + B_FULL + 8 * st, ph)) mbar_wait(sb + B_FULL + 8 * st, ph);
          const bool again = !HOT && N == 112 && first && !seg;
          if (HOT || N == 128) bar_sync(5 + wg, 256);
          else asm volatile("{\n.reg .pred p;\nsetp.eq.u32 p, %1, 0;\n@p bar.sync %0, 256;\n}\n" :: "r"(5 + wg), "r"((uint32_t)again) : "memory");
          wg_fence();
          const uint64_t dQ = desc_k(sb + SM_Q, qo), dK = desc_k(sb, ko + st * 4096);
          qo += (uint32_t)P.zero;
          static_for<0, 16>([&](auto k) { constexpr int kk = (k.value + KROT) & 15, off = (kk >> 2) * 64 + (kk & 3) * 2; wgmma_qk<off, off>(s, dQ, dK, k.value > 0); });
          wg_commit();
          if (HOT || N == 128) bar_arrive(6 - wg, 256);
          else asm volatile("{\n.reg .pred p;\nsetp.eq.u32 p, %1, 0;\n@p bar.arrive %0, 256;\n}\n" :: "r"(6 - wg), "r"((uint32_t)again) : "memory");
          if (HOT && N == 112 && first && !seg) {
            float a0 = 0.f, a1 = 0.f, a2 = 0.f, a3 = 0.f;
#pragma unroll
            for (int i = 0; i < 32; i++) { a0 += o[4 * i] * o[4 * i]; a2 += o[4 * i + 1] * o[4 * i + 1]; a1 += o[4 * i + 2] * o[4 * i + 2]; a3 += o[4 * i + 3] * o[4 * i + 3]; }
            a0 += a2; a1 += a3;
            a0 += __shfl_xor_sync(0xffffffffu, a0, 1); a1 += __shfl_xor_sync(0xffffffffu, a1, 1);
            a0 += __shfl_xor_sync(0xffffffffu, a0, 2); a1 += __shfl_xor_sync(0xffffffffu, a1, 2);
            unsafe = __any_sync(0xffffffffu, bar_red_or(tail ? 7 : 1 + wg, tail ? 256 : 128, wide || !(a0 <= SAFE_N2 / (KS * KS)) || !(a1 <= SAFE_N2 / (KS * KS))));
            if (lane == 0) { asm volatile("st.shared.u8 [%0], %1;" :: "r"(sb + SM_UNSAFE + wg), "r"((uint32_t)unsafe) : "memory"); mbar_arrive(sb + B_EVQ); }
          }
          STAMP(N == 112 && first && !seg && st0, wg, 0);
          wg_wait<0>();
          reg_fence(s);
          if (HOT && N == 112 && unsafe) return true;
          if (endseg) { if (lane == 0) mbar_arrive(sb + B_QEMPTY + 8 * wg); }
          if (!HOT && unsafe) {
            float a0 = fmaxf(s[0], s[1]), a1 = fmaxf(s[2], s[3]);
#pragma unroll
            for (int i = 1; i < N / 8; i++) { a0 = fmaxf(a0, fmaxf(s[4 * i], s[4 * i + 1])); a1 = fmaxf(a1, fmaxf(s[4 * i + 2], s[4 * i + 3])); }
            if (__any_sync(0xffffffffu, (a0 > m0 + TAU) || (a1 > m1 + TAU))) {
              a0 = fmaxf(a0, __shfl_xor_sync(0xffffffffu, a0, 1)); a1 = fmaxf(a1, __shfl_xor_sync(0xffffffffu, a1, 1));
              a0 = fmaxf(a0, __shfl_xor_sync(0xffffffffu, a0, 2)); a1 = fmaxf(a1, __shfl_xor_sync(0xffffffffu, a1, 2));
              const float x0 = ceilf(fmaxf(m0, a0)), x1 = ceilf(fmaxf(m1, a1)), sc0 = ex2(m0 - x0), sc1 = ex2(m1 - x1);
              m0 = x0; m1 = x1;
#pragma unroll
              for (int i = 0; i < 32; i++) { o[4 * i] *= sc0; o[4 * i + 1] *= sc0; o[4 * i + 2] *= sc1; o[4 * i + 3] *= sc1; }
            }
#pragma unroll
            for (int i = 0; i < N / 8; i++) { s[4 * i] -= m0; s[4 * i + 1] -= m0; s[4 * i + 2] -= m1; s[4 * i + 3] -= m1; }
          }
          auto pv = [&](auto k) { wgmma_rs_n256_tb<k.value * 512 + (63 << 16)>(o, p[4 * k.value], p[4 * k.value + 1], p[4 * k.value + 2], p[4 * k.value + 3], dK, k.value > 0 || N == 128 ? 1 : !first); };
#pragma unroll
          for (int i = 0; i < 16; i++) { p[i] = pack_bf16(ex2(s[2 * i]), ex2(s[2 * i + 1])); asm volatile("" : "+r"(p[i]) :: "memory"); }
          reg_fence(o);
          do bar_sync(5 + wg, 256); while (P.zero);
          wg_fence();
          static_for<0, 4>(pv);
          wg_commit();
#pragma unroll
          for (int i = 16; i < N / 4; i++) { p[i] = pack_bf16(ex2(s[2 * i]), ex2(s[2 * i + 1])); asm volatile("" : "+r"(p[i]) :: "memory"); }
          wg_fence();
          static_for<4, N / 16>(pv);
          wg_commit();
          bar_arrive(6 - wg, 256);
          if (N == 128) { wg_wait<1>(); if (endseg && last) { if (lane == 0) mbar_arrive(sb + B_HALF); } }
          wg_wait<0>();
          reg_fence(o); reg_fence(p);
          release(st);
          if (st) { st--; ph ^= 1; } else st = stop;
          return false;
        };
#pragma unroll 1
        for (int left = tail ? 8 - wg : (seg ? W.nb1 : W.nb0); left > 0; left--) { if (tile(IC<112>{}, false)) { resume = 1; return; } STAMP(first && !seg && st0, wg, 4); first = 0; }
#pragma unroll 1
        for (int left = tail ? 32 + wg : (seg ? W.na1 : W.na0); left > 0; left--) tile(IC<128>{}, left == 1);
        STAMP(st0 && last, wg, 6);
        {
        ROLE;
        if (last && fin && !(tail && wg == 1)) break;
        row_sums();
        if (last) mbar_wait(sb + (tail ? B_QEMPTY : B_HALF), 0);
        const uint32_t sp = sb + (tail ? 0 : (last ? (posw >> 12) + wg : (wg ? 4 - 2 * st : 6))) * 32768, sm = sb + SM_ML + (tail ? 0 : wg) * 512;
#pragma unroll
        for (int u = 0; u < 16; u++) sts128(sp + (u * 128 + tid) * 16, PART(u));
        if (t == 0) {
          asm volatile("st.shared.v2.f32 [%0], {%1,%2};" :: "r"(sm + (warp * 16 + g) * 8), "f"(m0), "f"(l0) : "memory");
          asm volatile("st.shared.v2.f32 [%0], {%1,%2};" :: "r"(sm + (warp * 16 + g) * 8 + 64), "f"(m1), "f"(l1) : "memory");
        }
        __syncwarp();
        if (lane == 0) mbar_arrive(sb + B_EVP0 + 8 * wg);
        STAMP(st0 && last, wg, 7);
        if (last) break;
        mbar_wait(sb + B_QFULL + 8 * wg, qph); qph ^= 1;
        uint32_t u; asm volatile("ld.shared.u8 %0, [%1];" : "=r"(u) : "r"(sb + SM_UNSAFE + wg) : "memory");
        unsafe = __any_sync(0xffffffffu, u != 0);
        if (HOT && unsafe) { resume = 2; return; }
        }
      }

      if (P.w[cta_id()].role & R_FIN) {
        ROLE;
        if (!(tail && wg == 1)) {
        row_sums();
        const int rl = wg * 64 + warp * 16 + g;
        uint32_t a[64];
#pragma unroll
        for (int i = 0; i < 64; i++) a[i] = pack_bf16(o[2 * i] - (i & 1 ? l1 : l0), o[2 * i + 1] - (i & 1 ? l1 : l0));
        reg_fence(a);
        {
          float2 e0, e1;
          mbar_wait(sb + B_QFULL + 8 * wg, qph);
          asm volatile("ld.shared.v2.f32 {%0,%1}, [%2];" : "=f"(e0.x), "=f"(e0.y) : "r"(sb + SM_ML + rl * 8) : "memory");
          asm volatile("ld.shared.v2.f32 {%0,%1}, [%2];" : "=f"(e1.x), "=f"(e1.y) : "r"(sb + SM_ML + rl * 8 + 64) : "memory");
          STAMP(st0, wg, 7);
          uint32_t fb0 = 0x3f803f80u, fb1 = 0x3f803f80u;
          const float s0 = l0 + e0.y, s1 = l1 + e1.y;
          const bool odd = __any_sync(0xffffffffu, m0 != e0.x || m1 != e1.x || !(fmaxf(s0, s1) < 0x1p40f) || !(fminf(s0, s1) > 0x1p-40f));
          if (HOT && odd) { resume = 3; return; }
          uint4 v[16];
#pragma unroll
          for (int u = 0; u < 16; u++) v[u] = lds128(sQ + (u * 128 + tid) * 16);
          if (!HOT && odd) {
            const float x0 = fmaxf(m0, e0.x), x1 = fmaxf(m1, e1.x);
            const float d0 = fmaxf(m0 - x0, -1000.f), d1 = fmaxf(m1 - x1, -1000.f), f0 = fmaxf(e0.x - x0, -1000.f), f1 = fmaxf(e1.x - x1, -1000.f);
            l0 = l0 * ex2(d0) + e0.y * ex2(f0); l1 = l1 * ex2(d1) + e1.y * ex2(f1);
            const int E0 = fexp(l0), E1 = fexp(l1);
            const uint32_t fa0 = pow2_bf2((int)d0 - E0), fa1 = pow2_bf2((int)d1 - E1);
            fb0 = pow2_bf2((int)f0 - E0); fb1 = pow2_bf2((int)f1 - E1);
            l0 = __uint_as_float(__float_as_uint(l0) - (E0 << 23)); l1 = __uint_as_float(__float_as_uint(l1) - (E1 << 23));
#pragma unroll
            for (int i = 0; i < 32; i++) { a[2 * i] = hmul2(a[2 * i], fa0); a[2 * i + 1] = hmul2(a[2 * i + 1], fa1); }
          } else { l0 = s0; l1 = s1; }
#pragma unroll
          for (int u = 0; u < 16; u++) {
            a[4 * u] = hfma2(v[u].x, fb0, a[4 * u]); a[4 * u + 1] = hfma2(v[u].y, fb1, a[4 * u + 1]);
            a[4 * u + 2] = hfma2(v[u].z, fb0, a[4 * u + 2]); a[4 * u + 3] = hfma2(v[u].w, fb1, a[4 * u + 3]);
          }
        }
        float fs0, fs1;
        asm("rcp.approx.ftz.f32 %0, %1;" : "=f"(fs0) : "f"(l0 * (KS / KC))); asm("rcp.approx.ftz.f32 %0, %1;" : "=f"(fs1) : "f"(l1 * (KS / KC)));
        STAMP(st0, wg, 8);
        reg_fence(a);
        bar_sync(5 + wg, 256);
        uint64_t dW[4];
        float y0[64], y1[64];
        auto half0 = [&](auto u_) {
          constexpr int u = u_.value;
          if (u % 4 == 0) { mbar_wait(sb + B_WF + 2 * u, 1); wg_fence(); dW[u / 4] = desc_mn(sb, ((posw >> u) & 15) * 2048); }
          wgmma_rs_n128_tb<(u & 3) * 512>(y0, a[4 * u], a[4 * u + 1], a[4 * u + 2], a[4 * u + 3], dW[u / 4], u != 0);
        };
        auto half1 = [&](auto u_) {
          constexpr int u = u_.value;
          wgmma_rs_n128_tb<(u & 3) * 512 + 128>(y1, a[4 * u], a[4 * u + 1], a[4 * u + 2], a[4 * u + 3], dW[u / 4], u != 0);
        };
        const bool wr = W.q0 * 128 + wg * 64 + warp * 16 < NN;
        uint4* po = (uint4*)(P.out + (size_t)(W.q0 * 128 + rl) * 256) + t;
        auto emit = [&](const float* y, uint4* dst) {
          if (wr && (!(DBG & 2) || P.zero)) {
            OUTW(dst, make_uint4(pack_bf16(y[0] * fs0, y[1] * fs0), pack_bf16(y[4] * fs0, y[5] * fs0), pack_bf16(y[8] * fs0, y[9] * fs0), pack_bf16(y[12] * fs0, y[13] * fs0)));
            OUTW(dst + 8 * 32, make_uint4(pack_bf16(y[2] * fs1, y[3] * fs1), pack_bf16(y[6] * fs1, y[7] * fs1), pack_bf16(y[10] * fs1, y[11] * fs1), pack_bf16(y[14] * fs1, y[15] * fs1)));
          }
          wg_fence();
        };
        static_for<0, 16>(half0);
        wg_commit();
        static_for<0, 4>(half1);
        wg_commit();
        wg_wait<1>();
        reg_fence(y0);
        emit(y0, po); static_for<4, 8>(half1);
        emit(y0 + 16, po + 4); static_for<8, 12>(half1);
        emit(y0 + 32, po + 8); static_for<12, 16>(half1);
        wg_commit();
        bar_arrive(6 - wg, 256);
        emit(y0 + 48, po + 12);
        wg_wait<0>();
        reg_fence(a); reg_fence(y1);
        STAMP(st0, wg, 9);
#pragma unroll
        for (int u = 0; u < 4; u++) emit(y1 + 16 * u, po + 16 + 4 * u);
        }
        finish();
      }
        }
#pragma unroll 1
    for (int step = HOT || resume ? 0 : -4; step < nloc; step++) {
      ROLE;
      const bool isw = !HOT && step < 0;
      if (isw) {
        const uint4* src = (const uint4*)(step < -2 ? P.wmsg : P.wv) + ((step & 1) * 128 + wg * 64 + warp) * 32 + lane;
        float cw[8] = {0.f, 0.f, 0.f, 0.f, 0.f, 0.f, 0.f, 0.f};
#pragma unroll 1
        for (int i = 0; i < 16; i++) cp_async16(sQ + sw_byte(i * 4 + warp, lane * 8), src + i * 128);
        cp_commit();
#pragma unroll
        for (int i = 0; i < 8; i++) {
          const uint4 v = __ldg((const uint4*)(step < -2 ? P.wmsg : P.wv) + (248 + i) * 32 + lane);
          const float k = step < -2 ? 0.f : (i == 7 ? -1.0f / 4.5f : -0.5f / 4.5f);
          cw[0] += bf_lo(v.x) * k; cw[1] += bf_hi(v.x) * k; cw[2] += bf_lo(v.y) * k; cw[3] += bf_hi(v.y) * k;
          cw[4] += bf_lo(v.z) * k; cw[5] += bf_hi(v.z) * k; cw[6] += bf_lo(v.w) * k; cw[7] += bf_hi(v.w) * k;
        }
        asm volatile("cp.async.wait_group 0;" ::: "memory");
#pragma unroll 1
        for (int i = 0; i < 16; i++) {
          const uint32_t ad = sQ + sw_byte(i * 4 + warp, lane * 8);
          const uint4 v = lds128(ad);
          uint4 w4 = make_uint4(pack_bf16(bf_lo(v.x) + cw[0], bf_hi(v.x) + cw[1]), pack_bf16(bf_lo(v.y) + cw[2], bf_hi(v.y) + cw[3]),
                                pack_bf16(bf_lo(v.z) + cw[4], bf_hi(v.z) + cw[5]), pack_bf16(bf_lo(v.w) + cw[6], bf_hi(v.w) + cw[7]));
          if (step == -1 && wg * 64 + i * 4 + warp == 127) w4 = make_uint4(0, 0, 0, 0);
          sts128(ad, w4);
        }
        fence_async_smem();
        bar_sync(7, 256);
      } else {
        SSTAMP(0);
        mbar_wait(sb + B_QFULL + 8 * wg, qph); qph ^= 1;
        STAMP(st0 && step == 0, wg, 8);
        SSTAMP(1);
        bar_sync(5 + wg, 256);
        SSTAMP(2);
      }
#pragma unroll 1
      for (int c = 0; c < 4; c++) {
        if (step == 0) mbar_wait(sb + B_WF + 8 * c, HOT || resume);
        const int turn2 = HOT || resume ? 3 : 4;
        if (c == turn2) bar_sync(5 + wg, 256);
        wg_fence();
        const uint64_t dA = desc_k(sb + SM_Q, wg * 2048 + c * 64), dW = desc_mn(sb, ((posw >> c * 4) & 15) * 2048);
        static_for<0, 4>([&](auto k) { wgmma_ss_n256_tb<k.value * 2, k.value * 512>(o, dA, dW, k.value > 0 ? 1 : c); });
        wg_commit();
        if ((c == 3 || c == turn2 - 1) && !isw) bar_arrive(6 - wg, 256);
        wg_wait<1>();
      }
      wg_wait<0>();
      reg_fence(o);
      {
        STAMP(st0 && step == 0, wg, 9);
        SSTAMP(3);
        if (isw) bar_sync(1 + wg, 128); else if (lane == 0) mbar_arrive(sb + B_QEMPTY + 8 * wg);
        uint8_t* dw = (uint8_t*)(step < -2 ? g_Wmo : g_Wvo) + ((step & 1) * 2 + wg) * 32768 + warp * 8192 + g * 128;
        const int row0 = (W.loc0 + step) * 128 + wg * 64 + warp * 16;
        uint4 r[16];
#pragma unroll
        for (int u = 0; u < 8; u++) { r[2 * u] = ROW0(u); r[2 * u + 1] = ROW1(u); }
        if (isw) {
#pragma unroll
          for (int u = 0; u < 16; u++) *(uint4*)(dw + (u >> 2) * 1024 + ((((u & 2) * 2 + t) ^ g) << 4) + (u & 1) * 4096) = r[u];
        } else if (row0 < NN) {
          uint4* po = (uint4*)(P.out + (size_t)(row0 + g) * 256) + t;
          uint32_t c1 = clk();
#pragma unroll
          for (int u = 0; u < 16; u++) {
            if (!(DBG & 1) || !HOT || P.zero) red_bf16x8(po + (u >> 1) * 4 + (u & 1) * 256, r[u]);
            if (!HOT) { c1 += PACE; while ((int)(clk() - c1) < 0) {} }
          }
        }
        if (!HOT && step == -1) { bar_sync(7, 256); if (tid_is(0)) flag_release(F_W); __syncwarp(); STAMP(st0, wg, 3); }
      }
    }
    finish();
    };
    if (resume < 0) run(std::true_type{});
    else fill();
    run(std::false_type{});
    asm volatile("setmaxnreg.dec.sync.aligned.u32 %0;" :: "n"(504 - 2 * CREG));
  } else {
    STAMP(lane == 0 && warp == 0, 2, 0);
        const int mi = cta >> 3;
    const uint32_t sW = sb + 3 * 32768;
    uint4 wa[4], wb[8];
    {
      const uint4* pq = (const uint4*)(P.wq + ((mi & 15) * 16 + g) * 256) + warp * 8 + t;
      const uint4* pk = (const uint4*)(P.wk + ((cta & 7) * 32 + g) * 256) + warp * 8 + t;
#pragma unroll
      for (int i = 0; i < 4; i++) wa[i] = __ldg(pq + (i >> 1) * 256 + (i & 1) * 4);
#pragma unroll
      for (int i = 0; i < 8; i++) wb[i] = __ldg(pk + (i >> 1) * 256 + (i & 1) * 4);
    }
    if (threadIdx.x == 352) {
      for (int i = 0; i < 3; i++) { mbar_init(sb + B_FULL + 8 * i, 1); mbar_init(sb + B_EMPTY + 8 * i, cta == 130 ? 4 : 8); }
      for (int i = 0; i < 4; i++) mbar_init(sb + B_WF + 8 * i, 1);
      for (int i = 0; i < 2; i++) { mbar_init(sb + B_QFULL + 8 * i, 1); mbar_init(sb + B_QEMPTY + 8 * i, 4); mbar_init(sb + B_EVP0 + 8 * i, 4); }
      mbar_init(sb + B_EVH, 8); mbar_init(sb + B_EVQ, 8); mbar_init(sb + B_HALF, 8); mbar_init(sb + B_BG, 1); mbar_init(sb + B_M0, 1); mbar_init(sb + B_HRD, 1);
      asm volatile("fence.mbarrier_init.release.cluster;" ::: "memory");
    }
    __syncwarp();
    bar_sync(4, 384);
    {
#pragma unroll
      for (int n = 0; n < 4; n++) {
        float c[4] = {0.f, 0.f, 0.f, 0.f};
#pragma unroll
        for (int u = 0; u < 2; u++) {
          mma16816(c, wa[u].x, wa[2 + u].x, wa[u].y, wa[2 + u].y, wb[2 * n + u].x, wb[2 * n + u].y);
          mma16816(c, wa[u].z, wa[2 + u].z, wa[u].w, wa[2 + u].w, wb[2 * n + u].z, wb[2 * n + u].w);
        }
        asm volatile("st.shared.v2.f32 [%0], {%1,%2};" :: "r"(sW + ((warp * 16 + g) * 40 + n * 8 + 2 * t) * 4), "f"(c[0]), "f"(c[1]) : "memory");
        asm volatile("st.shared.v2.f32 [%0], {%1,%2};" :: "r"(sW + ((warp * 16 + g + 8) * 40 + n * 8 + 2 * t) * 4), "f"(c[2]), "f"(c[3]) : "memory");
      }
      STAMP(lane == 0 && warp == 0, 2, 7);
      bar_sync(3, 128);
      if (warp < 2) {
        float c[8] = {0.f, 0.f, 0.f, 0.f, 0.f, 0.f, 0.f, 0.f};
#pragma unroll
        for (int k = 0; k < 4; k++) {
          const uint4 v = lds128(sW + ((k * 16 + warp * 8 + g) * 40 + t * 8) * 4), w = lds128(sW + ((k * 16 + warp * 8 + g) * 40 + t * 8 + 4) * 4);
          c[0] += __uint_as_float(v.x); c[1] += __uint_as_float(v.y); c[2] += __uint_as_float(v.z); c[3] += __uint_as_float(v.w);
          c[4] += __uint_as_float(w.x); c[5] += __uint_as_float(w.y); c[6] += __uint_as_float(w.z); c[7] += __uint_as_float(w.w);
        }
        const float ms = 1.4426950408889634f / 16.0f / KS;
        const uint4 m4 = make_uint4(pack_bf16(c[0] * ms, c[1] * ms), pack_bf16(c[2] * ms, c[3] * ms), pack_bf16(c[4] * ms, c[5] * ms), pack_bf16(c[6] * ms, c[7] * ms));
        sts128(sW + 16384 + (warp * 8 + g) * 64 + ((t ^ (g & 3)) << 4), m4);
      }
    }
    asm volatile("setmaxnreg.dec.sync.aligned.u32 %0;" :: "n"(504 - 2 * CREG));
    STAMP(lane == 0 && warp == 0, 2, 13);
    bar_sync(3, 128);
#define ep1 (lds32(sb + SM_EPOCH) + 1)
    if (threadIdx.x == 256 && cta < 128) {
      {
        fence_async_smem();
#pragma unroll 1
        for (int r = 0; r < 16; r++)
          bulk_s2g((uint8_t*)g_M + (mi * 2 + (r >> 3)) * 4096 + ((cta & 7) >> 1) * 1024 + (r & 7) * 128 + ((((cta & 1) * 4) ^ (r & 4)) << 4), sW + 16384 + r * 64, 64);
        bulk_commit();
        bulk_wait_all();
        red_relaxed(g_flag + F_M + (cta >> 5));
      }
    }
    __syncwarp();
    ROLE;
    if (warp == 3 && W.own) {
      mbar_wait_w(sb + B_EVH, 0);
      if (W.role < R_SIG) mbar_wait_w(sb + B_WF + 8, 0);
      if (lane == 0) {
        fence_async_smem();
        const int h0 = W.own == 2, nh = W.own == 3 ? 2 : 1;
        bulk_s2g(g_h + W.hp * 4096 + h0 * 2048, sb + SM_Q + h0 * 32768, nh * 32768);
        bulk_s2g(g_stat + W.q0 * 128 + h0 * 64, sb + SM_ML + h0 * 512, nh * 512);
        bulk_commit();
        bulk_wait_read();
        mbar_arrive(sb + B_HRD);
        bulk_wait_all();
        if (W.role >= R_SIG) red_relaxed(g_flag + F_H1 - 1 + W.role / R_SIG);
        red_relaxed(g_flag + F_H);
      }
      __syncwarp();
      STAMP(lane == 0, 2, 6);
    }
    if (warp == 0) {
      if (lane == 0) {
        STAMP(true, 2, 1);
        const uint32_t epoch = ld_relaxed(g_flag + F_EPOCH);
        if (total > 0) {
#pragma unroll
          for (int c = 0; c < 3; c++) mbar_expect_tx(sb + B_WF + 8 * c, c == 0 ? WCH_B - 8192 : WCH_B);
          mbar_expect_tx(sb + B_M0, 8192);
          int c = 0;
#pragma unroll 1
          for (uint32_t it = 0; c < 4; it++) {
            uint4 f;
            asm volatile("ld.relaxed.gpu.global.v4.u32 {%0,%1,%2,%3}, [%4];" : "=r"(f.x), "=r"(f.y), "=r"(f.z), "=r"(f.w) : "l"(g_flag + F_M) : "memory");
            uint32_t tm;
            asm volatile("mad.lo.u32 %0, %1, 32, 32;" : "=r"(tm) : "r"(epoch));
            int ok = (int)(f.x - tm) < 0 ? 0 : (int)(f.y - tm) < 0 ? 1 : (int)(f.z - tm) < 0 ? 2 : (int)(f.w - tm) < 0 ? 3 : 4;
            if (it > (1u << 23)) ok = 4;
            if (ok > c) {
              asm volatile("fence.acquire.gpu;" ::: "memory"); fence_async_gmem();
              if (c == 0) bulk_g2s(sb + (POS_M & 15) * 32768, g_M, 8192, sb + B_M0);
            }
#pragma unroll 1
            for (; c < ok; c++) {
              const uint32_t skip = c == 0 ? 8192 : 0;
              bulk_g2s(sb + ((POS_M >> c * 4) & 15) * 32768 + skip, pofs<const uint8_t>(g_M, c * WCH_B + skip), WCH_B - skip, sb + B_WF + 8 * c);
              STAMP(c == 0, 2, 2);
            }
          }
        }
        asm volatile("st.shared.u32 [%0], %1;" :: "r"(sb + SM_EPOCH), "r"(epoch) : "memory");
        if (total > 0) mbar_expect_tx(sb + B_WF + 24, WCH_B);
        int st = 0, ph = 0, qph = 0;
        const int nsl = tail ? 3 : 2;
        auto next_slot = [&]() { mbar_wait(sb + B_EMPTY + 8 * st, ph); if (++st == nsl) { st = 0; ph ^= 1; } };
        auto w_load = [&](int c0, int c1) {
#pragma unroll 1
          for (int c = c0; c < c1; c++) {
            mbar_expect_tx(sb + B_WF + 8 * c, WCH_B);
            bulk_g2s(sb + ((posw >> c * 4) & 15) * 32768, pofs<const uint8_t>(fin ? g_Wvo : g_Wmo, c * WCH_B), WCH_B, sb + B_WF + 8 * c);
          }
        };
        auto q_load = [&](const uint4* src, bool wait_empty) {
#pragma unroll 1
          for (int h = 0; h < 2; h++) {
            if (wait_empty) mbar_wait(sb + B_QEMPTY + 8 * h, qph);
            mbar_expect_tx(sb + B_QFULL + 8 * h, 32768);
            (HINT & 2 ? bulk_g2s_last : bulk_g2s)(sb + SM_Q + h * 32768, src + h * 2048, 32768, sb + B_QFULL + 8 * h);
          }
          if (wait_empty) qph ^= 1;
        };
        auto part_out = [&](int slot, int h, uint32_t region, int parity) {
          mbar_wait(sb + B_EVP0 + 8 * h, parity);
          fence_async_smem();
          bulk_s2g(g_part + slot * 4096 + h * 2048, sb + region * 32768, 32768);
          bulk_s2g(g_ml + slot * 128 + h * 64, sb + SM_ML + h * 512, 512);
          bulk_commit();
        };
        auto announce = [&](int f) {
          if (RELF) { fence_async_gmem(); flag_release(f); }
          else red_relaxed(g_flag + f);
        };
        if (total > 0) {
          STAMP(true, 2, 3);
          const int q1 = W.q0 + 2 * W.own - 3;
          if (!tail) { flag_wait(F_H1 + (fin ? 0 : W.own), ep1 * (fin ? NH1_0 : (W.own == 1 ? NH1_1 : NH1_2))); fence_async_gmem(); }
          STAMP(true, 2, 4);
          uint32_t ko = W.k0 * 8192;
#pragma unroll 1
          for (int j = 0; j < total; j++) {
            if (j == (tail ? 0 : 1)) { flag_wait(F_H, ep1 * NHSIG); fence_async_gmem(); }
            if (j == n0) {
              flag_wait(F_QP + q1 * LN_, ep1); fence_async_gmem();
              const uint32_t u = __ldcg(g_unsafe + q1);
              asm volatile("st.shared.u32 [%0], %1;" :: "r"(sb + SM_UNSAFE), "r"(u) : "memory");
              ko = W.k1 * 8192;
            }
            if (j == n0 + 1) q_load(g_qp + q1 * 4096, true);
            if (j == total - 1) { flag_wait(F_W, ep1); fence_async_gmem(); if (!tail) w_load(0, 1); }
            const uint32_t bytes = (j < n0 ? j < W.nb0 : j - n0 < W.nb1) ? 112 * 512 : 128 * 512, s0 = st;
            const uint32_t region = (tail ? 1 : 2) + 2 * s0, skip = j == n0 + 1 ? 32768 : 0;
            if (skip) part_out(W.slotA, 0, 6, 0);
            next_slot();
            mbar_expect_tx(sb + B_FULL + 8 * s0, bytes);
            bulk_g2s(sb + region * 32768 + skip, pofs<const uint8_t>(g_h, ko + skip), bytes - skip, sb + B_FULL + 8 * s0);
            if (skip) {
              part_out(W.slotA, 1, region, 0);
              bulk_wait_read();
              bulk_g2s(sb + region * 32768, pofs<const uint8_t>(g_h, ko), skip, sb + B_FULL + 8 * s0);
              bulk_wait_all();
              announce(F_PART + W.slotA * LN_);
            }
            ko += bytes;
          }
          next_slot();
          if (tail) { next_slot(); next_slot(); }
        } else { flag_wait(F_W, ep1); fence_async_gmem(); }
        STAMP(true, 2, 5);
        const bool staged = total > 0 && !tail;
        w_load(staged, staged ? (fin ? 2 : 3) : 4);
#pragma unroll 1
        for (int i = 0; i < W.nloc; i++) {
          const int tl = W.loc0 + i, last = tl * 128 + 127 < NN ? tl * 128 + 127 : NN - 1;
          flag_wait(F_AGG + ((last >= NGW) + (last >= 4 * NGW) + (last >= 9 * NGW)) * LN_, ep1 * NGW); fence_async_gmem();
          if (total == 0) g_flag[F_EPOCH] = epoch + 1;
          q_load(g_agg + tl * 4096, total > 0 || i > 0);
        }
        if (tail) { mbar_wait(sb + B_BG, 0); mbar_wait(sb + B_EVP0 + 8, 0); mbar_arrive(sb + B_QFULL); }
        else if (fin) {
          int h = 0, c = 2, have = W.slotB >= 0 || (DBG & 8) ? 2 : 0;
          mbar_wait(sb + B_BG, 0);
#pragma unroll 1
          for (uint32_t it = 0; (h < 2 || c < 4) && it < (1u << 23); it++) {
            if (have < 2) {
              uint2 f;
              asm volatile("ld.relaxed.gpu.global.v2.u32 {%0,%1}, [%2];" : "=r"(f.x), "=r"(f.y) : "l"(g_flag + F_PART + W.slotA * LN_) : "memory");
              have = (int)(f.x - (epoch + 1)) < 0 ? 0 : ((int)(f.y - (epoch + 1)) < 0 ? 1 : 2);
            }
            if (h < have && mbar_try_wait_nb(sb + B_QEMPTY + 8 * h, 0)) {
              asm volatile("fence.acquire.gpu;" ::: "memory"); fence_async_gmem();
              STAMP(true, 2, 14 + h);
              mbar_expect_tx(sb + B_QFULL + 8 * h, 32768 + 512);
              bulk_g2s(sb + SM_ML + h * 512, g_ml + W.slotA * 128 + h * 64, 512, sb + B_QFULL + 8 * h);
              bulk_g2s(sb + SM_Q + h * 32768, g_part + W.slotA * 4096 + h * 2048, 32768, sb + B_QFULL + 8 * h);
              h++;
            }
            const bool half = mbar_try_wait_nb(sb + B_HALF, 0);
            const int c1 = half ? 4 : (h > 0 ? 3 : 2);
            if (c < c1) { w_load(c, c1); c = c1; }
          }
        } else if (total > 0) {
#pragma unroll 1
          for (int h = 0; h < 2; h++) part_out(W.slotB, h, (posw >> 12) + h, 1);
          asm volatile("cp.async.bulk.wait_group.read 1;" ::: "memory");
          w_load(3, 4);
          asm volatile("cp.async.bulk.wait_group 1;" ::: "memory");
          announce(F_PART + W.slotB * LN_);
          STAMP(true, 2, 14);
          bulk_wait_all();
          announce(F_PART + W.slotB * LN_ + 1);
          STAMP(true, 2, 15);
        }
        DUMP(true, 2, 14, 16);
        DUMP(true, 2, 0, 8);
      }
      return;
    }
  }
    {
      const int gw = cta * 3 + warp - 1;
      ROLE;
      if (total > 0) {
        mbar_wait_w(sb + B_EVQ, 0);
        const uint32_t c0 = clk();
        if (warp == 1 && (W.role & R_PUB)) {
          g_unsafe[W.q0] = lds32(sb + SM_UNSAFE);
#pragma unroll 1
          for (int k = 0; k < 4; k++) {
            __nanosleep(2000);
            if (lane == 0) bulk_s2g(pofs<uint4>(g_qp, W.q0 * 65536 + k * 16384), sb + SM_Q + k * 16384, 16384);
            bulk_commit();
          }
          bulk_wait_all();
          flag_release_w(F_QP + W.q0 * LN_);
        }
        while (__any_sync(0xffffffffu, clk() - c0 < GSTART)) __nanosleep(500);
        STAMP(lane == 0 && warp == 1, 2, 8);
#define ovf_cnt pofs<uint32_t>(g_flag, (F_OVF + (ep1 & 1) * LN_) * 4)
        if (gw == 0) g_flag[F_OVF + ((ep1 + 1) & 1) * LN_] = 0;
#pragma unroll 1
        for (int e0 = gw * 32; e0 < NE; e0 += NGW * 32 * 7) {
          int d[7], s[7], pos[7];
          const int* pd = pofs<const int>(P.dst, (e0 + lane) * 4);
          const int* ps = pofs<const int>(P.src, (e0 + lane) * 4);
#pragma unroll
          for (int k = 0; k < 7; k++) { const bool ok = e0 + k * NGW * 32 < NE; d[k] = ok ? (HINT & 1 ? __ldcs(pd + k * NGW * 32) : __ldg(pd + k * NGW * 32)) : -1; s[k] = ok ? (HINT & 1 ? __ldcs(ps + k * NGW * 32) : __ldg(ps + k * NGW * 32)) : 0; }
          uint32_t ov = 0;
#pragma unroll
          for (int k = 0; k < 7; k++) {
            pos[k] = 0;
            if (d[k] >= 0) asm volatile("atom.relaxed.gpu.global.add.u32 %0, [%1], 1;" : "=r"(pos[k]) : "l"(pofs<int>(g_cnt, d[k] << 2)) : "memory");
            s[k] = (uint32_t)(uintptr_t)g_u + s[k] * 512;
            if (d[k] >= 0 && pos[k] < CAP) asm volatile("st.volatile.global.u32 [%0], %1;" :: "l"(pofs<int>(g_bin, (d[k] * CAPS + pos[k]) << 2)), "r"(s[k]) : "memory");
            ov |= (pos[k] >= CAP) << k;
          }
          if (__any_sync(0xffffffffu, ov != 0)) {
            uint32_t at;
            asm volatile("atom.relaxed.gpu.global.add.u32 %0, [%1], %2;" : "=r"(at) : "l"(ovf_cnt), "r"(__popc(ov)) : "memory");
#pragma unroll
            for (int k = 0; k < 7; k++) if ((ov >> k) & 1) g_ovf[at++] = make_int2(d[k], s[k]);
          }
        }
        flag_wait_w(F_H, ep1 * NHSIG);
#pragma unroll 1
        for (int n0 = gw; n0 < NN; n0 += 4 * NGW) {
          uint4 xv[4]; float2 st[4];
#pragma unroll
          for (int k = 0; k < 4; k++) {
            const int n = n0 + k * NGW < NN ? n0 + k * NGW : n0;
            xv[k] = (HINT & 1 ? ldcs_v : ldcg_v)(pofs<const uint4>(P.x, n * 512 + lane * 16));
            st[k] = __ldcg(pofs<const float2>(g_stat, n * 8));
          }
#pragma unroll
          for (int k = 3; k >= 0; k--) {
            const int n = n0 + k * NGW;
            const float a = st[k].x * US, c = fmaf(st[k].y, US, UB + 8388608.0f);
#define FIX(w) __byte_perm(__float_as_uint(fmaf(bf_lo(w), a, c)), __float_as_uint(fmaf(bf_hi(w), a, c)), 0x5410)
            if (n < NN) {
              *pofs<uint4>(P.out, n * 512 + lane * 16) = xv[k];
              *pofs<uint4>(g_u, n * 512 + lane * 16) = make_uint4(FIX(xv[k].x), FIX(xv[k].y), FIX(xv[k].z), FIX(xv[k].w));
            }
          }
        }
        flag_release_w(F_BIN);
        STAMP(lane == 0 && warp == 1, 2, 9);
        flag_wait_w(F_BIN, ep1 * NGW);
        STAMP(lane == 0 && warp == 1, 2, 10);
        const int myn = gw + lane * NGW < NN ? gw + lane * NGW : gw;
        int cnts = __ldcg(g_cnt + myn);
        cnts = gw + lane * NGW < NN ? (cnts > CAP ? CAP + 1 : cnts) | ((int)__ldg((const unsigned short*)P.dinv + myn) << 16) : 0;
        __syncwarp();
        g_cnt[myn] = 0;
        const uint32_t uhi = (uintptr_t)g_u >> 32, lx = lane * 16;
        uint32_t obin = gw * CAPS * 4;
        uint32_t ent = __ldcg(pofs<const uint32_t>(g_bin, obin + lane * 4)), entn = __ldcg(pofs<const uint32_t>(g_bin, obin + NGW * CAPS * 4 + lane * 4));
        int cd = __shfl_sync(0xffffffffu, cnts, 0), cb = min(cd & 0xffff, CAP), e = 0;
        uint32_t sa[4] = {0, 0, 0, 0}, sh[4] = {0, 0, 0, 0};
        auto add = [&](uint32_t x, uint32_t y, uint32_t z, uint32_t w) {
          sa[0] += x; sa[1] += y; sa[2] += z; sa[3] += w;
          sh[0] += x >> 16; sh[1] += y >> 16; sh[2] += z >> 16; sh[3] += w >> 16;
        };
        int rnd = -1, rows = -1, cdo = 0;
#pragma unroll 1
        for (;;) {
          const bool hold = rows >= 0 && rnd == 8;
          const int m = hold ? 0 : cb - e;
          uint4 v[8];
          if (m >= 8) {
#pragma unroll
            for (int k = 0; k < 8; k++) v[k] = ldcg_v(addr64(__shfl_sync(0xffffffffu, ent, k) + lx, uhi));
          } else {
#pragma unroll
            for (int k = 0; k < 8; k++) {
              v[k] = make_uint4(0, 0, 0, 0);
              if (k < 7) ldcg_if(v[k], addr64(__shfl_sync(0xffffffffu, ent, k) + lx, uhi), k < m);
            }
          }
          if (rows >= 0) {
            const int n = gw + rnd * NGW;
            if (n < NN) {
              const float di = __uint_as_float(cdo & 0xffff0000u) * (1.0f / US), nl = -di * UB * (float)rows;
#define AGG(k) pack_bf16(fmaf((float)(sa[k] - (sh[k] << 16)), di, nl), fmaf((float)sh[k], di, nl))
              *pofs<uint4>(g_agg, ((n >> 3) * 4096 + (n & 7) * 144) ^ ((lx & 0x70) | ((lx & 0x180) << 3))) = make_uint4(AGG(0), AGG(1), AGG(2), AGG(3));
            }
#pragma unroll
            for (int k = 0; k < 4; k++) sa[k] = sh[k] = 0;
            rows = -1;
            if (rnd == 0 || rnd == 3 || rnd == 8 || rnd == NRND - 1) flag_release_w(F_AGG + ((rnd > 0) + (rnd > 3) + (rnd > 8)) * LN_);
            if (rnd == NRND - 1) break;
            if (hold) {
              if (fin && W.slotB >= 0) {
        #pragma unroll 1
                for (int k = 0; k < 2; k++) flag_wait_w(F_PART + (k ? W.slotB : W.slotA) * LN_, ep1);
        #pragma unroll 1
                for (int b = warp - 1; b < 8; b += 3) {
                  float2* ma = g_ml + W.slotA * 128 + b * 16 + g;
                  const float2* mb = g_ml + W.slotB * 128 + b * 16 + g;
                  const float2 a0 = __ldcg(ma), a1 = __ldcg(ma + 8), b0 = __ldcg(mb), b1 = __ldcg(mb + 8);
                  const float x0 = fmaxf(a0.x, b0.x), x1 = fmaxf(a1.x, b1.x);
                  const float fa0 = ex2(a0.x - x0), fa1 = ex2(a1.x - x1), fb0 = ex2(b0.x - x0), fb1 = ex2(b1.x - x1);
                  __syncwarp();
                  if (t == 0) { ma[0] = make_float2(x0, a0.y * fa0 + b0.y * fb0); ma[8] = make_float2(x1, a1.y * fa1 + b1.y * fb1); }
                  const uint32_t ofs = ((b >> 2) * 2048 + (b & 3) * 32 + lane) * 16;
        #pragma unroll 1
                  for (int u = 0; u < 16; u += 4) {
                    uint4* pa = pofs<uint4>(g_part, W.slotA * 65536 + ofs + u * 2048);
                    const uint4* pb = pofs<const uint4>(g_part, W.slotB * 65536 + ofs + u * 2048);
                    uint4 va[4], vb[4];
        #pragma unroll
                    for (int k = 0; k < 4; k++) { va[k] = ldcg_v(pa + k * 128); vb[k] = (HINT & 2 ? ldcs_v : ldcg_v)(pb + k * 128); }
        #define FOLD(w, fa, fb) pack_bf16(bf_lo(va[k].w) * fa + bf_lo(vb[k].w) * fb, bf_hi(va[k].w) * fa + bf_hi(vb[k].w) * fb)
        #pragma unroll
                    for (int k = 3; k >= 0; k--) pa[k * 128] = make_uint4(FOLD(x, fa0, fb0), FOLD(y, fa1, fb1), FOLD(z, fa0, fb0), FOLD(w, fa1, fb1));
                  }
                }
                bar_sync(3, 96);
                if (warp == 1) asm volatile("fence.acq_rel.gpu;" ::: "memory");
              }
              if (fin && warp == 1 && lane == 0) mbar_arrive(sb + B_BG);
              while (__any_sync(0xffffffffu, clk() - c0 < GPAUSE)) __nanosleep(500);
              continue;
            }
          }
#define SUM8(f) (v[7].f + v[6].f + v[5].f + v[4].f + v[3].f + v[2].f + v[1].f + v[0].f)
          add(SUM8(x), SUM8(y), SUM8(z), SUM8(w));
          e += 8;
          if (e < cb) {
            ent = __shfl_down_sync(0xffffffffu, ent, 8);
            if (e == 32) ent = __ldcg(pofs<const uint32_t>(g_bin, obin + 128 + lx / 4));
            continue;
          }
          rnd++; rows = cb; cdo = cd;
          if ((cd & 0xffff) > CAP) {
            const int no = __shfl_sync(0xffffffffu, (int)ld_relaxed(ovf_cnt), 0);
#pragma unroll 1
            for (int i0 = 0; i0 < no; i0 += 32) {
              int2 en = __ldcg(g_ovf + min(i0 + lane, no - 1));
              uint32_t mk = __ballot_sync(0xffffffffu, en.x == gw + rnd * NGW && i0 + lane < no);
              rows += __popc(mk);
#pragma unroll 1
              while (mk) {
                const int bit = __ffs(mk) - 1; mk &= mk - 1;
                const uint4 r = ldcg_v(addr64((uint32_t)__shfl_sync(0xffffffffu, en.y, bit) + lx, uhi));
                add(r.x, r.y, r.z, r.w);
              }
            }
          }
          obin += NGW * CAPS * 4;
          ent = entn; entn = __ldcg(pofs<const uint32_t>(g_bin, obin + NGW * CAPS * 4 + lx / 4));
          cd = __shfl_sync(0xffffffffu, cnts, rnd + 1); cb = min(cd & 0xffff, CAP); e = 0;
        }
      }
      STAMP(lane == 0 && warp == 1, 2, 11);
      if ((HINT & 4) && warp == 2 && fin && lane == 0) {
        prefetch_l2(pofs<uint8_t>(P.out, W.q0 * 65536), tail ? 8192 : 65536);
        if (W.slotB >= 0) prefetch_l2(pofs<uint8_t>(g_part, W.slotA * 65536), 65536);
        prefetch_l2(pofs<uint8_t>(g_Wvo, (cta & 63) * 4096), 4096);
      }
      DUMP(warp == 1 && lane == 0, 2, 8, 14);
    }
}

}

extern "C" void kernel_launch(void* const* d_in, const int* in_sizes, int n_in, void* d_out, int out_size) {
  Params P;
  P.x = (const __nv_bfloat16*)d_in[0];
  P.src = (const int*)d_in[1];
  P.dst = (const int*)d_in[2];
  P.dinv = (const __nv_bfloat16*)d_in[3];
  P.wmsg = (const __nv_bfloat16*)d_in[4];
  P.wq = (const __nv_bfloat16*)d_in[5];
  P.wk = (const __nv_bfloat16*)d_in[6];
  P.wv = (const __nv_bfloat16*)d_in[7];
  P.wout = (const __nv_bfloat16*)d_in[8];
  P.out = (__nv_bfloat16*)d_out;
  P.zero = 0;
  for (int c = 0; c < NCTA; c++) P.w[c] = make_work(c);
  static void* scr = nullptr;
  if (!scr) {
    cudaFuncSetAttribute(gps_kernel, cudaFuncAttributeMaxDynamicSharedMemorySize, SMEM_BYTES);
    cudaGetSymbolAddress(&scr, g_scr);
  }
  P.s = (Scratch*)((((uintptr_t)scr + SCR_ALIGN - 1) & ~(uintptr_t)(SCR_ALIGN - 1)) + SCR_OFS);
  P.u = (uint4*)(((uintptr_t)P.s->u + 511) & ~(uintptr_t)511);
  if (((uintptr_t)P.u >> 32) != (((uintptr_t)(P.u + NN * 32) - 1) >> 32)) P.u += NN * 32;
  gps_kernel<<<NCTA, 384, SMEM_BYTES>>>(P);
}
```

```cpp
#include <cuda_runtime.h>
#include <cuda_bf16.h>
#include <stdint.h>
#include <stddef.h>
#include <type_traits>
#define FB 5
#define MB 5
#define GSTART 18000
#define HINT 7
#define RELF 0
#define DBG 0
#define OUTW red_bf16x8
#define XD 2
#define PACE 64
#define GPAUSE 120000
#define XDELAY 200
#define CREG 224
#define BACKOFF 1000

namespace {

constexpr int NN = 10000;
constexpr int NE = 160000;
constexpr int NQT = 79;
constexpr int NCTA = 132;
constexpr int CAP = 64;
constexpr int CAPS = 64;
constexpr int NHSIG = 105;
constexpr uint32_t WCH_B = 32768;
constexpr int NGW = (NCTA - 1) * 3;
constexpr float TAU = 16.0f;
constexpr float SAFE_N2 = 36.0f, SAFE_C = 0.6f;
#define KOFF 3
#define PSH -8.0f
#define KROT 15
constexpr float US = 256.0f, UB = 4095.0f;
constexpr float KS = 0.25f, KC = KOFF * KS;
constexpr uint32_t KS2 = 0x3e803e80u, KC2 = KOFF == 2 ? 0x3f003f00u : (KOFF == 1 ? 0x3e803e80u : 0x3f403f40u);

constexpr int NAGG = 4;
constexpr int NRND = (NN + NGW - 1) / NGW;
constexpr int NSLOT = 105;
constexpr int F_EPOCH = 0, F_H = 1, F_M = 4  , F_H1 = 8  , LN_ = 32;
constexpr int F_BIN = LN_, F_W = 2 * LN_, F_OVF = 3 * LN_  , F_QP = 5 * LN_, F_AGG = F_QP + NQT * LN_,
              F_PART = F_AGG + NAGG * LN_, F_END = F_PART + NSLOT * LN_;

struct Scratch {
  uint32_t flag[F_END];
  alignas(4096) uint4 M[8192];
  uint4 Wvo[8192], Wmo[8192];
  float2 ml[NSLOT * 128];
  uint32_t unsafe[96];
  int cnt[NN + 32];
  float2 stat[NQT * 128];
  alignas(4096) uint4 h[NQT * 4096];
  uint4 u[2 * NN * 32 + 32];
  uint4 qp[NQT * 4096];
  uint4 agg[NQT * 4096];
  uint4 part[NSLOT * 4096];
  int bin[(NRND + 2) * NGW * CAPS];
  int2 ovf[NE];
};
static_assert(offsetof(Scratch, h) % 128 == 0, "alignment");
#define SCR_ALIGN (2u << 20)
#define SCR_OFS 0
__device__ uint4 g_scr[(sizeof(Scratch) + SCR_ALIGN + SCR_OFS) / 16];
struct alignas(16) Work { short k0, k1; signed char q0, hp, nb0, na0, nb1, na1, slotA, slotB, loc0, nloc, own, role; };
constexpr int R_FIN = 1, R_PUB = 2, R_TAIL = 4, R_SIG = 8  ;
struct Params {
  const __nv_bfloat16 *x, *wq, *wk;
  Scratch* s;
  uint4* u;
  __nv_bfloat16* out;
  const __nv_bfloat16 *wout, *wmsg, *wv, *dinv;
  const int *src, *dst;
  long long zero;
  Work w[NCTA];
};
constexpr int first_cnt(int k) { return 2 * ((k + 6) / 8 - k / 8 + 1); }
constexpr int NH1_0 = 2, NH1_1 = first_cnt(48 * 8 - MB), NH1_2 = first_cnt(48 * 8 - MB + 16 * 8 - (15 - MB) / 2);
constexpr int NSERV = NQT - 52;
__host__ __device__ inline int logical_cta(int c) {
  const int p = c >> 1, rank = c & 1;
  return p < 52 ? 5 * (p >> 1) + (rank ? 1 + 2 * (p & 1) : 4 * (p & 1)) : (p < 65 ? 5 * (2 * (p - 52) + rank) + 2 : c);
}
inline Work make_work(int c) {
  Work w;
  const int gi = c / 5, r = c % 5, q = gi * 3;
  const bool helper = r & 1, mid = r == 2;
  w.q0 = helper ? q + 1 : q + (r >> 1);
  const int hb1 = (15 - MB) / 2, hb3 = 15 - MB - hb1;
  w.nb0 = helper ? (r == 1 ? hb1 : hb3) : (mid ? MB : FB);
  w.na0 = (helper ? 16 : 48) - w.nb0;
  w.k0 = helper ? (48 * 8 - MB) + (r >> 1) * (16 * 8 - hb1) : 0;
  w.k1 = 48 * 8 - FB;
  w.nb1 = helper ? (FB < 7 ? 7 : 15) - FB : 0;
  w.na1 = helper ? (FB < 7 ? 31 : 32) - w.nb1 : 0;
  w.slotA = 4 * gi + (helper ? r - 1 : (mid ? 0 : (r >> 1) + 1));
  w.slotB = helper ? 4 * gi + r : (mid ? 4 * gi + 2 : -1);
  w.loc0 = NSERV + gi * 2 + (r >> 1);
  w.nloc = helper;
  w.own = helper ? (r + 1) >> 1 : (mid ? 0 : 3);
  w.role = helper ? 0 : (mid ? R_FIN : R_FIN | R_PUB);
  const int k1st[3] = {0, 48 * 8 - MB, 48 * 8 - MB + 16 * 8 - hb1};
  int pos[NQT], sig[NQT];
  for (int i = 0; i < NQT; i++) { pos[i] = i; sig[i] = 0; }
  for (int i = 0; i < 3; i++)
    for (int p = k1st[i] / 8; p <= (k1st[i] + 6) / 8; p++) {
      int m = 1, at = 0;
      while (sig[m]) m += 3;
      while (pos[at] != p) at++;
      pos[at] = pos[m]; pos[m] = p; sig[m] = 1 + i;
    }
  w.hp = c < 131 ? pos[w.q0] : 0;
  if (helper && c < 130) w.role |= sig[w.q0] * R_SIG;
  if (c == 130) { w.nb0 = 15; w.na0 = 65; w.slotA = NSLOT - 1; w.own = 1; w.role = R_FIN | R_TAIL; }
  if (c == 131) { w.nb0 = w.na0 = w.nb1 = w.na1 = 0; w.loc0 = 0; w.nloc = NSERV; w.own = 0; }
  return w;
}
#define g_flag P.s->flag
#define g_M P.s->M
#define g_Wvo P.s->Wvo
#define g_Wmo P.s->Wmo
#define g_ml P.s->ml
#define g_unsafe P.s->unsafe
#define g_cnt P.s->cnt
#define g_h P.s->h
#define g_u P.u
#define g_stat P.s->stat
#define g_qp P.s->qp
#define g_agg P.s->agg
#define g_part P.s->part
#define g_bin P.s->bin
#define g_ovf P.s->ovf

__device__ __forceinline__ uint32_t smem_u32(const void* p) { return (uint32_t)__cvta_generic_to_shared(p); }
__device__ __forceinline__ void mbar_init(uint32_t bar, uint32_t cnt) { asm volatile("mbarrier.init.shared::cta.b64 [%0], %1;" :: "r"(bar), "r"(cnt) : "memory"); }
__device__ __forceinline__ void mbar_arrive(uint32_t bar) { asm volatile("mbarrier.arrive.shared::cta.b64 _, [%0];" :: "r"(bar) : "memory"); }
__device__ __forceinline__ void mbar_expect_tx(uint32_t bar, uint32_t bytes) { asm volatile("mbarrier.arrive.expect_tx.shared::cta.b64 _, [%0], %1;" :: "r"(bar), "r"(bytes) : "memory"); }
__device__ __forceinline__ bool mbar_try_wait(uint32_t bar, uint32_t parity) {
  uint32_t ok;
  asm volatile("{\n.reg .pred p;\nmbarrier.try_wait.parity.shared::cta.b64 p, [%1], %2;\nselp.b32 %0, 1, 0, p;\n}\n" : "=r"(ok) : "r"(bar), "r"(parity) : "memory");
  return ok;
}
__device__ __forceinline__ bool mbar_try_wait_nb(uint32_t bar, uint32_t parity) {
  uint32_t ok;
  asm volatile("{\n.reg .pred p;\nmbarrier.test_wait.parity.shared::cta.b64 p, [%1], %2;\nselp.b32 %0, 1, 0, p;\n}\n" : "=r"(ok) : "r"(bar), "r"(parity) : "memory");
  return ok;
}
__device__ __forceinline__ void mbar_wait(uint32_t bar, uint32_t parity) {
#pragma unroll 1
  for (uint32_t it = 0; it < (1u << 25); it++) if (mbar_try_wait(bar, parity)) break;
}
__device__ __forceinline__ void bulk_s2g(void* dst, uint32_t src, uint32_t bytes) {
  asm volatile("cp.async.bulk.global.shared::cta.bulk_group [%0], [%1], %2;" :: "l"(dst), "r"(src), "r"(bytes) : "memory");
}
__device__ __forceinline__ void bulk_commit() { asm volatile("cp.async.bulk.commit_group;" ::: "memory"); }
__device__ __forceinline__ void bulk_wait_read() { asm volatile("cp.async.bulk.wait_group.read 0;" ::: "memory"); }
__device__ __forceinline__ void bulk_wait_all() { asm volatile("cp.async.bulk.wait_group 0;" ::: "memory"); }
__device__ __forceinline__ bool bar_red_or(int id, int cnt, bool c) {
  uint32_t r;
  asm volatile("{\n.reg .pred p, q;\nsetp.ne.b32 q, %3, 0;\nbar.red.or.pred p, %1, %2, q;\nselp.b32 %0, 1, 0, p;\n}\n"
               : "=r"(r) : "r"(id), "r"(cnt), "r"((uint32_t)c) : "memory");
  return r != 0;
}
template <class T> __device__ __forceinline__ T* pofs(const void* base, uint32_t off) {
  asm volatile("" : "+r"(off));
  return (T*)((uint8_t*)base + off);
}
__device__ __forceinline__ const void* addr64(uint32_t lo, uint32_t hi) { uint64_t a; asm("mov.b64 %0, {%1, %2};" : "=l"(a) : "r"(lo), "r"(hi)); return (const void*)a; }
__device__ __forceinline__ uint4 ldcg_v(const void* a) {
  uint4 v;
  asm volatile("ld.volatile.global.v4.u32 {%0,%1,%2,%3}, [%4];" : "=r"(v.x), "=r"(v.y), "=r"(v.z), "=r"(v.w) : "l"(a) : "memory");
  return v;
}
__device__ __forceinline__ uint4 ldcs_v(const void* a) {
  uint4 v;
  asm volatile("ld.global.cs.v4.u32 {%0,%1,%2,%3}, [%4];" : "=r"(v.x), "=r"(v.y), "=r"(v.z), "=r"(v.w) : "l"(a) : "memory");
  return v;
}
__device__ __forceinline__ void prefetch_l2(const void* a, uint32_t bytes) { asm volatile("cp.async.bulk.prefetch.L2.global [%0], %1;" :: "l"(a), "r"(bytes) : "memory"); }
__device__ __forceinline__ void ldcg_if(uint4& v, const void* a, bool c) {
  asm volatile("{\n.reg .pred p;\nsetp.ne.b32 p, %5, 0;\n@p ld.volatile.global.v4.u32 {%0,%1,%2,%3}, [%4];\n}\n"
               : "+r"(v.x), "+r"(v.y), "+r"(v.z), "+r"(v.w) : "l"(a), "r"((uint32_t)c) : "memory");
}
__device__ __forceinline__ void cp_async16(uint32_t dst, const void* src) {
  asm volatile("cp.async.cg.shared.global [%0], [%1], 16;" :: "r"(dst), "l"(src) : "memory");
}
__device__ __forceinline__ void red_bf16x8(void* a, uint4 v) {
  asm volatile("red.global.add.noftz.v4.bf16x2 [%0], {%1,%2,%3,%4};" :: "l"(a), "r"(v.x), "r"(v.y), "r"(v.z), "r"(v.w) : "memory");
}
__device__ __forceinline__ uint32_t clk() { uint32_t c; asm volatile("mov.u32 %0, %%clock;" : "=r"(c) :: "memory"); return c; }
__device__ __forceinline__ void stsm4(uint32_t a, uint32_t r0, uint32_t r1, uint32_t r2, uint32_t r3) {
  asm volatile("stmatrix.sync.aligned.m8n8.x4.shared.b16 [%0], {%1,%2,%3,%4};" :: "r"(a), "r"(r0), "r"(r1), "r"(r2), "r"(r3) : "memory");
}
__device__ __forceinline__ void ldsm4(uint32_t a, uint32_t& r0, uint32_t& r1, uint32_t& r2, uint32_t& r3) {
  asm volatile("ldmatrix.sync.aligned.m8n8.x4.shared.b16 {%0,%1,%2,%3}, [%4];" : "=r"(r0), "=r"(r1), "=r"(r2), "=r"(r3) : "r"(a) : "memory");
}
__device__ __forceinline__ void red_relaxed(uint32_t* p) { asm volatile("red.relaxed.gpu.global.add.u32 [%0], 1;" :: "l"(p) : "memory"); }
__device__ __forceinline__ uint32_t lds32(uint32_t a) { uint32_t v; asm volatile("ld.shared.u32 %0, [%1];" : "=r"(v) : "r"(a) : "memory"); return v; }
__device__ __forceinline__ void cp_commit() { asm volatile("cp.async.commit_group;" ::: "memory"); }
__device__ __forceinline__ uint32_t hmul2(uint32_t a, uint32_t b) { uint32_t d; asm("mul.rn.bf16x2 %0, %1, %2;" : "=r"(d) : "r"(a), "r"(b)); return d; }
__device__ __forceinline__ uint32_t hfma2(uint32_t a, uint32_t b, uint32_t c) { uint32_t d; asm("fma.rn.bf16x2 %0, %1, %2, %3;" : "=r"(d) : "r"(a), "r"(b), "r"(c)); return d; }
__device__ __forceinline__ uint32_t pow2_bf2(int n) { return (uint32_t)max(n + 127, 0) * 0x00800080u; }
__device__ __forceinline__ int fexp(float x) { return (int)(__float_as_uint(x) >> 23) - 127; }
__device__ __forceinline__ void bulk_g2s(uint32_t dst, const void* src, uint32_t bytes, uint32_t bar) {
  asm volatile("cp.async.bulk.shared::cta.global.mbarrier::complete_tx::bytes [%0], [%1], %2, [%3];"
    :: "r"(dst), "l"(src), "r"(bytes), "r"(bar) : "memory");
}
__device__ __forceinline__ void bulk_g2s_last(uint32_t dst, const void* src, uint32_t bytes, uint32_t bar) {
  asm volatile("{\n.reg .b64 p;\ncreatepolicy.fractional.L2::evict_first.b64 p;\n"
    "cp.async.bulk.shared::cta.global.mbarrier::complete_tx::bytes.L2::cache_hint [%0], [%1], %2, [%3], p;\n}\n"
    :: "r"(dst), "l"(src), "r"(bytes), "r"(bar) : "memory");
}
__device__ __forceinline__ void wg_fence() { asm volatile("wgmma.fence.sync.aligned;" ::: "memory"); }
__device__ __forceinline__ void wg_commit() { asm volatile("wgmma.commit_group.sync.aligned;" ::: "memory"); }
template<int N> __device__ __forceinline__ void wg_wait() { asm volatile("wgmma.wait_group.sync.aligned %0;" :: "n"(N) : "memory"); }
__device__ __forceinline__ void bar_sync(int id, int cnt) { asm volatile("bar.sync %0, %1;" :: "r"(id), "r"(cnt) : "memory"); }
__device__ __forceinline__ void fence_async_smem() { asm volatile("fence.proxy.async.shared::cta;" ::: "memory"); }
__device__ __forceinline__ void fence_async_gmem() { asm volatile("fence.proxy.async.global;" ::: "memory"); }
__device__ __forceinline__ void bar_arrive(int id, int cnt) { asm volatile("bar.arrive %0, %1;" :: "r"(id), "r"(cnt) : "memory"); }
__device__ __forceinline__ void red_release(uint32_t* p) { asm volatile("red.release.gpu.global.add.u32 [%0], 1;" :: "l"(p) : "memory"); }
__device__ __forceinline__ void red_release_w(uint32_t* p) {
  __syncwarp();
  asm volatile("{\n.reg .pred q;\n.reg .b32 l;\nmov.u32 l, %%laneid;\nsetp.eq.u32 q, l, 0;\n@q fence.release.gpu;\n@q red.relaxed.gpu.global.add.u32 [%0], 1;\n}\n" :: "l"(p) : "memory");
}
__device__ __forceinline__ void mbar_wait_w(uint32_t bar, uint32_t parity) {
#pragma unroll 1
  for (uint32_t it = 0; it < (1u << 25); it++) if (__all_sync(0xffffffffu, mbar_try_wait(bar, parity))) break;
}
#define flag_release_w(f) red_release_w(g_flag + (f))
#define flag_wait_w(f, target) poll_acquire_w(g_flag + (f), target)
#define flag_release(f) red_release(g_flag + (f))
__device__ __forceinline__ uint32_t ld_relaxed(const uint32_t* p) {
  uint32_t v; asm volatile("ld.relaxed.gpu.global.u32 %0, [%1];" : "=r"(v) : "l"(p) : "memory"); return v;
}
#define flag_wait(f, target) poll_acquire(g_flag + (f), target)
__device__ __forceinline__ void poll_acquire(const uint32_t* p, uint32_t target) {
#pragma unroll 1
  for (uint32_t it = 0; it < (1u << 23); it++) if ((int)(ld_relaxed(p) - target) >= 0) break;
  asm volatile("fence.acquire.gpu;" ::: "memory");
}
__device__ __forceinline__ void poll_acquire_w(const uint32_t* p, uint32_t target) {
#pragma unroll 1
  for (uint32_t it = 0; it < (1u << 23); it++) {
    if (__all_sync(0xffffffffu, (int)(ld_relaxed(p) - target) >= 0)) break;
    if (BACKOFF) __nanosleep(BACKOFF);
  }
  asm volatile("fence.acquire.gpu;" ::: "memory");
}
template<int N> __device__ __forceinline__ void reg_fence(float (&d)[N]) {
#pragma unroll
  for (int i = 0; i < N; i++) asm volatile("" : "+f"(d[i]) :: "memory");
}
template<int N> __device__ __forceinline__ void reg_fence(uint32_t (&d)[N]) {
#pragma unroll
  for (int i = 0; i < N; i++) asm volatile("" : "+r"(d[i]) :: "memory");
}
__device__ __forceinline__ float ex2(float x) { float y; asm("ex2.approx.ftz.f32 %0, %1;" : "=f"(y) : "f"(x)); return y; }
__device__ __forceinline__ uint32_t pack_bf16(float lo, float hi) { uint32_t r; asm("cvt.rn.bf16x2.f32 %0, %1, %2;" : "=r"(r) : "f"(hi), "f"(lo)); return r; }
__device__ __forceinline__ float bf_lo(uint32_t w) { return __uint_as_float(w << 16); }
__device__ __forceinline__ float bf_hi(uint32_t w) { return __uint_as_float(w & 0xffff0000u); }
__device__ __forceinline__ uint64_t desc_k(uint32_t addr, uint32_t add) { return (uint64_t)((((addr & 0x3FFFF) >> 4) | (1u << 16)) + add) | (0x40000100ull << 32); }
__device__ __forceinline__ uint64_t desc_mn(uint32_t addr, uint32_t add) { return (uint64_t)((((addr & 0x3FFFF) >> 4) | ((1024u >> 4) << 16)) + add) | (0x40000100ull << 32); }
__device__ __forceinline__ void sts128(uint32_t a, uint4 v) { asm volatile("st.shared.v4.u32 [%0], {%1,%2,%3,%4};" :: "r"(a), "r"(v.x), "r"(v.y), "r"(v.z), "r"(v.w) : "memory"); }
__device__ __forceinline__ uint4 lds128(uint32_t a) { uint4 v; asm volatile("ld.shared.v4.u32 {%0,%1,%2,%3}, [%4];" : "=r"(v.x), "=r"(v.y), "=r"(v.z), "=r"(v.w) : "r"(a) : "memory"); return v; }
__device__ __forceinline__ void mma16816(float (&c)[4], uint32_t a0, uint32_t a1, uint32_t a2, uint32_t a3, uint32_t b0, uint32_t b1) {
  asm volatile("mma.sync.aligned.m16n8k16.row.col.f32.bf16.bf16.f32 {%0,%1,%2,%3}, {%4,%5,%6,%7}, {%8,%9}, {%0,%1,%2,%3};"
    : "+f"(c[0]), "+f"(c[1]), "+f"(c[2]), "+f"(c[3]) : "r"(a0), "r"(a1), "r"(a2), "r"(a3), "r"(b0), "r"(b1));
}
__device__ __forceinline__ uint32_t sw_byte(int r, int c) {
  return (uint32_t)((r >> 3) * 4096 + (c >> 6) * 1024 + (r & 7) * 128 + ((((c >> 3) & 7) ^ (r & 7)) << 4) + (c & 7) * 2);
}
__device__ __forceinline__ int cta_id() { int c; asm volatile("mov.u32 %0, %%ctaid.x;" : "=r"(c)); return c; }
__device__ __forceinline__ bool tid_is(int v) { int t; asm volatile("mov.u32 %0, %%tid.x;" : "=r"(t)); return t == v; }
#define STAMP(cond, who, i)
#define CSTAMP(cond, who, i)
#define DUMP(cond, who, i0, i1)
#define XSTAMP(cond, i)
#define SSTAMP(i)

template <int OA, int OB> __device__ __forceinline__ void wgmma_ss_n256_tb(float (&d)[128], uint64_t da, uint64_t db, int scale_d) {
  asm volatile("{\n.reg .pred p;\n.reg .b64 a, b;\nsetp.ne.b32 p, %130, 0;\nadd.s64 a, %128, %131;\nadd.s64 b, %129, %132;\n"
    "wgmma.mma_async.sync.aligned.m64n256k16.f32.bf16.bf16 "
    "{%0, %1, %2, %3, %4, %5, %6, %7, %8, %9, %10, %11, %12, %13, %14, %15, %16, %17, %18, %19, %20, %21, %22, %23, %24, %25, %26, %27, %28, %29, %30, %31, %32, %33, %34, %35, %36, %37, %38, %39, %40, %41, %42, %43, %44, %45, %46, %47, %48, %49, %50, %51, %52, %53, %54, %55, %56, %57, %58, %59, %60, %61, %62, %63, %64, %65, %66, %67, %68, %69, %70, %71, %72, %73, %74, %75, %76, %77, %78, %79, %80, %81, %82, %83, %84, %85, %86, %87, %88, %89, %90, %91, %92, %93, %94, %95, %96, %97, %98, %99, %100, %101, %102, %103, %104, %105, %106, %107, %108, %109, %110, %111, %112, %113, %114, %115, %116, %117, %118, %119, %120, %121, %122, %123, %124, %125, %126, %127}, "
    "a, b, p, 1, 1, 0, 1;\n}\n"
    : "+f"(d[0]), "+f"(d[1]), "+f"(d[2]), "+f"(d[3]), "+f"(d[4]), "+f"(d[5]), "+f"(d[6]), "+f"(d[7]), "+f"(d[8]), "+f"(d[9]), "+f"(d[10]), "+f"(d[11]), "+f"(d[12]), "+f"(d[13]), "+f"(d[14]), "+f"(d[15]), "+f"(d[16]), "+f"(d[17]), "+f"(d[18]), "+f"(d[19]), "+f"(d[20]), "+f"(d[21]), "+f"(d[22]), "+f"(d[23]), "+f"(d[24]), "+f"(d[25]), "+f"(d[26]), "+f"(d[27]), "+f"(d[28]), "+f"(d[29]), "+f"(d[30]), "+f"(d[31]), "+f"(d[32]), "+f"(d[33]), "+f"(d[34]), "+f"(d[35]), "+f"(d[36]), "+f"(d[37]), "+f"(d[38]), "+f"(d[39]), "+f"(d[40]), "+f"(d[41]), "+f"(d[42]), "+f"(d[43]), "+f"(d[44]), "+f"(d[45]), "+f"(d[46]), "+f"(d[47]), "+f"(d[48]), "+f"(d[49]), "+f"(d[50]), "+f"(d[51]), "+f"(d[52]), "+f"(d[53]), "+f"(d[54]), "+f"(d[55]), "+f"(d[56]), "+f"(d[57]), "+f"(d[58]), "+f"(d[59]), "+f"(d[60]), "+f"(d[61]), "+f"(d[62]), "+f"(d[63]), "+f"(d[64]), "+f"(d[65]), "+f"(d[66]), "+f"(d[67]), "+f"(d[68]), "+f"(d[69]), "+f"(d[70]), "+f"(d[71]), "+f"(d[72]), "+f"(d[73]), "+f"(d[74]), "+f"(d[75]), "+f"(d[76]), "+f"(d[77]), "+f"(d[78]), "+f"(d[79]), "+f"(d[80]), "+f"(d[81]), "+f"(d[82]), "+f"(d[83]), "+f"(d[84]), "+f"(d[85]), "+f"(d[86]), "+f"(d[87]), "+f"(d[88]), "+f"(d[89]), "+f"(d[90]), "+f"(d[91]), "+f"(d[92]), "+f"(d[93]), "+f"(d[94]), "+f"(d[95]), "+f"(d[96]), "+f"(d[97]), "+f"(d[98]), "+f"(d[99]), "+f"(d[100]), "+f"(d[101]), "+f"(d[102]), "+f"(d[103]), "+f"(d[104]), "+f"(d[105]), "+f"(d[106]), "+f"(d[107]), "+f"(d[108]), "+f"(d[109]), "+f"(d[110]), "+f"(d[111]), "+f"(d[112]), "+f"(d[113]), "+f"(d[114]), "+f"(d[115]), "+f"(d[116]), "+f"(d[117]), "+f"(d[118]), "+f"(d[119]), "+f"(d[120]), "+f"(d[121]), "+f"(d[122]), "+f"(d[123]), "+f"(d[124]), "+f"(d[125]), "+f"(d[126]), "+f"(d[127])
    : "l"(da), "l"(db), "r"(scale_d), "n"(OA), "n"(OB));
}
template <int OA, int OB> __device__ __forceinline__ void wgmma_qk(float (&d)[64], uint64_t da, uint64_t db, int scale_d) {
  asm volatile("{\n.reg .pred p;\n.reg .b64 a, b;\nsetp.ne.b32 p, %66, 0;\nadd.s64 a, %64, %67;\nadd.s64 b, %65, %68;\n"
    "wgmma.mma_async.sync.aligned.m64n128k16.f32.bf16.bf16 "
    "{%0, %1, %2, %3, %4, %5, %6, %7, %8, %9, %10, %11, %12, %13, %14, %15, %16, %17, %18, %19, %20, %21, %22, %23, %24, %25, %26, %27, %28, %29, %30, %31, %32, %33, %34, %35, %36, %37, %38, %39, %40, %41, %42, %43, %44, %45, %46, %47, %48, %49, %50, %51, %52, %53, %54, %55, %56, %57, %58, %59, %60, %61, %62, %63}, "
    "a, b, p, 1, 1, 0, 0;\n}\n"
    : "+f"(d[0]), "+f"(d[1]), "+f"(d[2]), "+f"(d[3]), "+f"(d[4]), "+f"(d[5]), "+f"(d[6]), "+f"(d[7]), "+f"(d[8]), "+f"(d[9]), "+f"(d[10]), "+f"(d[11]), "+f"(d[12]), "+f"(d[13]), "+f"(d[14]), "+f"(d[15]), "+f"(d[16]), "+f"(d[17]), "+f"(d[18]), "+f"(d[19]), "+f"(d[20]), "+f"(d[21]), "+f"(d[22]), "+f"(d[23]), "+f"(d[24]), "+f"(d[25]), "+f"(d[26]), "+f"(d[27]), "+f"(d[28]), "+f"(d[29]), "+f"(d[30]), "+f"(d[31]), "+f"(d[32]), "+f"(d[33]), "+f"(d[34]), "+f"(d[35]), "+f"(d[36]), "+f"(d[37]), "+f"(d[38]), "+f"(d[39]), "+f"(d[40]), "+f"(d[41]), "+f"(d[42]), "+f"(d[43]), "+f"(d[44]), "+f"(d[45]), "+f"(d[46]), "+f"(d[47]), "+f"(d[48]), "+f"(d[49]), "+f"(d[50]), "+f"(d[51]), "+f"(d[52]), "+f"(d[53]), "+f"(d[54]), "+f"(d[55]), "+f"(d[56]), "+f"(d[57]), "+f"(d[58]), "+f"(d[59]), "+f"(d[60]), "+f"(d[61]), "+f"(d[62]), "+f"(d[63])
    : "l"(da), "l"(db), "r"(scale_d), "n"(OA), "n"(OB));
}
template <int OA, int OB> __device__ __forceinline__ void wgmma_qk(float (&d)[56], uint64_t da, uint64_t db, int scale_d) {
  asm volatile("{\n.reg .pred p;\n.reg .b64 a, b;\nsetp.ne.b32 p, %58, 0;\nadd.s64 a, %56, %59;\nadd.s64 b, %57, %60;\n"
    "wgmma.mma_async.sync.aligned.m64n112k16.f32.bf16.bf16 "
    "{%0, %1, %2, %3, %4, %5, %6, %7, %8, %9, %10, %11, %12, %13, %14, %15, %16, %17, %18, %19, %20, %21, %22, %23, %24, %25, %26, %27, %28, %29, %30, %31, %32, %33, %34, %35, %36, %37, %38, %39, %40, %41, %42, %43, %44, %45, %46, %47, %48, %49, %50, %51, %52, %53, %54, %55}, "
    "a, b, p, 1, 1, 0, 0;\n}\n"
    : "+f"(d[0]), "+f"(d[1]), "+f"(d[2]), "+f"(d[3]), "+f"(d[4]), "+f"(d[5]), "+f"(d[6]), "+f"(d[7]), "+f"(d[8]), "+f"(d[9]), "+f"(d[10]), "+f"(d[11]), "+f"(d[12]), "+f"(d[13]), "+f"(d[14]), "+f"(d[15]), "+f"(d[16]), "+f"(d[17]), "+f"(d[18]), "+f"(d[19]), "+f"(d[20]), "+f"(d[21]), "+f"(d[22]), "+f"(d[23]), "+f"(d[24]), "+f"(d[25]), "+f"(d[26]), "+f"(d[27]), "+f"(d[28]), "+f"(d[29]), "+f"(d[30]), "+f"(d[31]), "+f"(d[32]), "+f"(d[33]), "+f"(d[34]), "+f"(d[35]), "+f"(d[36]), "+f"(d[37]), "+f"(d[38]), "+f"(d[39]), "+f"(d[40]), "+f"(d[41]), "+f"(d[42]), "+f"(d[43]), "+f"(d[44]), "+f"(d[45]), "+f"(d[46]), "+f"(d[47]), "+f"(d[48]), "+f"(d[49]), "+f"(d[50]), "+f"(d[51]), "+f"(d[52]), "+f"(d[53]), "+f"(d[54]), "+f"(d[55])
    : "l"(da), "l"(db), "r"(scale_d), "n"(OA), "n"(OB));
}
template <int OB> __device__ __forceinline__ void wgmma_rs_n256_tb(float (&d)[128], uint32_t a0, uint32_t a1, uint32_t a2, uint32_t a3, uint64_t db, int scale_d) {
  asm volatile("{\n.reg .pred p;\n.reg .b64 b;\nsetp.ne.b32 p, %133, 0;\nadd.s64 b, %132, %134;\n"
    "wgmma.mma_async.sync.aligned.m64n256k16.f32.bf16.bf16 "
    "{%0, %1, %2, %3, %4, %5, %6, %7, %8, %9, %10, %11, %12, %13, %14, %15, %16, %17, %18, %19, %20, %21, %22, %23, %24, %25, %26, %27, %28, %29, %30, %31, %32, %33, %34, %35, %36, %37, %38, %39, %40, %41, %42, %43, %44, %45, %46, %47, %48, %49, %50, %51, %52, %53, %54, %55, %56, %57, %58, %59, %60, %61, %62, %63, %64, %65, %66, %67, %68, %69, %70, %71, %72, %73, %74, %75, %76, %77, %78, %79, %80, %81, %82, %83, %84, %85, %86, %87, %88, %89, %90, %91, %92, %93, %94, %95, %96, %97, %98, %99, %100, %101, %102, %103, %104, %105, %106, %107, %108, %109, %110, %111, %112, %113, %114, %115, %116, %117, %118, %119, %120, %121, %122, %123, %124, %125, %126, %127}, "
    "{%128, %129, %130, %131}, b, p, 1, 1, 1;\n}\n"
    : "+f"(d[0]), "+f"(d[1]), "+f"(d[2]), "+f"(d[3]), "+f"(d[4]), "+f"(d[5]), "+f"(d[6]), "+f"(d[7]), "+f"(d[8]), "+f"(d[9]), "+f"(d[10]), "+f"(d[11]), "+f"(d[12]), "+f"(d[13]), "+f"(d[14]), "+f"(d[15]), "+f"(d[16]), "+f"(d[17]), "+f"(d[18]), "+f"(d[19]), "+f"(d[20]), "+f"(d[21]), "+f"(d[22]), "+f"(d[23]), "+f"(d[24]), "+f"(d[25]), "+f"(d[26]), "+f"(d[27]), "+f"(d[28]), "+f"(d[29]), "+f"(d[30]), "+f"(d[31]), "+f"(d[32]), "+f"(d[33]), "+f"(d[34]), "+f"(d[35]), "+f"(d[36]), "+f"(d[37]), "+f"(d[38]), "+f"(d[39]), "+f"(d[40]), "+f"(d[41]), "+f"(d[42]), "+f"(d[43]), "+f"(d[44]), "+f"(d[45]), "+f"(d[46]), "+f"(d[47]), "+f"(d[48]), "+f"(d[49]), "+f"(d[50]), "+f"(d[51]), "+f"(d[52]), "+f"(d[53]), "+f"(d[54]), "+f"(d[55]), "+f"(d[56]), "+f"(d[57]), "+f"(d[58]), "+f"(d[59]), "+f"(d[60]), "+f"(d[61]), "+f"(d[62]), "+f"(d[63]), "+f"(d[64]), "+f"(d[65]), "+f"(d[66]), "+f"(d[67]), "+f"(d[68]), "+f"(d[69]), "+f"(d[70]), "+f"(d[71]), "+f"(d[72]), "+f"(d[73]), "+f"(d[74]), "+f"(d[75]), "+f"(d[76]), "+f"(d[77]), "+f"(d[78]), "+f"(d[79]), "+f"(d[80]), "+f"(d[81]), "+f"(d[82]), "+f"(d[83]), "+f"(d[84]), "+f"(d[85]), "+f"(d[86]), "+f"(d[87]), "+f"(d[88]), "+f"(d[89]), "+f"(d[90]), "+f"(d[91]), "+f"(d[92]), "+f"(d[93]), "+f"(d[94]), "+f"(d[95]), "+f"(d[96]), "+f"(d[97]), "+f"(d[98]), "+f"(d[99]), "+f"(d[100]), "+f"(d[101]), "+f"(d[102]), "+f"(d[103]), "+f"(d[104]), "+f"(d[105]), "+f"(d[106]), "+f"(d[107]), "+f"(d[108]), "+f"(d[109]), "+f"(d[110]), "+f"(d[111]), "+f"(d[112]), "+f"(d[113]), "+f"(d[114]), "+f"(d[115]), "+f"(d[116]), "+f"(d[117]), "+f"(d[118]), "+f"(d[119]), "+f"(d[120]), "+f"(d[121]), "+f"(d[122]), "+f"(d[123]), "+f"(d[124]), "+f"(d[125]), "+f"(d[126]), "+f"(d[127])
    : "r"(a0), "r"(a1), "r"(a2), "r"(a3), "l"(db), "r"(scale_d), "n"(OB));
}
template <int OB> __device__ __forceinline__ void wgmma_rs_n256_tb_first(float (&d)[128], uint32_t a0, uint32_t a1, uint32_t a2, uint32_t a3, uint64_t db) {
  asm volatile("{\n.reg .pred p;\n.reg .b64 b;\nsetp.ne.b32 p, 0, 0;\nadd.s64 b, %132, %133;\n"
    "wgmma.mma_async.sync.aligned.m64n256k16.f32.bf16.bf16 "
    "{%0, %1, %2, %3, %4, %5, %6, %7, %8, %9, %10, %11, %12, %13, %14, %15, %16, %17, %18, %19, %20, %21, %22, %23, %24, %25, %26, %27, %28, %29, %30, %31, %32, %33, %34, %35, %36, %37, %38, %39, %40, %41, %42, %43, %44, %45, %46, %47, %48, %49, %50, %51, %52, %53, %54, %55, %56, %57, %58, %59, %60, %61, %62, %63, %64, %65, %66, %67, %68, %69, %70, %71, %72, %73, %74, %75, %76, %77, %78, %79, %80, %81, %82, %83, %84, %85, %86, %87, %88, %89, %90, %91, %92, %93, %94, %95, %96, %97, %98, %99, %100, %101, %102, %103, %104, %105, %106, %107, %108, %109, %110, %111, %112, %113, %114, %115, %116, %117, %118, %119, %120, %121, %122, %123, %124, %125, %126, %127}, "
    "{%128, %129, %130, %131}, b, p, 1, 1, 1;\n}\n"
    : "=f"(d[0]), "=f"(d[1]), "=f"(d[2]), "=f"(d[3]), "=f"(d[4]), "=f"(d[5]), "=f"(d[6]), "=f"(d[7]), "=f"(d[8]), "=f"(d[9]), "=f"(d[10]), "=f"(d[11]), "=f"(d[12]), "=f"(d[13]), "=f"(d[14]), "=f"(d[15]), "=f"(d[16]), "=f"(d[17]), "=f"(d[18]), "=f"(d[19]), "=f"(d[20]), "=f"(d[21]), "=f"(d[22]), "=f"(d[23]), "=f"(d[24]), "=f"(d[25]), "=f"(d[26]), "=f"(d[27]), "=f"(d[28]), "=f"(d[29]), "=f"(d[30]), "=f"(d[31]), "=f"(d[32]), "=f"(d[33]), "=f"(d[34]), "=f"(d[35]), "=f"(d[36]), "=f"(d[37]), "=f"(d[38]), "=f"(d[39]), "=f"(d[40]), "=f"(d[41]), "=f"(d[42]), "=f"(d[43]), "=f"(d[44]), "=f"(d[45]), "=f"(d[46]), "=f"(d[47]), "=f"(d[48]), "=f"(d[49]), "=f"(d[50]), "=f"(d[51]), "=f"(d[52]), "=f"(d[53]), "=f"(d[54]), "=f"(d[55]), "=f"(d[56]), "=f"(d[57]), "=f"(d[58]), "=f"(d[59]), "=f"(d[60]), "=f"(d[61]), "=f"(d[62]), "=f"(d[63]), "=f"(d[64]), "=f"(d[65]), "=f"(d[66]), "=f"(d[67]), "=f"(d[68]), "=f"(d[69]), "=f"(d[70]), "=f"(d[71]), "=f"(d[72]), "=f"(d[73]), "=f"(d[74]), "=f"(d[75]), "=f"(d[76]), "=f"(d[77]), "=f"(d[78]), "=f"(d[79]), "=f"(d[80]), "=f"(d[81]), "=f"(d[82]), "=f"(d[83]), "=f"(d[84]), "=f"(d[85]), "=f"(d[86]), "=f"(d[87]), "=f"(d[88]), "=f"(d[89]), "=f"(d[90]), "=f"(d[91]), "=f"(d[92]), "=f"(d[93]), "=f"(d[94]), "=f"(d[95]), "=f"(d[96]), "=f"(d[97]), "=f"(d[98]), "=f"(d[99]), "=f"(d[100]), "=f"(d[101]), "=f"(d[102]), "=f"(d[103]), "=f"(d[104]), "=f"(d[105]), "=f"(d[106]), "=f"(d[107]), "=f"(d[108]), "=f"(d[109]), "=f"(d[110]), "=f"(d[111]), "=f"(d[112]), "=f"(d[113]), "=f"(d[114]), "=f"(d[115]), "=f"(d[116]), "=f"(d[117]), "=f"(d[118]), "=f"(d[119]), "=f"(d[120]), "=f"(d[121]), "=f"(d[122]), "=f"(d[123]), "=f"(d[124]), "=f"(d[125]), "=f"(d[126]), "=f"(d[127])
    : "r"(a0), "r"(a1), "r"(a2), "r"(a3), "l"(db), "n"(OB));
}
template <int OB> __device__ __forceinline__ void wgmma_rs_n128_tb(float (&d)[64], uint32_t a0, uint32_t a1, uint32_t a2, uint32_t a3, uint64_t db, int scale_d) {
  asm volatile("{\n.reg .pred p;\n.reg .b64 b;\nsetp.ne.b32 p, %69, 0;\nadd.s64 b, %68, %70;\n"
    "wgmma.mma_async.sync.aligned.m64n128k16.f32.bf16.bf16 "
    "{%0, %1, %2, %3, %4, %5, %6, %7, %8, %9, %10, %11, %12, %13, %14, %15, %16, %17, %18, %19, %20, %21, %22, %23, %24, %25, %26, %27, %28, %29, %30, %31, %32, %33, %34, %35, %36, %37, %38, %39, %40, %41, %42, %43, %44, %45, %46, %47, %48, %49, %50, %51, %52, %53, %54, %55, %56, %57, %58, %59, %60, %61, %62, %63}, "
    "{%64, %65, %66, %67}, b, p, 1, 1, 1;\n}\n"
    : "+f"(d[0]), "+f"(d[1]), "+f"(d[2]), "+f"(d[3]), "+f"(d[4]), "+f"(d[5]), "+f"(d[6]), "+f"(d[7]), "+f"(d[8]), "+f"(d[9]), "+f"(d[10]), "+f"(d[11]), "+f"(d[12]), "+f"(d[13]), "+f"(d[14]), "+f"(d[15]), "+f"(d[16]), "+f"(d[17]), "+f"(d[18]), "+f"(d[19]), "+f"(d[20]), "+f"(d[21]), "+f"(d[22]), "+f"(d[23]), "+f"(d[24]), "+f"(d[25]), "+f"(d[26]), "+f"(d[27]), "+f"(d[28]), "+f"(d[29]), "+f"(d[30]), "+f"(d[31]), "+f"(d[32]), "+f"(d[33]), "+f"(d[34]), "+f"(d[35]), "+f"(d[36]), "+f"(d[37]), "+f"(d[38]), "+f"(d[39]), "+f"(d[40]), "+f"(d[41]), "+f"(d[42]), "+f"(d[43]), "+f"(d[44]), "+f"(d[45]), "+f"(d[46]), "+f"(d[47]), "+f"(d[48]), "+f"(d[49]), "+f"(d[50]), "+f"(d[51]), "+f"(d[52]), "+f"(d[53]), "+f"(d[54]), "+f"(d[55]), "+f"(d[56]), "+f"(d[57]), "+f"(d[58]), "+f"(d[59]), "+f"(d[60]), "+f"(d[61]), "+f"(d[62]), "+f"(d[63])
    : "r"(a0), "r"(a1), "r"(a2), "r"(a3), "l"(db), "r"(scale_d), "n"(OB));
}
template <int V> using IC = std::integral_constant<int, V>;
template <int I, int N, class F> __device__ __forceinline__ void static_for(F&& f) {
  if constexpr (I < N) { f(std::integral_constant<int, I>{}); static_for<I + 1, N>(f); }
}

constexpr uint32_t SM_Q = 0, SM_BAR = 7 * 32768;
constexpr uint32_t B_FULL = SM_BAR, B_EMPTY = B_FULL + 24, B_WF = B_EMPTY + 24, B_QFULL = B_WF + 32, B_QEMPTY = B_QFULL + 16,
                   B_EVH = B_QEMPTY + 16, B_EVQ = B_EVH + 8, B_EVP0 = B_EVQ + 8, B_BG = B_EVP0 + 16, B_M0 = B_BG + 8, B_HALF = B_M0 + 8,
                   B_HRD = B_HALF + 8, SM_UNSAFE = B_HRD + 8, SM_TS = SM_UNSAFE + 8, SM_ML = (SM_TS + 192 + 15) / 16 * 16, SM_EPOCH = SM_ML + 1024, SM_END = SM_EPOCH + 16;
constexpr uint32_t POS_M = 0x5462;
constexpr int SMEM_BYTES = SM_END;

#define ROW0(u) make_uint4(pack_bf16(o[16 * u], o[16 * u + 1]), pack_bf16(o[16 * u + 4], o[16 * u + 5]), \
                           pack_bf16(o[16 * u + 8], o[16 * u + 9]), pack_bf16(o[16 * u + 12], o[16 * u + 13]))
#define ROW1(u) make_uint4(pack_bf16(o[16 * u + 2], o[16 * u + 3]), pack_bf16(o[16 * u + 6], o[16 * u + 7]), \
                           pack_bf16(o[16 * u + 10], o[16 * u + 11]), pack_bf16(o[16 * u + 14], o[16 * u + 15]))

__global__ void __cluster_dims__(2, 1, 1) __launch_bounds__(384, 1) gps_kernel(const __grid_constant__ Params P) {
  extern __shared__ __align__(1024) uint8_t smem_raw[];
  constexpr uint32_t SB = 1024;
  const uint32_t sb = smem_u32(smem_raw);
  if ((sb & 0xffffff) != SB) return;
  const int cta = blockIdx.x;
  const int wg = __shfl_sync(0xffffffffu, (int)threadIdx.x >> 7, 0);
  const int warp = __shfl_sync(0xffffffffu, ((int)threadIdx.x >> 5) & 3, 0);
  const int lane = threadIdx.x & 31;
#define ROLE                                                                                       \
  const Work& W = P.w[cta_id()];                                                                   \
  [[maybe_unused]] const int n0 = W.nb0 + W.na0, n1 = W.nb1 + W.na1, total = n0 + n1;              \
  [[maybe_unused]] const bool fin = W.role & R_FIN, tail = W.role & R_TAIL;                        \
  [[maybe_unused]] const uint32_t posw = total == 0 || tail ? POS_M : ((total & 1) ? 0x2546 : 0x4326)
  const int g = lane >> 2, t = lane & 3;
  if (wg < 2) {
    const int tid = threadIdx.x & 127;
    ROLE;
    const uint32_t sQ = sb + SM_Q + wg * 32768;
#define st0 tid_is(wg * 128)
    STAMP(st0, wg, 0);
    const int rr = lane >> 3, j = lane & 7;
    const uint32_t c0 = clk();
    while (clk() - c0 < XDELAY) {}
    const uint4* px[4];
#pragma unroll
    for (int i = 0; i < 4; i++) px[i] = (const uint4*)(P.x + (size_t)min(W.q0 * 128 + wg * 64 + warp * 16 + i * 4 + rr, NN - 1) * 256) + j;
    auto x_load = [&](int c) {
      if (c < 4) {
#pragma unroll
        for (int i = 0; i < 4; i++)
          cp_async16(sQ + warp * 8192 + (i >> 1) * 4096 + c * 1024 + ((i & 1) * 4 + rr) * 128 + ((j ^ ((i & 1) * 4 + rr)) << 4), px[i] + c * 8);
      }
      cp_commit();
    };
    if (total > 0) {
#pragma unroll
      for (int c = 0; c < XD; c++) x_load(c);
    }
    bar_sync(4, 384);
    if (wg == 1) bar_arrive(5, 256);

    const uint32_t sF = sQ + warp * 8192 + ((lane >> 3) & 1) * 4096 + (lane & 7) * 128;
    auto frag = [&](int k) { return sF + (k >> 2) * 1024 + ((((k & 3) * 2 + (lane >> 4)) ^ (lane & 7)) << 4); };
    uint32_t hq[64];
    const bool own = (W.own >> wg) & 1;
    if (total > 0) {
      float c1[4] = {0.f, 0.f, 0.f, 0.f}, ca[4] = {0.f, 0.f, 0.f, 0.f}, cb[4] = {0.f, 0.f, 0.f, 0.f};
#pragma unroll
      for (int k = 0; k < 16; k++) {
        if ((k & 3) == 0) {
          asm volatile("cp.async.wait_group %0;" :: "n"(XD - 1) : "memory");
          __syncwarp();
          x_load(k / 4 + XD);
        }
        ldsm4(frag(k), hq[4 * k], hq[4 * k + 1], hq[4 * k + 2], hq[4 * k + 3]);
        mma16816(c1, hq[4 * k], hq[4 * k + 1], hq[4 * k + 2], hq[4 * k + 3], 0x3f803f80u, 0x3f803f80u);
        mma16816(ca, hq[4 * k], hq[4 * k + 1], hq[4 * k + 2], hq[4 * k + 3], hq[4 * k], hq[4 * k + 2]);
        mma16816(cb, hq[4 * k], hq[4 * k + 1], hq[4 * k + 2], hq[4 * k + 3], hq[4 * k + 1], hq[4 * k + 3]);
      }
      const float mu0 = c1[0] * (1.0f / 256.0f), mu1 = c1[2] * (1.0f / 256.0f);
      const float v0 = fmaf(__shfl_sync(0xffffffffu, g & 1 ? ca[1] : ca[0], g * 4 + (g >> 1)), 1.0f / 256.0f, 1e-5f - mu0 * mu0);
      const float v1 = fmaf(__shfl_sync(0xffffffffu, g & 1 ? cb[3] : cb[2], g * 4 + (g >> 1)), 1.0f / 256.0f, 1e-5f - mu1 * mu1);
      float rs0, rs1;
      asm("rsqrt.approx.ftz.f32 %0, %1;" : "=f"(rs0) : "f"(v0)); asm("rsqrt.approx.ftz.f32 %0, %1;" : "=f"(rs1) : "f"(v1));
      if (W.q0 * 128 + wg * 64 + warp * 16 >= NN) rs0 = rs1 = 0.f;
      float nb0 = -mu0 * rs0, nb1 = -mu1 * rs1;
      const uint32_t sS = sb + SM_ML + (wg * 64 + warp * 16) * 8;
      if (t == 0) {
        asm volatile("st.shared.v2.f32 [%0], {%1,%2};" :: "r"(sS + g * 8), "f"(rs0), "f"(nb0) : "memory");
        asm volatile("st.shared.v2.f32 [%0], {%1,%2};" :: "r"(sS + g * 8 + 64), "f"(rs1), "f"(nb1) : "memory");
      }
      if (__any_sync(0xffffffffu, !(4.f * mu0 * mu0 <= v0) || !(4.f * mu1 * mu1 <= v1))) {
#pragma unroll 1
        for (int r = 0; r < 16; r++) {
          const uint32_t ad = sQ + warp * 8192 + (r >> 3) * 4096 + rr * 1024 + (r & 7) * 128 + ((j ^ (r & 7)) << 4);
          const uint4 v = lds128(ad);
          float f[8] = {bf_lo(v.x), bf_hi(v.x), bf_lo(v.y), bf_hi(v.y), bf_lo(v.z), bf_hi(v.z), bf_lo(v.w), bf_hi(v.w)};
          float sum = 0.f, ss = 0.f, rs;
#pragma unroll
          for (int i = 0; i < 8; i++) sum += f[i];
#pragma unroll 1
          for (int k = 1; k < 32; k *= 2) sum += __shfl_xor_sync(0xffffffffu, sum, k);
          sum *= 1.0f / 256.0f;
#pragma unroll
          for (int i = 0; i < 8; i++) { f[i] -= sum; ss += f[i] * f[i]; }
#pragma unroll 1
          for (int k = 1; k < 32; k *= 2) ss += __shfl_xor_sync(0xffffffffu, ss, k);
          asm("rsqrt.approx.ftz.f32 %0, %1;" : "=f"(rs) : "f"(fmaf(ss, 1.0f / 256.0f, 1e-5f)));
          if (W.q0 * 128 + wg * 64 + warp * 16 >= NN) rs = 0.f;
          sts128(ad, make_uint4(pack_bf16(f[0] * rs, f[1] * rs), pack_bf16(f[2] * rs, f[3] * rs), pack_bf16(f[4] * rs, f[5] * rs), pack_bf16(f[6] * rs, f[7] * rs)));
          if (lane == 0) asm volatile("st.shared.v2.f32 [%0], {%1,%2};" :: "r"(sS + r * 8), "f"(rs), "f"(-sum * rs) : "memory");
        }
        __syncwarp();
#pragma unroll
        for (int k = 0; k < 16; k++) ldsm4(frag(k), hq[4 * k], hq[4 * k + 1], hq[4 * k + 2], hq[4 * k + 3]);
        rs0 = rs1 = 1.f; nb0 = nb1 = 0.f;
      }
      asm volatile("setmaxnreg.inc.sync.aligned.u32 %0;" :: "n"(CREG));
      const uint32_t ah0 = pack_bf16(rs0, rs0), ah1 = pack_bf16(rs1, rs1), n0_ = pack_bf16(nb0, nb0), n1_ = pack_bf16(nb1, nb1);
      const uint32_t al0 = pack_bf16(rs0 - bf_lo(ah0), rs0 - bf_lo(ah0)), al1 = pack_bf16(rs1 - bf_lo(ah1), rs1 - bf_lo(ah1));
#pragma unroll
      for (int i = 0; i < 32; i++) {
        hq[2 * i] = hfma2(hq[2 * i], ah0, hfma2(hq[2 * i], al0, n0_));
        hq[2 * i + 1] = hfma2(hq[2 * i + 1], ah1, hfma2(hq[2 * i + 1], al1, n1_));
      }
      if (own) {
        const float e0 = fmaf(bf_hi(__shfl_sync(0xffffffffu, hq[62], lane | 3)), -0.5f * KS, KC), e1 = fmaf(bf_hi(__shfl_sync(0xffffffffu, hq[63], lane | 3)), -0.5f * KS, KC);
#pragma unroll
        for (int k = 0; k < 16; k++)
          stsm4(frag(k), hfma2(hq[4 * k], KS2, KC2), hfma2(hq[4 * k + 1], KS2, KC2),
                k < 15 ? hfma2(hq[4 * k + 2], KS2, KC2) : pack_bf16(fmaf(bf_lo(hq[62]), KS, e0), t == 3 ? KC : fmaf(bf_hi(hq[62]), KS, e0)),
                k < 15 ? hfma2(hq[4 * k + 3], KS2, KC2) : pack_bf16(fmaf(bf_lo(hq[63]), KS, e1), t == 3 ? KC : fmaf(bf_hi(hq[63]), KS, e1)));
      }
      __syncwarp();
      if (lane == 0) mbar_arrive(sb + B_EVH);
    } else {
      asm volatile("setmaxnreg.inc.sync.aligned.u32 %0;" :: "n"(CREG));
    }
    STAMP(st0, wg, 1);

    float o[128];
    int qph = 0, st = tail ? wg : 0, ph = 0;
    auto release = [&](int stg) { if (lane == 0) mbar_arrive(sb + B_EMPTY + 8 * stg); };
    int resume = total > 0 ? -1 : 0;
    auto fill = [&]() __attribute__((always_inline)) {
#pragma unroll
      for (int i = 0; i < 32; i++)
        asm volatile("ld.volatile.shared.v4.f32 {%0,%1,%2,%3}, [%4];" : "=f"(o[4 * i]), "=f"(o[4 * i + 1]), "=f"(o[4 * i + 2]), "=f"(o[4 * i + 3]) : "r"(sb) : "memory");
    };
    auto finish = [&]() __attribute__((always_inline)) {
      STAMP(st0, wg, 11);
      DUMP(st0, wg, 0, 16);
      if (!P.zero) { asm volatile("exit;"); __builtin_unreachable(); }
      fill();
    };
    auto run = [&](auto hot_) __attribute__((always_inline)) {
    constexpr bool HOT = hot_.value;
    const int nloc = P.w[cta_id()].nloc;
    if (!HOT && resume == 0) {
#pragma unroll 1
      for (int i = 0; i < 32; i++) {
        const int r = i * 8 + wg * 4 + warp;
        cp_async16(sb + ((POS_M >> (r >> 6) * 4) & 15) * 32768 + sw_byte(r & 63, lane * 8), (const uint4*)P.wout + r * 32 + lane);
      }
    }
    bool wide = false;
    if (HOT) {
      reg_fence(hq);
      auto qstep = [&](auto k_) {
        constexpr int k = k_.value;
        if (k < 2 || k % 4 == 0) { mbar_wait(k == 0 ? sb + B_M0 : sb + B_WF + 2 * (k & ~3), 0); if (k == 0 || k == 4) bar_sync(5 + wg, 256); wg_fence(); }
        if constexpr (k == 0) wgmma_rs_n256_tb_first<0>(o, hq[0], hq[1], hq[2], hq[3], desc_mn(SB, (POS_M & 15) * 2048));
        else wgmma_rs_n256_tb<(k & 3) * 512>(o, hq[4 * k], hq[4 * k + 1], hq[4 * k + 2], hq[4 * k + 3], desc_mn(SB, ((POS_M >> (k & ~3)) & 15) * 2048), 1);
      };
      static_for<0, 4>(qstep);
      wg_commit();
      bar_arrive(6 - wg, 256);
      wg_wait<0>();
      if (!tail) release(0);
      static_for<4, 16>(qstep);
      wg_commit();
      bar_arrive(6 - wg, 256);
      wg_wait<0>();
      reg_fence(o); reg_fence(hq);
      if (!tail) release(1);
      STAMP(st0, wg, 2);
      float c0 = (o[124] + (t == 3 ? 2.f : 1.f) * o[125]) * (-0.5f / 4.5f), c1 = (o[126] + (t == 3 ? 2.f : 1.f) * o[127]) * (-0.5f / 4.5f);
      c0 += __shfl_xor_sync(0xffffffffu, c0, 1); c1 += __shfl_xor_sync(0xffffffffu, c1, 1);
      c0 += __shfl_xor_sync(0xffffffffu, c0, 2); c1 += __shfl_xor_sync(0xffffffffu, c1, 2);
      float r0 = t == 3 ? 0.f : o[125], r1 = t == 3 ? 0.f : o[127], r2 = o[124], r3 = o[126];
#pragma unroll
      for (int i = 0; i < 31; i++) { r2 += o[4 * i]; r0 += o[4 * i + 1]; r3 += o[4 * i + 2]; r1 += o[4 * i + 3]; }
      r0 += r2; r1 += r3;
      r0 += __shfl_xor_sync(0xffffffffu, r0, 1); r1 += __shfl_xor_sync(0xffffffffu, r1, 1);
      r0 += __shfl_xor_sync(0xffffffffu, r0, 2); r1 += __shfl_xor_sync(0xffffffffu, r1, 2);
      r0 = fmaf(c0, -255.f, PSH / KC - r0); r1 = fmaf(c1, -255.f, PSH / KC - r1);
      wide = !(fabsf(c0) <= SAFE_C / KS) || !(fabsf(c1) <= SAFE_C / KS);
      if (own) mbar_wait(sb + B_HRD, 0);
#pragma unroll
      for (int k = 0; k < 16; k++)
        stsm4(frag(k),
              pack_bf16(o[8 * k] + c0, o[8 * k + 1] + c0), pack_bf16(o[8 * k + 2] + c1, o[8 * k + 3] + c1),
              pack_bf16(o[8 * k + 4] + c0, k == 15 && t == 3 ? r0 : o[8 * k + 5] + c0), pack_bf16(o[8 * k + 6] + c1, k == 15 && t == 3 ? r1 : o[8 * k + 7] + c1));
      fence_async_smem();
      __syncwarp();
      STAMP(st0, wg, 3);
      if (tail) { bar_sync(7, 256); if (wg == 0) { release(0); release(1); release(2); } }
      }

    if (HOT || resume) {
      ROLE;
      float m0, m1;
      const int qh = tail ? 0 : wg, tl = tail;
      uint32_t qo = qh * 2048;
      const uint32_t ko = (2 - tl) * 2048, stop = 1 + tl + (uint32_t)P.zero;
      float l0, l1;
      auto row_sums = [&]() { l0 = __shfl_sync(0xffffffffu, o[125] + 0.f, lane | 3); l1 = __shfl_sync(0xffffffffu, o[127] + 0.f, lane | 3); };
#define PART(u) make_uint4(pack_bf16(o[8 * u] - l0, o[8 * u + 1] - l0), pack_bf16(o[8 * u + 2] - l1, o[8 * u + 3] - l1), \
                           pack_bf16(o[8 * u + 4] - l0, o[8 * u + 5] - l0), pack_bf16(o[8 * u + 6] - l1, o[8 * u + 7] - l1))
      bool unsafe = !HOT;
      m0 = m1 = 0.f;
#pragma unroll 1
      for (int seg = HOT ? 0 : resume - 1; seg < 2; seg++) {
        ROLE;
        const bool last = __any_sync(0xffffffffu, seg || n1 == 0);
        m0 = m1 = !HOT && unsafe ? -INFINITY : 0.f;
        int first = 1;
        auto tile = [&](auto n_, bool endseg) __attribute__((always_inline)) -> bool {
          constexpr int N = n_.value;
          float s[N / 2]; uint32_t p[N / 4];
          if (!mbar_try_wait(sb + B_FULL + 8 * st, ph)) mbar_wait(sb + B_FULL + 8 * st, ph);
          const bool again = !HOT && N == 112 && first && !seg;
          if (HOT || N == 128) bar_sync(5 + wg, 256);
          else asm volatile("{\n.reg .pred p;\nsetp.eq.u32 p, %1, 0;\n@p bar.sync %0, 256;\n}\n" :: "r"(5 + wg), "r"((uint32_t)again) : "memory");
          wg_fence();
          const uint64_t dQ = desc_k(SB + SM_Q, qo), dK = desc_k(SB, ko + st * 4096);
          qo += (uint32_t)P.zero;
          static_for<0, 16>([&](auto k) { constexpr int kk = (k.value + KROT) & 15, off = (kk >> 2) * 64 + (kk & 3) * 2; wgmma_qk<off, off>(s, dQ, dK, k.value > 0); });
          wg_commit();
          if (HOT || N == 128) bar_arrive(6 - wg, 256);
          else asm volatile("{\n.reg .pred p;\nsetp.eq.u32 p, %1, 0;\n@p bar.arrive %0, 256;\n}\n" :: "r"(6 - wg), "r"((uint32_t)again) : "memory");
          if (HOT && N == 112 && first && !seg) {
            float a0 = 0.f, a1 = 0.f, a2 = 0.f, a3 = 0.f;
#pragma unroll
            for (int i = 0; i < 32; i++) { a0 += o[4 * i] * o[4 * i]; a2 += o[4 * i + 1] * o[4 * i + 1]; a1 += o[4 * i + 2] * o[4 * i + 2]; a3 += o[4 * i + 3] * o[4 * i + 3]; }
            a0 += a2; a1 += a3;
            a0 += __shfl_xor_sync(0xffffffffu, a0, 1); a1 += __shfl_xor_sync(0xffffffffu, a1, 1);
            a0 += __shfl_xor_sync(0xffffffffu, a0, 2); a1 += __shfl_xor_sync(0xffffffffu, a1, 2);
            unsafe = __any_sync(0xffffffffu, bar_red_or(tail ? 7 : 1 + wg, tail ? 256 : 128, wide || !(a0 <= SAFE_N2 / (KS * KS)) || !(a1 <= SAFE_N2 / (KS * KS))));
            if (lane == 0) { asm volatile("st.shared.u8 [%0], %1;" :: "r"(sb + SM_UNSAFE + wg), "r"((uint32_t)unsafe) : "memory"); mbar_arrive(sb + B_EVQ); }
          }
          STAMP(N == 112 && first && !seg && st0, wg, 0);
          wg_wait<0>();
          reg_fence(s);
          if (HOT && N == 112 && unsafe) return true;
          if (endseg) { if (lane == 0) mbar_arrive(sb + B_QEMPTY + 8 * wg); }
          if (!HOT && unsafe) {
            float a0 = fmaxf(s[0], s[1]), a1 = fmaxf(s[2], s[3]);
#pragma unroll
            for (int i = 1; i < N / 8; i++) { a0 = fmaxf(a0, fmaxf(s[4 * i], s[4 * i + 1])); a1 = fmaxf(a1, fmaxf(s[4 * i + 2], s[4 * i + 3])); }
            if (__any_sync(0xffffffffu, (a0 > m0 + TAU) || (a1 > m1 + TAU))) {
              a0 = fmaxf(a0, __shfl_xor_sync(0xffffffffu, a0, 1)); a1 = fmaxf(a1, __shfl_xor_sync(0xffffffffu, a1, 1));
              a0 = fmaxf(a0, __shfl_xor_sync(0xffffffffu, a0, 2)); a1 = fmaxf(a1, __shfl_xor_sync(0xffffffffu, a1, 2));
              const float x0 = ceilf(fmaxf(m0, a0)), x1 = ceilf(fmaxf(m1, a1)), sc0 = ex2(m0 - x0), sc1 = ex2(m1 - x1);
              m0 = x0; m1 = x1;
#pragma unroll
              for (int i = 0; i < 32; i++) { o[4 * i] *= sc0; o[4 * i + 1] *= sc0; o[4 * i + 2] *= sc1; o[4 * i + 3] *= sc1; }
            }
#pragma unroll
            for (int i = 0; i < N / 8; i++) { s[4 * i] -= m0; s[4 * i + 1] -= m0; s[4 * i + 2] -= m1; s[4 * i + 3] -= m1; }
          }
          auto pv = [&](auto k) { wgmma_rs_n256_tb<k.value * 512 + (63 << 16)>(o, p[4 * k.value], p[4 * k.value + 1], p[4 * k.value + 2], p[4 * k.value + 3], dK, k.value > 0 || N == 128 ? 1 : !first); };
#pragma unroll
          for (int i = 0; i < 16; i++) { p[i] = pack_bf16(ex2(s[2 * i]), ex2(s[2 * i + 1])); asm volatile("" : "+r"(p[i]) :: "memory"); }
          reg_fence(o);
          do bar_sync(5 + wg, 256); while (P.zero);
          wg_fence();
          static_for<0, 4>(pv);
          wg_commit();
#pragma unroll
          for (int i = 16; i < N / 4; i++) { p[i] = pack_bf16(ex2(s[2 * i]), ex2(s[2 * i + 1])); asm volatile("" : "+r"(p[i]) :: "memory"); }
          wg_fence();
          static_for<4, N / 16>(pv);
          wg_commit();
          bar_arrive(6 - wg, 256);
          if (N == 128) { wg_wait<1>(); if (endseg && last) { if (lane == 0) mbar_arrive(sb + B_HALF); } }
          wg_wait<0>();
          reg_fence(o); reg_fence(p);
          release(st);
          if (st) { st--; ph ^= 1; } else st = stop;
          return false;
        };
#pragma unroll 1
        for (int left = tail ? 8 - wg : (seg ? W.nb1 : W.nb0); left > 0; left--) { if (tile(IC<112>{}, false)) { resume = 1; return; } STAMP(first && !seg && st0, wg, 4); first = 0; }
#pragma unroll 1
        for (int left = tail ? 32 + wg : (seg ? W.na1 : W.na0); left > 0; left--) tile(IC<128>{}, left == 1);
        STAMP(st0 && last, wg, 6);
        {
        ROLE;
        if (last && fin && !(tail && wg == 1)) break;
        row_sums();
        if (last) mbar_wait(sb + (tail ? B_QEMPTY : B_HALF), 0);
        const uint32_t sp = sb + (tail ? 0 : (last ? (posw >> 12) + wg : (wg ? 4 - 2 * st : 6))) * 32768, sm = sb + SM_ML + (tail ? 0 : wg) * 512;
#pragma unroll
        for (int u = 0; u < 16; u++) sts128(sp + (u * 128 + tid) * 16, PART(u));
        if (t == 0) {
          asm volatile("st.shared.v2.f32 [%0], {%1,%2};" :: "r"(sm + (warp * 16 + g) * 8), "f"(m0), "f"(l0) : "memory");
          asm volatile("st.shared.v2.f32 [%0], {%1,%2};" :: "r"(sm + (warp * 16 + g) * 8 + 64), "f"(m1), "f"(l1) : "memory");
        }
        __syncwarp();
        if (lane == 0) mbar_arrive(sb + B_EVP0 + 8 * wg);
        STAMP(st0 && last, wg, 7);
        if (last) break;
        mbar_wait(sb + B_QFULL + 8 * wg, qph); qph ^= 1;
        uint32_t u; asm volatile("ld.shared.u8 %0, [%1];" : "=r"(u) : "r"(sb + SM_UNSAFE + wg) : "memory");
        unsafe = __any_sync(0xffffffffu, u != 0);
        if (HOT && unsafe) { resume = 2; return; }
        }
      }

      if (P.w[cta_id()].role & R_FIN) {
        ROLE;
        if (!(tail && wg == 1)) {
        row_sums();
        const int rl = wg * 64 + warp * 16 + g;
        uint32_t a[64];
#pragma unroll
        for (int i = 0; i < 64; i++) a[i] = pack_bf16(o[2 * i] - (i & 1 ? l1 : l0), o[2 * i + 1] - (i & 1 ? l1 : l0));
        reg_fence(a);
        {
          float2 e0, e1;
          mbar_wait(sb + B_QFULL + 8 * wg, qph);
          asm volatile("ld.shared.v2.f32 {%0,%1}, [%2];" : "=f"(e0.x), "=f"(e0.y) : "r"(sb + SM_ML + rl * 8) : "memory");
          asm volatile("ld.shared.v2.f32 {%0,%1}, [%2];" : "=f"(e1.x), "=f"(e1.y) : "r"(sb + SM_ML + rl * 8 + 64) : "memory");
          STAMP(st0, wg, 7);
          uint32_t fb0 = 0x3f803f80u, fb1 = 0x3f803f80u;
          const float s0 = l0 + e0.y, s1 = l1 + e1.y;
          const bool odd = __any_sync(0xffffffffu, m0 != e0.x || m1 != e1.x || !(fmaxf(s0, s1) < 0x1p40f) || !(fminf(s0, s1) > 0x1p-40f));
          if (HOT && odd) { resume = 3; return; }
          uint4 v[16];
#pragma unroll
          for (int u = 0; u < 16; u++) v[u] = lds128(sQ + (u * 128 + tid) * 16);
          if (!HOT && odd) {
            const float x0 = fmaxf(m0, e0.x), x1 = fmaxf(m1, e1.x);
            const float d0 = fmaxf(m0 - x0, -1000.f), d1 = fmaxf(m1 - x1, -1000.f), f0 = fmaxf(e0.x - x0, -1000.f), f1 = fmaxf(e1.x - x1, -1000.f);
            l0 = l0 * ex2(d0) + e0.y * ex2(f0); l1 = l1 * ex2(d1) + e1.y * ex2(f1);
            const int E0 = fexp(l0), E1 = fexp(l1);
            const uint32_t fa0 = pow2_bf2((int)d0 - E0), fa1 = pow2_bf2((int)d1 - E1);
            fb0 = pow2_bf2((int)f0 - E0); fb1 = pow2_bf2((int)f1 - E1);
            l0 = __uint_as_float(__float_as_uint(l0) - (E0 << 23)); l1 = __uint_as_float(__float_as_uint(l1) - (E1 << 23));
#pragma unroll
            for (int i = 0; i < 32; i++) { a[2 * i] = hmul2(a[2 * i], fa0); a[2 * i + 1] = hmul2(a[2 * i + 1], fa1); }
          } else { l0 = s0; l1 = s1; }
#pragma unroll
          for (int u = 0; u < 16; u++) {
            a[4 * u] = hfma2(v[u].x, fb0, a[4 * u]); a[4 * u + 1] = hfma2(v[u].y, fb1, a[4 * u + 1]);
            a[4 * u + 2] = hfma2(v[u].z, fb0, a[4 * u + 2]); a[4 * u + 3] = hfma2(v[u].w, fb1, a[4 * u + 3]);
          }
        }
        float fs0, fs1;
        asm("rcp.approx.ftz.f32 %0, %1;" : "=f"(fs0) : "f"(l0 * (KS / KC))); asm("rcp.approx.ftz.f32 %0, %1;" : "=f"(fs1) : "f"(l1 * (KS / KC)));
        STAMP(st0, wg, 8);
        reg_fence(a);
        bar_sync(5 + wg, 256);
        uint64_t dW[4];
        float y0[64], y1[64];
        auto half0 = [&](auto u_) {
          constexpr int u = u_.value;
          if (u % 4 == 0) { mbar_wait(sb + B_WF + 2 * u, 1); wg_fence(); dW[u / 4] = desc_mn(SB, ((posw >> u) & 15) * 2048); }
          wgmma_rs_n128_tb<(u & 3) * 512>(y0, a[4 * u], a[4 * u + 1], a[4 * u + 2], a[4 * u + 3], dW[u / 4], u != 0);
        };
        auto half1 = [&](auto u_) {
          constexpr int u = u_.value;
          wgmma_rs_n128_tb<(u & 3) * 512 + 128>(y1, a[4 * u], a[4 * u + 1], a[4 * u + 2], a[4 * u + 3], dW[u / 4], u != 0);
        };
        const bool wr = W.q0 * 128 + wg * 64 + warp * 16 < NN;
        uint4* po = (uint4*)(P.out + (size_t)(W.q0 * 128 + rl) * 256) + t;
        auto emit = [&](const float* y, uint4* dst) {
          if (wr && (!(DBG & 2) || P.zero)) {
            OUTW(dst, make_uint4(pack_bf16(y[0] * fs0, y[1] * fs0), pack_bf16(y[4] * fs0, y[5] * fs0), pack_bf16(y[8] * fs0, y[9] * fs0), pack_bf16(y[12] * fs0, y[13] * fs0)));
            OUTW(dst + 8 * 32, make_uint4(pack_bf16(y[2] * fs1, y[3] * fs1), pack_bf16(y[6] * fs1, y[7] * fs1), pack_bf16(y[10] * fs1, y[11] * fs1), pack_bf16(y[14] * fs1, y[15] * fs1)));
          }
          wg_fence();
        };
        static_for<0, 16>(half0);
        wg_commit();
        static_for<0, 4>(half1);
        wg_commit();
        wg_wait<1>();
        reg_fence(y0);
        emit(y0, po); static_for<4, 8>(half1);
        emit(y0 + 16, po + 4); static_for<8, 12>(half1);
        emit(y0 + 32, po + 8); static_for<12, 16>(half1);
        wg_commit();
        bar_arrive(6 - wg, 256);
        emit(y0 + 48, po + 12);
        wg_wait<0>();
        reg_fence(a); reg_fence(y1);
        STAMP(st0, wg, 9);
#pragma unroll
        for (int u = 0; u < 4; u++) emit(y1 + 16 * u, po + 16 + 4 * u);
        }
        finish();
      }
        }
#pragma unroll 1
    for (int step = HOT || resume ? 0 : -4; step < nloc; step++) {
      ROLE;
      const bool isw = !HOT && step < 0;
      if (isw) {
        const uint4* src = (const uint4*)(step < -2 ? P.wmsg : P.wv) + ((step & 1) * 128 + wg * 64 + warp) * 32 + lane;
        float cw[8] = {0.f, 0.f, 0.f, 0.f, 0.f, 0.f, 0.f, 0.f};
#pragma unroll 1
        for (int i = 0; i < 16; i++) cp_async16(sQ + sw_byte(i * 4 + warp, lane * 8), src + i * 128);
        cp_commit();
#pragma unroll
        for (int i = 0; i < 8; i++) {
          const uint4 v = __ldg((const uint4*)(step < -2 ? P.wmsg : P.wv) + (248 + i) * 32 + lane);
          const float k = step < -2 ? 0.f : (i == 7 ? -1.0f / 4.5f : -0.5f / 4.5f);
          cw[0] += bf_lo(v.x) * k; cw[1] += bf_hi(v.x) * k; cw[2] += bf_lo(v.y) * k; cw[3] += bf_hi(v.y) * k;
          cw[4] += bf_lo(v.z) * k; cw[5] += bf_hi(v.z) * k; cw[6] += bf_lo(v.w) * k; cw[7] += bf_hi(v.w) * k;
        }
        asm volatile("cp.async.wait_group 0;" ::: "memory");
#pragma unroll 1
        for (int i = 0; i < 16; i++) {
          const uint32_t ad = sQ + sw_byte(i * 4 + warp, lane * 8);
          const uint4 v = lds128(ad);
          uint4 w4 = make_uint4(pack_bf16(bf_lo(v.x) + cw[0], bf_hi(v.x) + cw[1]), pack_bf16(bf_lo(v.y) + cw[2], bf_hi(v.y) + cw[3]),
                                pack_bf16(bf_lo(v.z) + cw[4], bf_hi(v.z) + cw[5]), pack_bf16(bf_lo(v.w) + cw[6], bf_hi(v.w) + cw[7]));
          if (step == -1 && wg * 64 + i * 4 + warp == 127) w4 = make_uint4(0, 0, 0, 0);
          sts128(ad, w4);
        }
        fence_async_smem();
        bar_sync(7, 256);
      } else {
        SSTAMP(0);
        mbar_wait(sb + B_QFULL + 8 * wg, qph); qph ^= 1;
        STAMP(st0 && step == 0, wg, 8);
        SSTAMP(1);
        bar_sync(5 + wg, 256);
        SSTAMP(2);
      }
#pragma unroll 1
      for (int c = 0; c < 4; c++) {
        if (step == 0) mbar_wait(sb + B_WF + 8 * c, HOT || resume);
        const int turn2 = HOT || resume ? 3 : 4;
        if (c == turn2) bar_sync(5 + wg, 256);
        wg_fence();
        const uint64_t dA = desc_k(SB + SM_Q, wg * 2048 + c * 64), dW = desc_mn(SB, ((posw >> c * 4) & 15) * 2048);
        static_for<0, 4>([&](auto k) { wgmma_ss_n256_tb<k.value * 2, k.value * 512>(o, dA, dW, k.value > 0 ? 1 : c); });
        wg_commit();
        if ((c == 3 || c == turn2 - 1) && !isw) bar_arrive(6 - wg, 256);
        wg_wait<1>();
      }
      wg_wait<0>();
      reg_fence(o);
      {
        STAMP(st0 && step == 0, wg, 9);
        SSTAMP(3);
        if (isw) bar_sync(1 + wg, 128); else if (lane == 0) mbar_arrive(sb + B_QEMPTY + 8 * wg);
        uint8_t* dw = (uint8_t*)(step < -2 ? g_Wmo : g_Wvo) + ((step & 1) * 2 + wg) * 32768 + warp * 8192 + g * 128;
        const int row0 = (W.loc0 + step) * 128 + wg * 64 + warp * 16;
        uint4 r[16];
#pragma unroll
        for (int u = 0; u < 8; u++) { r[2 * u] = ROW0(u); r[2 * u + 1] = ROW1(u); }
        if (isw) {
#pragma unroll
          for (int u = 0; u < 16; u++) *(uint4*)(dw + (u >> 2) * 1024 + ((((u & 2) * 2 + t) ^ g) << 4) + (u & 1) * 4096) = r[u];
        } else if (row0 < NN) {
          uint4* po = (uint4*)(P.out + (size_t)(row0 + g) * 256) + t;
          uint32_t c1 = clk();
#pragma unroll
          for (int u = 0; u < 16; u++) {
            if (!(DBG & 1) || !HOT || P.zero) red_bf16x8(po + (u >> 1) * 4 + (u & 1) * 256, r[u]);
            if (!HOT) { c1 += PACE; while ((int)(clk() - c1) < 0) {} }
          }
        }
        if (!HOT && step == -1) { bar_sync(7, 256); if (tid_is(0)) flag_release(F_W); __syncwarp(); STAMP(st0, wg, 3); }
      }
    }
    finish();
    };
    if (resume < 0) run(std::true_type{});
    else fill();
    run(std::false_type{});
    asm volatile("setmaxnreg.dec.sync.aligned.u32 %0;" :: "n"(504 - 2 * CREG));
  } else {
    STAMP(lane == 0 && warp == 0, 2, 0);
        const int mi = cta >> 3;
    const uint32_t sW = sb + 3 * 32768;
    uint4 wa[4], wb[8];
    {
      const uint4* pq = (const uint4*)(P.wq + ((mi & 15) * 16 + g) * 256) + warp * 8 + t;
      const uint4* pk = (const uint4*)(P.wk + ((cta & 7) * 32 + g) * 256) + warp * 8 + t;
#pragma unroll
      for (int i = 0; i < 4; i++) wa[i] = __ldg(pq + (i >> 1) * 256 + (i & 1) * 4);
#pragma unroll
      for (int i = 0; i < 8; i++) wb[i] = __ldg(pk + (i >> 1) * 256 + (i & 1) * 4);
    }
    if (threadIdx.x == 352) {
      for (int i = 0; i < 3; i++) { mbar_init(sb + B_FULL + 8 * i, 1); mbar_init(sb + B_EMPTY + 8 * i, cta == 130 ? 4 : 8); }
      for (int i = 0; i < 4; i++) mbar_init(sb + B_WF + 8 * i, 1);
      for (int i = 0; i < 2; i++) { mbar_init(sb + B_QFULL + 8 * i, 1); mbar_init(sb + B_QEMPTY + 8 * i, 4); mbar_init(sb + B_EVP0 + 8 * i, 4); }
      mbar_init(sb + B_EVH, 8); mbar_init(sb + B_EVQ, 8); mbar_init(sb + B_HALF, 8); mbar_init(sb + B_BG, 1); mbar_init(sb + B_M0, 1); mbar_init(sb + B_HRD, 1);
      asm volatile("fence.mbarrier_init.release.cluster;" ::: "memory");
    }
    __syncwarp();
    bar_sync(4, 384);
    {
#pragma unroll
      for (int n = 0; n < 4; n++) {
        float c[4] = {0.f, 0.f, 0.f, 0.f};
#pragma unroll
        for (int u = 0; u < 2; u++) {
          mma16816(c, wa[u].x, wa[2 + u].x, wa[u].y, wa[2 + u].y, wb[2 * n + u].x, wb[2 * n + u].y);
          mma16816(c, wa[u].z, wa[2 + u].z, wa[u].w, wa[2 + u].w, wb[2 * n + u].z, wb[2 * n + u].w);
        }
        asm volatile("st.shared.v2.f32 [%0], {%1,%2};" :: "r"(sW + ((warp * 16 + g) * 40 + n * 8 + 2 * t) * 4), "f"(c[0]), "f"(c[1]) : "memory");
        asm volatile("st.shared.v2.f32 [%0], {%1,%2};" :: "r"(sW + ((warp * 16 + g + 8) * 40 + n * 8 + 2 * t) * 4), "f"(c[2]), "f"(c[3]) : "memory");
      }
      STAMP(lane == 0 && warp == 0, 2, 7);
      bar_sync(3, 128);
      if (warp < 2) {
        float c[8] = {0.f, 0.f, 0.f, 0.f, 0.f, 0.f, 0.f, 0.f};
#pragma unroll
        for (int k = 0; k < 4; k++) {
          const uint4 v = lds128(sW + ((k * 16 + warp * 8 + g) * 40 + t * 8) * 4), w = lds128(sW + ((k * 16 + warp * 8 + g) * 40 + t * 8 + 4) * 4);
          c[0] += __uint_as_float(v.x); c[1] += __uint_as_float(v.y); c[2] += __uint_as_float(v.z); c[3] += __uint_as_float(v.w);
          c[4] += __uint_as_float(w.x); c[5] += __uint_as_float(w.y); c[6] += __uint_as_float(w.z); c[7] += __uint_as_float(w.w);
        }
        const float ms = 1.4426950408889634f / 16.0f / KS;
        const uint4 m4 = make_uint4(pack_bf16(c[0] * ms, c[1] * ms), pack_bf16(c[2] * ms, c[3] * ms), pack_bf16(c[4] * ms, c[5] * ms), pack_bf16(c[6] * ms, c[7] * ms));
        sts128(sW + 16384 + (warp * 8 + g) * 64 + ((t ^ (g & 3)) << 4), m4);
      }
    }
    asm volatile("setmaxnreg.dec.sync.aligned.u32 %0;" :: "n"(504 - 2 * CREG));
    STAMP(lane == 0 && warp == 0, 2, 13);
    bar_sync(3, 128);
#define ep1 (lds32(sb + SM_EPOCH) + 1)
    if (threadIdx.x == 256 && cta < 128) {
      {
        fence_async_smem();
#pragma unroll 1
        for (int r = 0; r < 16; r++)
          bulk_s2g((uint8_t*)g_M + (mi * 2 + (r >> 3)) * 4096 + ((cta & 7) >> 1) * 1024 + (r & 7) * 128 + ((((cta & 1) * 4) ^ (r & 4)) << 4), sW + 16384 + r * 64, 64);
        bulk_commit();
        bulk_wait_all();
        red_relaxed(g_flag + F_M + (cta >> 5));
      }
    }
    __syncwarp();
    ROLE;
    if (warp == 3 && W.own) {
      mbar_wait_w(sb + B_EVH, 0);
      if (W.role < R_SIG) mbar_wait_w(sb + B_WF + 8, 0);
      if (lane == 0) {
        fence_async_smem();
        const int h0 = W.own == 2, nh = W.own == 3 ? 2 : 1;
        bulk_s2g(g_h + W.hp * 4096 + h0 * 2048, sb + SM_Q + h0 * 32768, nh * 32768);
        bulk_s2g(g_stat + W.q0 * 128 + h0 * 64, sb + SM_ML + h0 * 512, nh * 512);
        bulk_commit();
        bulk_wait_read();
        mbar_arrive(sb + B_HRD);
        bulk_wait_all();
        if (W.role >= R_SIG) red_relaxed(g_flag + F_H1 - 1 + W.role / R_SIG);
        red_relaxed(g_flag + F_H);
      }
      __syncwarp();
      STAMP(lane == 0, 2, 6);
    }
    if (warp == 0) {
      if (lane == 0) {
        STAMP(true, 2, 1);
        const uint32_t epoch = ld_relaxed(g_flag + F_EPOCH);
        if (total > 0) {
#pragma unroll
          for (int c = 0; c < 3; c++) mbar_expect_tx(sb + B_WF + 8 * c, c == 0 ? WCH_B - 8192 : WCH_B);
          mbar_expect_tx(sb + B_M0, 8192);
          int c = 0;
#pragma unroll 1
          for (uint32_t it = 0; c < 4; it++) {
            uint4 f;
            asm volatile("ld.relaxed.gpu.global.v4.u32 {%0,%1,%2,%3}, [%4];" : "=r"(f.x), "=r"(f.y), "=r"(f.z), "=r"(f.w) : "l"(g_flag + F_M) : "memory");
            uint32_t tm;
            asm volatile("mad.lo.u32 %0, %1, 32, 32;" : "=r"(tm) : "r"(epoch));
            int ok = (int)(f.x - tm) < 0 ? 0 : (int)(f.y - tm) < 0 ? 1 : (int)(f.z - tm) < 0 ? 2 : (int)(f.w - tm) < 0 ? 3 : 4;
            if (it > (1u << 23)) ok = 4;
            if (ok > c) {
              asm volatile("fence.acquire.gpu;" ::: "memory"); fence_async_gmem();
              if (c == 0) bulk_g2s(sb + (POS_M & 15) * 32768, g_M, 8192, sb + B_M0);
            }
#pragma unroll 1
            for (; c < ok; c++) {
              const uint32_t skip = c == 0 ? 8192 : 0;
              bulk_g2s(sb + ((POS_M >> c * 4) & 15) * 32768 + skip, pofs<const uint8_t>(g_M, c * WCH_B + skip), WCH_B - skip, sb + B_WF + 8 * c);
              STAMP(c == 0, 2, 2);
            }
          }
        }
        asm volatile("st.shared.u32 [%0], %1;" :: "r"(sb + SM_EPOCH), "r"(epoch) : "memory");
        if (total > 0) mbar_expect_tx(sb + B_WF + 24, WCH_B);
        int st = 0, ph = 0, qph = 0;
        const int nsl = tail ? 3 : 2;
        auto next_slot = [&]() { mbar_wait(sb + B_EMPTY + 8 * st, ph); if (++st == nsl) { st = 0; ph ^= 1; } };
        auto w_load = [&](int c0, int c1) {
#pragma unroll 1
          for (int c = c0; c < c1; c++) {
            mbar_expect_tx(sb + B_WF + 8 * c, WCH_B);
            bulk_g2s(sb + ((posw >> c * 4) & 15) * 32768, pofs<const uint8_t>(fin ? g_Wvo : g_Wmo, c * WCH_B), WCH_B, sb + B_WF + 8 * c);
          }
        };
        auto q_load = [&](const uint4* src, bool wait_empty) {
#pragma unroll 1
          for (int h = 0; h < 2; h++) {
            if (wait_empty) mbar_wait(sb + B_QEMPTY + 8 * h, qph);
            mbar_expect_tx(sb + B_QFULL + 8 * h, 32768);
            (HINT & 2 ? bulk_g2s_last : bulk_g2s)(sb + SM_Q + h * 32768, src + h * 2048, 32768, sb + B_QFULL + 8 * h);
          }
          if (wait_empty) qph ^= 1;
        };
        auto part_out = [&](int slot, int h, uint32_t region, int parity) {
          mbar_wait(sb + B_EVP0 + 8 * h, parity);
          fence_async_smem();
          bulk_s2g(g_part + slot * 4096 + h * 2048, sb + region * 32768, 32768);
          bulk_s2g(g_ml + slot * 128 + h * 64, sb + SM_ML + h * 512, 512);
          bulk_commit();
        };
        auto announce = [&](int f) {
          if (RELF) { fence_async_gmem(); flag_release(f); }
          else red_relaxed(g_flag + f);
        };
        if (total > 0) {
          STAMP(true, 2, 3);
          const int q1 = W.q0 + 2 * W.own - 3;
          if (!tail) { flag_wait(F_H1 + (fin ? 0 : W.own), ep1 * (fin ? NH1_0 : (W.own == 1 ? NH1_1 : NH1_2))); fence_async_gmem(); }
          STAMP(true, 2, 4);
          uint32_t ko = W.k0 * 8192;
#pragma unroll 1
          for (int j = 0; j < total; j++) {
            if (j == (tail ? 0 : 1)) { flag_wait(F_H, ep1 * NHSIG); fence_async_gmem(); }
            if (j == n0) {
              flag_wait(F_QP + q1 * LN_, ep1); fence_async_gmem();
              const uint32_t u = __ldcg(g_unsafe + q1);
              asm volatile("st.shared.u32 [%0], %1;" :: "r"(sb + SM_UNSAFE), "r"(u) : "memory");
              ko = W.k1 * 8192;
            }
            if (j == n0 + 1) q_load(g_qp + q1 * 4096, true);
            if (j == total - 1) { flag_wait(F_W, ep1); fence_async_gmem(); if (!tail) w_load(0, 1); }
            const uint32_t bytes = (j < n0 ? j < W.nb0 : j - n0 < W.nb1) ? 112 * 512 : 128 * 512, s0 = st;
            const uint32_t region = (tail ? 1 : 2) + 2 * s0, skip = j == n0 + 1 ? 32768 : 0;
            if (skip) part_out(W.slotA, 0, 6, 0);
            next_slot();
            mbar_expect_tx(sb + B_FULL + 8 * s0, bytes);
            bulk_g2s(sb + region * 32768 + skip, pofs<const uint8_t>(g_h, ko + skip), bytes - skip, sb + B_FULL + 8 * s0);
            if (skip) {
              part_out(W.slotA, 1, region, 0);
              bulk_wait_read();
              bulk_g2s(sb + region * 32768, pofs<const uint8_t>(g_h, ko), skip, sb + B_FULL + 8 * s0);
              bulk_wait_all();
              announce(F_PART + W.slotA * LN_);
            }
            ko += bytes;
          }
          next_slot();
          if (tail) { next_slot(); next_slot(); }
        } else { flag_wait(F_W, ep1); fence_async_gmem(); }
        STAMP(true, 2, 5);
        const bool staged = total > 0 && !tail;
        w_load(staged, staged ? (fin ? 2 : 3) : 4);
#pragma unroll 1
        for (int i = 0; i < W.nloc; i++) {
          const int tl = W.loc0 + i, last = tl * 128 + 127 < NN ? tl * 128 + 127 : NN - 1;
          flag_wait(F_AGG + ((last >= NGW) + (last >= 4 * NGW) + (last >= 9 * NGW)) * LN_, ep1 * NGW); fence_async_gmem();
          if (total == 0) g_flag[F_EPOCH] = epoch + 1;
          q_load(g_agg + tl * 4096, total > 0 || i > 0);
        }
        if (tail) { mbar_wait(sb + B_BG, 0); mbar_wait(sb + B_EVP0 + 8, 0); mbar_arrive(sb + B_QFULL); }
        else if (fin) {
          int h = 0, c = 2, have = W.slotB >= 0 || (DBG & 8) ? 2 : 0;
          mbar_wait(sb + B_BG, 0);
#pragma unroll 1
          for (uint32_t it = 0; (h < 2 || c < 4) && it < (1u << 23); it++) {
            if (have < 2) {
              uint2 f;
              asm volatile("ld.relaxed.gpu.global.v2.u32 {%0,%1}, [%2];" : "=r"(f.x), "=r"(f.y) : "l"(g_flag + F_PART + W.slotA * LN_) : "memory");
              have = (int)(f.x - (epoch + 1)) < 0 ? 0 : ((int)(f.y - (epoch + 1)) < 0 ? 1 : 2);
            }
            if (h < have && mbar_try_wait_nb(sb + B_QEMPTY + 8 * h, 0)) {
              asm volatile("fence.acquire.gpu;" ::: "memory"); fence_async_gmem();
              STAMP(true, 2, 14 + h);
              mbar_expect_tx(sb + B_QFULL + 8 * h, 32768 + 512);
              bulk_g2s(sb + SM_ML + h * 512, g_ml + W.slotA * 128 + h * 64, 512, sb + B_QFULL + 8 * h);
              bulk_g2s(sb + SM_Q + h * 32768, g_part + W.slotA * 4096 + h * 2048, 32768, sb + B_QFULL + 8 * h);
              h++;
            }
            const bool half = mbar_try_wait_nb(sb + B_HALF, 0);
            const int c1 = half ? 4 : (h > 0 ? 3 : 2);
            if (c < c1) { w_load(c, c1); c = c1; }
          }
        } else if (total > 0) {
#pragma unroll 1
          for (int h = 0; h < 2; h++) part_out(W.slotB, h, (posw >> 12) + h, 1);
          asm volatile("cp.async.bulk.wait_group.read 1;" ::: "memory");
          w_load(3, 4);
          asm volatile("cp.async.bulk.wait_group 1;" ::: "memory");
          announce(F_PART + W.slotB * LN_);
          STAMP(true, 2, 14);
          bulk_wait_all();
          announce(F_PART + W.slotB * LN_ + 1);
          STAMP(true, 2, 15);
        }
        DUMP(true, 2, 14, 16);
        DUMP(true, 2, 0, 8);
      }
      return;
    }
  }
    {
      const int gw = cta * 3 + warp - 1;
      ROLE;
      if (total > 0) {
        mbar_wait_w(sb + B_EVQ, 0);
        const uint32_t c0 = clk();
        if (warp == 1 && (W.role & R_PUB)) {
          g_unsafe[W.q0] = lds32(sb + SM_UNSAFE);
#pragma unroll 1
          for (int k = 0; k < 4; k++) {
            __nanosleep(2000);
            if (lane == 0) bulk_s2g(pofs<uint4>(g_qp, W.q0 * 65536 + k * 16384), sb + SM_Q + k * 16384, 16384);
            bulk_commit();
          }
          bulk_wait_all();
          flag_release_w(F_QP + W.q0 * LN_);
        }
        while (__any_sync(0xffffffffu, clk() - c0 < GSTART)) __nanosleep(500);
        STAMP(lane == 0 && warp == 1, 2, 8);
#define ovf_cnt pofs<uint32_t>(g_flag, (F_OVF + (ep1 & 1) * LN_) * 4)
        if (gw == 0) g_flag[F_OVF + ((ep1 + 1) & 1) * LN_] = 0;
#pragma unroll 1
        for (int e0 = gw * 32; e0 < NE; e0 += NGW * 32 * 7) {
          int d[7], s[7], pos[7];
          const int* pd = pofs<const int>(P.dst, (e0 + lane) * 4);
          const int* ps = pofs<const int>(P.src, (e0 + lane) * 4);
#pragma unroll
          for (int k = 0; k < 7; k++) { const bool ok = e0 + k * NGW * 32 < NE; d[k] = ok ? (HINT & 1 ? __ldcs(pd + k * NGW * 32) : __ldg(pd + k * NGW * 32)) : -1; s[k] = ok ? (HINT & 1 ? __ldcs(ps + k * NGW * 32) : __ldg(ps + k * NGW * 32)) : 0; }
          uint32_t ov = 0;
#pragma unroll
          for (int k = 0; k < 7; k++) {
            pos[k] = 0;
            if (d[k] >= 0) asm volatile("atom.relaxed.gpu.global.add.u32 %0, [%1], 1;" : "=r"(pos[k]) : "l"(pofs<int>(g_cnt, d[k] << 2)) : "memory");
            s[k] = (uint32_t)(uintptr_t)g_u + s[k] * 512;
            if (d[k] >= 0 && pos[k] < CAP) asm volatile("st.volatile.global.u32 [%0], %1;" :: "l"(pofs<int>(g_bin, (d[k] * CAPS + pos[k]) << 2)), "r"(s[k]) : "memory");
            ov |= (pos[k] >= CAP) << k;
          }
          if (__any_sync(0xffffffffu, ov != 0)) {
            uint32_t at;
            asm volatile("atom.relaxed.gpu.global.add.u32 %0, [%1], %2;" : "=r"(at) : "l"(ovf_cnt), "r"(__popc(ov)) : "memory");
#pragma unroll
            for (int k = 0; k < 7; k++) if ((ov >> k) & 1) g_ovf[at++] = make_int2(d[k], s[k]);
          }
        }
        flag_wait_w(F_H, ep1 * NHSIG);
#pragma unroll 1
        for (int n0 = gw; n0 < NN; n0 += 4 * NGW) {
          uint4 xv[4]; float2 st[4];
#pragma unroll
          for (int k = 0; k < 4; k++) {
            const int n = n0 + k * NGW < NN ? n0 + k * NGW : n0;
            xv[k] = (HINT & 1 ? ldcs_v : ldcg_v)(pofs<const uint4>(P.x, n * 512 + lane * 16));
            st[k] = __ldcg(pofs<const float2>(g_stat, n * 8));
          }
#pragma unroll
          for (int k = 3; k >= 0; k--) {
            const int n = n0 + k * NGW;
            const float a = st[k].x * US, c = fmaf(st[k].y, US, UB + 8388608.0f);
#define FIX(w) __byte_perm(__float_as_uint(fmaf(bf_lo(w), a, c)), __float_as_uint(fmaf(bf_hi(w), a, c)), 0x5410)
            if (n < NN) {
              *pofs<uint4>(P.out, n * 512 + lane * 16) = xv[k];
              *pofs<uint4>(g_u, n * 512 + lane * 16) = make_uint4(FIX(xv[k].x), FIX(xv[k].y), FIX(xv[k].z), FIX(xv[k].w));
            }
          }
        }
        flag_release_w(F_BIN);
        STAMP(lane == 0 && warp == 1, 2, 9);
        flag_wait_w(F_BIN, ep1 * NGW);
        STAMP(lane == 0 && warp == 1, 2, 10);
        const int myn = gw + lane * NGW < NN ? gw + lane * NGW : gw;
        int cnts = __ldcg(g_cnt + myn);
        cnts = gw + lane * NGW < NN ? (cnts > CAP ? CAP + 1 : cnts) | ((int)__ldg((const unsigned short*)P.dinv + myn) << 16) : 0;
        __syncwarp();
        g_cnt[myn] = 0;
        const uint32_t uhi = (uintptr_t)g_u >> 32, lx = lane * 16;
        uint32_t obin = gw * CAPS * 4;
        uint32_t ent = __ldcg(pofs<const uint32_t>(g_bin, obin + lane * 4)), entn = __ldcg(pofs<const uint32_t>(g_bin, obin + NGW * CAPS * 4 + lane * 4));
        int cd = __shfl_sync(0xffffffffu, cnts, 0), cb = min(cd & 0xffff, CAP), e = 0;
        uint32_t sa[4] = {0, 0, 0, 0}, sh[4] = {0, 0, 0, 0};
        auto add = [&](uint32_t x, uint32_t y, uint32_t z, uint32_t w) {
          sa[0] += x; sa[1] += y; sa[2] += z; sa[3] += w;
          sh[0] += x >> 16; sh[1] += y >> 16; sh[2] += z >> 16; sh[3] += w >> 16;
        };
        int rnd = -1, rows = -1, cdo = 0;
#pragma unroll 1
        for (;;) {
          const bool hold = rows >= 0 && rnd == 8;
          const int m = hold ? 0 : cb - e;
          uint4 v[8];
          if (m >= 8) {
#pragma unroll
            for (int k = 0; k < 8; k++) v[k] = ldcg_v(addr64(__shfl_sync(0xffffffffu, ent, k) + lx, uhi));
          } else {
#pragma unroll
            for (int k = 0; k < 8; k++) {
              v[k] = make_uint4(0, 0, 0, 0);
              if (k < 7) ldcg_if(v[k], addr64(__shfl_sync(0xffffffffu, ent, k) + lx, uhi), k < m);
            }
          }
          if (rows >= 0) {
            const int n = gw + rnd * NGW;
            if (n < NN) {
              const float di = __uint_as_float(cdo & 0xffff0000u) * (1.0f / US), nl = -di * UB * (float)rows;
#define AGG(k) pack_bf16(fmaf((float)(sa[k] - (sh[k] << 16)), di, nl), fmaf((float)sh[k], di, nl))
              *pofs<uint4>(g_agg, ((n >> 3) * 4096 + (n & 7) * 144) ^ ((lx & 0x70) | ((lx & 0x180) << 3))) = make_uint4(AGG(0), AGG(1), AGG(2), AGG(3));
            }
#pragma unroll
            for (int k = 0; k < 4; k++) sa[k] = sh[k] = 0;
            rows = -1;
            if (rnd == 0 || rnd == 3 || rnd == 8 || rnd == NRND - 1) flag_release_w(F_AGG + ((rnd > 0) + (rnd > 3) + (rnd > 8)) * LN_);
            if (rnd == NRND - 1) break;
            if (hold) {
              if (fin && W.slotB >= 0) {
        #pragma unroll 1
                for (int k = 0; k < 2; k++) flag_wait_w(F_PART + (k ? W.slotB : W.slotA) * LN_, ep1);
        #pragma unroll 1
                for (int b = warp - 1; b < 8; b += 3) {
                  float2* ma = g_ml + W.slotA * 128 + b * 16 + g;
                  const float2* mb = g_ml + W.slotB * 128 + b * 16 + g;
                  const float2 a0 = __ldcg(ma), a1 = __ldcg(ma + 8), b0 = __ldcg(mb), b1 = __ldcg(mb + 8);
                  const float x0 = fmaxf(a0.x, b0.x), x1 = fmaxf(a1.x, b1.x);
                  const float fa0 = ex2(a0.x - x0), fa1 = ex2(a1.x - x1), fb0 = ex2(b0.x - x0), fb1 = ex2(b1.x - x1);
                  __syncwarp();
                  if (t == 0) { ma[0] = make_float2(x0, a0.y * fa0 + b0.y * fb0); ma[8] = make_float2(x1, a1.y * fa1 + b1.y * fb1); }
                  const uint32_t ofs = ((b >> 2) * 2048 + (b & 3) * 32 + lane) * 16;
        #pragma unroll 1
                  for (int u = 0; u < 16; u += 4) {
                    uint4* pa = pofs<uint4>(g_part, W.slotA * 65536 + ofs + u * 2048);
                    const uint4* pb = pofs<const uint4>(g_part, W.slotB * 65536 + ofs + u * 2048);
                    uint4 va[4], vb[4];
        #pragma unroll
                    for (int k = 0; k < 4; k++) { va[k] = ldcg_v(pa + k * 128); vb[k] = (HINT & 2 ? ldcs_v : ldcg_v)(pb + k * 128); }
        #define FOLD(w, fa, fb) pack_bf16(bf_lo(va[k].w) * fa + bf_lo(vb[k].w) * fb, bf_hi(va[k].w) * fa + bf_hi(vb[k].w) * fb)
        #pragma unroll
                    for (int k = 3; k >= 0; k--) pa[k * 128] = make_uint4(FOLD(x, fa0, fb0), FOLD(y, fa1, fb1), FOLD(z, fa0, fb0), FOLD(w, fa1, fb1));
                  }
                }
                bar_sync(3, 96);
                if (warp == 1) asm volatile("fence.acq_rel.gpu;" ::: "memory");
              }
              if (fin && warp == 1 && lane == 0) mbar_arrive(sb + B_BG);
              while (__any_sync(0xffffffffu, clk() - c0 < GPAUSE)) __nanosleep(500);
              continue;
            }
          }
#define SUM8(f) (v[7].f + v[6].f + v[5].f + v[4].f + v[3].f + v[2].f + v[1].f + v[0].f)
          add(SUM8(x), SUM8(y), SUM8(z), SUM8(w));
          e += 8;
          if (e < cb) {
            ent = __shfl_down_sync(0xffffffffu, ent, 8);
            if (e == 32) ent = __ldcg(pofs<const uint32_t>(g_bin, obin + 128 + lx / 4));
            continue;
          }
          rnd++; rows = cb; cdo = cd;
          if ((cd & 0xffff) > CAP) {
            const int no = __shfl_sync(0xffffffffu, (int)ld_relaxed(ovf_cnt), 0);
#pragma unroll 1
            for (int i0 = 0; i0 < no; i0 += 32) {
              int2 en = __ldcg(g_ovf + min(i0 + lane, no - 1));
              uint32_t mk = __ballot_sync(0xffffffffu, en.x == gw + rnd * NGW && i0 + lane < no);
              rows += __popc(mk);
#pragma unroll 1
              while (mk) {
                const int bit = __ffs(mk) - 1; mk &= mk - 1;
                const uint4 r = ldcg_v(addr64((uint32_t)__shfl_sync(0xffffffffu, en.y, bit) + lx, uhi));
                add(r.x, r.y, r.z, r.w);
              }
            }
          }
          obin += NGW * CAPS * 4;
          ent = entn; entn = __ldcg(pofs<const uint32_t>(g_bin, obin + NGW * CAPS * 4 + lx / 4));
          cd = __shfl_sync(0xffffffffu, cnts, rnd + 1); cb = min(cd & 0xffff, CAP); e = 0;
        }
      }
      STAMP(lane == 0 && warp == 1, 2, 11);
      if ((HINT & 4) && warp == 2 && fin && lane == 0) {
        prefetch_l2(pofs<uint8_t>(P.out, W.q0 * 65536), tail ? 8192 : 65536);
        if (W.slotB >= 0) prefetch_l2(pofs<uint8_t>(g_part, W.slotA * 65536), 65536);
        prefetch_l2(pofs<uint8_t>(g_Wvo, (cta & 63) * 4096), 4096);
      }
      DUMP(warp == 1 && lane == 0, 2, 8, 14);
    }
}

}

extern "C" void kernel_launch(void* const* d_in, const int* in_sizes, int n_in, void* d_out, int out_size) {
  Params P;
  P.x = (const __nv_bfloat16*)d_in[0];
  P.src = (const int*)d_in[1];
  P.dst = (const int*)d_in[2];
  P.dinv = (const __nv_bfloat16*)d_in[3];
  P.wmsg = (const __nv_bfloat16*)d_in[4];
  P.wq = (const __nv_bfloat16*)d_in[5];
  P.wk = (const __nv_bfloat16*)d_in[6];
  P.wv = (const __nv_bfloat16*)d_in[7];
  P.wout = (const __nv_bfloat16*)d_in[8];
  P.out = (__nv_bfloat16*)d_out;
  P.zero = 0;
  for (int c = 0; c < NCTA; c++) P.w[c] = make_work(logical_cta(c));
  static void* scr = nullptr;
  if (!scr) {
    cudaFuncSetAttribute(gps_kernel, cudaFuncAttributeMaxDynamicSharedMemorySize, SMEM_BYTES);
    cudaGetSymbolAddress(&scr, g_scr);
  }
  P.s = (Scratch*)((((uintptr_t)scr + SCR_ALIGN - 1) & ~(uintptr_t)(SCR_ALIGN - 1)) + SCR_OFS);
  P.u = (uint4*)(((uintptr_t)P.s->u + 511) & ~(uintptr_t)511);
  if (((uintptr_t)P.u >> 32) != (((uintptr_t)(P.u + NN * 32) - 1) >> 32)) P.u += NN * 32;
  gps_kernel<<<NCTA, 384, SMEM_BYTES>>>(P);
}
```

```cpp
#include <cuda_runtime.h>
#include <cuda_bf16.h>
#include <stdint.h>
#include <stddef.h>
#include <type_traits>
#define FB 5
#define MB 5
#define GSTART 40000
#define XD 2
#define NTAIL 5
#define PACE 64
#define GPAUSE 112000
#define XDELAY 200
#define CREG 224
#define BACKOFF 1000

namespace {

constexpr int NN = 10000;
constexpr int NE = 160000;
constexpr int NQT = 79;
constexpr int NCTA = 132;
constexpr int CAP = 64;
constexpr int CAPS = 64;
constexpr int NHSIG = 105;
constexpr uint32_t WCH_B = 32768;
constexpr int NGW = (NCTA - 1) * 3;
constexpr float TAU = 16.0f;
constexpr float SAFE_N2 = 36.0f, SAFE_C = 0.6f;
#define KOFF 3
#define PSH -8.0f
#define KROT 15
constexpr float US = 256.0f, UB = 4095.0f;
constexpr float KS = 0.25f, KC = KOFF * KS;
constexpr uint32_t KS2 = 0x3e803e80u, KC2 = KOFF == 2 ? 0x3f003f00u : (KOFF == 1 ? 0x3e803e80u : 0x3f403f40u);

constexpr int NAGG = 4;
constexpr int NRND = (NN + NGW - 1) / NGW;
constexpr int NSLOT = 105;
constexpr int F_EPOCH = 0, F_H = 1, F_M = 4  , F_H1 = 8  , LN_ = 32;
constexpr int F_BIN = LN_, F_W = 2 * LN_, F_OVF = 3 * LN_  , F_QP = 5 * LN_, F_AGG = F_QP + NQT * LN_,
              F_PART = F_AGG + NAGG * LN_, F_END = F_PART + NSLOT * LN_;

struct Scratch {
  uint32_t flag[F_END];
  alignas(4096) uint4 M[8192];
  uint4 Wvo[8192], Wmo[8192];
  float2 ml[NSLOT * 128];
  uint32_t unsafe[96];
  int cnt[NN + 32];
  float2 stat[NQT * 128];
  alignas(4096) uint4 h[NQT * 4096];
  uint4 u[2 * NN * 32 + 32];
  uint4 qp[NQT * 4096];
  uint4 agg[NQT * 4096];
  uint4 part[NSLOT * 4096];
  int bin[(NRND + 2) * NGW * CAPS];
  int2 ovf[NE];
};
static_assert(offsetof(Scratch, h) % 128 == 0, "alignment");
#define SCR_ALIGN (2u << 20)
#define SCR_OFS 0
__device__ uint4 g_scr[(sizeof(Scratch) + SCR_ALIGN + SCR_OFS) / 16];
struct alignas(16) Work { short k0, k1; signed char q0, hp, nb0, na0, nb1, na1, slotA, slotB, loc0, nloc, own, role; };
constexpr int R_FIN = 1, R_PUB = 2, R_TAIL = 4, R_SIG = 8  ;
struct Params {
  const __nv_bfloat16 *x, *wq, *wk;
  Scratch* s;
  uint4* u;
  __nv_bfloat16* out;
  const __nv_bfloat16 *wout, *wmsg, *wv, *dinv;
  const int *src, *dst;
  long long zero;
  Work w[NCTA];
};
constexpr int first_cnt(int k) { return 2 * ((k + 6) / 8 - k / 8 + 1); }
constexpr int NH1_0 = 2, NH1_1 = first_cnt(48 * 8 - MB), NH1_2 = first_cnt(48 * 8 - MB + 16 * 8 - (15 - MB) / 2);
constexpr int NSERV = NQT - 52;
inline Work make_work(int c) {
  Work w;
  const int gi = c / 5, r = c % 5, q = gi * 3;
  const bool helper = r & 1, mid = r == 2;
  w.q0 = helper ? q + 1 : q + (r >> 1);
  const int hb1 = (15 - MB) / 2, hb3 = 15 - MB - hb1;
  w.nb0 = helper ? (r == 1 ? hb1 : hb3) : (mid ? MB : FB);
  w.na0 = (helper ? 16 : 48) - w.nb0;
  w.k0 = helper ? (48 * 8 - MB) + (r >> 1) * (16 * 8 - hb1) : 0;
  w.k1 = 48 * 8 - FB;
  w.nb1 = helper ? (FB < 7 ? 7 : 15) - FB : 0;
  w.na1 = helper ? (FB < 7 ? 31 : 32) - w.nb1 : 0;
  w.slotA = 4 * gi + (helper ? r - 1 : (mid ? 0 : (r >> 1) + 1));
  w.slotB = helper ? 4 * gi + r : (mid ? 4 * gi + 2 : -1);
  w.loc0 = NSERV + gi * 2 + (r >> 1);
  w.nloc = helper;
  w.own = helper ? (r + 1) >> 1 : (mid ? 0 : 3);
  w.role = helper ? 0 : (mid ? R_FIN : R_FIN | R_PUB);
  const int k1st[3] = {0, 48 * 8 - MB, 48 * 8 - MB + 16 * 8 - hb1};
  int pos[NQT], sig[NQT];
  for (int i = 0; i < NQT; i++) { pos[i] = i; sig[i] = 0; }
  for (int i = 0; i < 3; i++)
    for (int p = k1st[i] / 8; p <= (k1st[i] + 6) / 8; p++) {
      int m = 1, at = 0;
      while (sig[m]) m += 3;
      while (pos[at] != p) at++;
      pos[at] = pos[m]; pos[m] = p; sig[m] = 1 + i;
    }
  w.hp = c < 131 ? pos[w.q0] : 0;
  if (helper && c < 130) w.role |= sig[w.q0] * R_SIG;
  if (c == 130) { w.nb0 = 15; w.na0 = 65; w.slotA = NSLOT - 1; w.own = 1; w.role = R_FIN | R_TAIL; w.loc0 = NSERV - NTAIL; w.nloc = NTAIL; }
  if (c == 131) { w.nb0 = w.na0 = w.nb1 = w.na1 = 0; w.loc0 = 0; w.nloc = NSERV - NTAIL; w.own = 0; }
  return w;
}
#define g_flag P.s->flag
#define g_M P.s->M
#define g_Wvo P.s->Wvo
#define g_Wmo P.s->Wmo
#define g_ml P.s->ml
#define g_unsafe P.s->unsafe
#define g_cnt P.s->cnt
#define g_h P.s->h
#define g_u P.u
#define g_stat P.s->stat
#define g_qp P.s->qp
#define g_agg P.s->agg
#define g_part P.s->part
#define g_bin P.s->bin
#define g_ovf P.s->ovf

__device__ __forceinline__ uint32_t smem_u32(const void* p) { return (uint32_t)__cvta_generic_to_shared(p); }
__device__ __forceinline__ void mbar_init(uint32_t bar, uint32_t cnt) { asm volatile("mbarrier.init.shared::cta.b64 [%0], %1;" :: "r"(bar), "r"(cnt) : "memory"); }
__device__ __forceinline__ void mbar_arrive(uint32_t bar) { asm volatile("mbarrier.arrive.shared::cta.b64 _, [%0];" :: "r"(bar) : "memory"); }
__device__ __forceinline__ void mbar_expect_tx(uint32_t bar, uint32_t bytes) { asm volatile("mbarrier.arrive.expect_tx.shared::cta.b64 _, [%0], %1;" :: "r"(bar), "r"(bytes) : "memory"); }
__device__ __forceinline__ bool mbar_try_wait(uint32_t bar, uint32_t parity) {
  uint32_t ok;
  asm volatile("{\n.reg .pred p;\nmbarrier.try_wait.parity.shared::cta.b64 p, [%1], %2;\nselp.b32 %0, 1, 0, p;\n}\n" : "=r"(ok) : "r"(bar), "r"(parity) : "memory");
  return ok;
}
__device__ __forceinline__ bool mbar_try_wait_nb(uint32_t bar, uint32_t parity) {
  uint32_t ok;
  asm volatile("{\n.reg .pred p;\nmbarrier.test_wait.parity.shared::cta.b64 p, [%1], %2;\nselp.b32 %0, 1, 0, p;\n}\n" : "=r"(ok) : "r"(bar), "r"(parity) : "memory");
  return ok;
}
__device__ __forceinline__ void mbar_wait(uint32_t bar, uint32_t parity) {
#pragma unroll 1
  for (uint32_t it = 0; it < (1u << 25); it++) if (mbar_try_wait(bar, parity)) break;
}
__device__ __forceinline__ void bulk_s2g(void* dst, uint32_t src, uint32_t bytes) {
  asm volatile("cp.async.bulk.global.shared::cta.bulk_group [%0], [%1], %2;" :: "l"(dst), "r"(src), "r"(bytes) : "memory");
}
__device__ __forceinline__ void bulk_commit() { asm volatile("cp.async.bulk.commit_group;" ::: "memory"); }
__device__ __forceinline__ void bulk_wait_read() { asm volatile("cp.async.bulk.wait_group.read 0;" ::: "memory"); }
__device__ __forceinline__ void bulk_wait_all() { asm volatile("cp.async.bulk.wait_group 0;" ::: "memory"); }
__device__ __forceinline__ bool bar_red_or(int id, int cnt, bool c) {
  uint32_t r;
  asm volatile("{\n.reg .pred p, q;\nsetp.ne.b32 q, %3, 0;\nbar.red.or.pred p, %1, %2, q;\nselp.b32 %0, 1, 0, p;\n}\n"
               : "=r"(r) : "r"(id), "r"(cnt), "r"((uint32_t)c) : "memory");
  return r != 0;
}
template <class T> __device__ __forceinline__ T* pofs(const void* base, uint32_t off) {
  asm volatile("" : "+r"(off));
  return (T*)((uint8_t*)base + off);
}
__device__ __forceinline__ const void* addr64(uint32_t lo, uint32_t hi) { uint64_t a; asm("mov.b64 %0, {%1, %2};" : "=l"(a) : "r"(lo), "r"(hi)); return (const void*)a; }
__device__ __forceinline__ uint4 ldcg_v(const void* a) {
  uint4 v;
  asm volatile("ld.volatile.global.v4.u32 {%0,%1,%2,%3}, [%4];" : "=r"(v.x), "=r"(v.y), "=r"(v.z), "=r"(v.w) : "l"(a) : "memory");
  return v;
}
__device__ __forceinline__ uint4 ldcs_v(const void* a) {
  uint4 v;
  asm volatile("ld.global.cs.v4.u32 {%0,%1,%2,%3}, [%4];" : "=r"(v.x), "=r"(v.y), "=r"(v.z), "=r"(v.w) : "l"(a) : "memory");
  return v;
}
__device__ __forceinline__ void prefetch_l2(const void* a, uint32_t bytes) { asm volatile("cp.async.bulk.prefetch.L2.global [%0], %1;" :: "l"(a), "r"(bytes) : "memory"); }
__device__ __forceinline__ void ldcg_if(uint4& v, const void* a, bool c) {
  asm volatile("{\n.reg .pred p;\nsetp.ne.b32 p, %5, 0;\n@p ld.volatile.global.v4.u32 {%0,%1,%2,%3}, [%4];\n}\n"
               : "+r"(v.x), "+r"(v.y), "+r"(v.z), "+r"(v.w) : "l"(a), "r"((uint32_t)c) : "memory");
}
__device__ __forceinline__ void cp_async16(uint32_t dst, const void* src) {
  asm volatile("cp.async.cg.shared.global [%0], [%1], 16;" :: "r"(dst), "l"(src) : "memory");
}
__device__ __forceinline__ void red_bf16x8(void* a, uint4 v) {
  asm volatile("red.global.add.noftz.v4.bf16x2 [%0], {%1,%2,%3,%4};" :: "l"(a), "r"(v.x), "r"(v.y), "r"(v.z), "r"(v.w) : "memory");
}
__device__ __forceinline__ uint32_t clk() { uint32_t c; asm volatile("mov.u32 %0, %%clock;" : "=r"(c) :: "memory"); return c; }
__device__ __forceinline__ void stsm4(uint32_t a, uint32_t r0, uint32_t r1, uint32_t r2, uint32_t r3) {
  asm volatile("stmatrix.sync.aligned.m8n8.x4.shared.b16 [%0], {%1,%2,%3,%4};" :: "r"(a), "r"(r0), "r"(r1), "r"(r2), "r"(r3) : "memory");
}
__device__ __forceinline__ void ldsm4(uint32_t a, uint32_t& r0, uint32_t& r1, uint32_t& r2, uint32_t& r3) {
  asm volatile("ldmatrix.sync.aligned.m8n8.x4.shared.b16 {%0,%1,%2,%3}, [%4];" : "=r"(r0), "=r"(r1), "=r"(r2), "=r"(r3) : "r"(a) : "memory");
}
__device__ __forceinline__ void red_relaxed(uint32_t* p) { asm volatile("red.relaxed.gpu.global.add.u32 [%0], 1;" :: "l"(p) : "memory"); }
__device__ __forceinline__ uint32_t lds32(uint32_t a) { uint32_t v; asm volatile("ld.shared.u32 %0, [%1];" : "=r"(v) : "r"(a) : "memory"); return v; }
__device__ __forceinline__ void cp_commit() { asm volatile("cp.async.commit_group;" ::: "memory"); }
__device__ __forceinline__ uint32_t hmul2(uint32_t a, uint32_t b) { uint32_t d; asm("mul.rn.bf16x2 %0, %1, %2;" : "=r"(d) : "r"(a), "r"(b)); return d; }
__device__ __forceinline__ uint32_t hfma2(uint32_t a, uint32_t b, uint32_t c) { uint32_t d; asm("fma.rn.bf16x2 %0, %1, %2, %3;" : "=r"(d) : "r"(a), "r"(b), "r"(c)); return d; }
__device__ __forceinline__ uint32_t pow2_bf2(int n) { return (uint32_t)max(n + 127, 0) * 0x00800080u; }
__device__ __forceinline__ int fexp(float x) { return (int)(__float_as_uint(x) >> 23) - 127; }
__device__ __forceinline__ void bulk_g2s(uint32_t dst, const void* src, uint32_t bytes, uint32_t bar) {
  asm volatile("cp.async.bulk.shared::cta.global.mbarrier::complete_tx::bytes [%0], [%1], %2, [%3];"
    :: "r"(dst), "l"(src), "r"(bytes), "r"(bar) : "memory");
}
__device__ __forceinline__ void bulk_g2s_last(uint32_t dst, const void* src, uint32_t bytes, uint32_t bar) {
  asm volatile("{\n.reg .b64 p;\ncreatepolicy.fractional.L2::evict_first.b64 p;\n"
    "cp.async.bulk.shared::cta.global.mbarrier::complete_tx::bytes.L2::cache_hint [%0], [%1], %2, [%3], p;\n}\n"
    :: "r"(dst), "l"(src), "r"(bytes), "r"(bar) : "memory");
}
__device__ __forceinline__ void wg_fence() { asm volatile("wgmma.fence.sync.aligned;" ::: "memory"); }
__device__ __forceinline__ void wg_commit() { asm volatile("wgmma.commit_group.sync.aligned;" ::: "memory"); }
template<int N> __device__ __forceinline__ void wg_wait() { asm volatile("wgmma.wait_group.sync.aligned %0;" :: "n"(N) : "memory"); }
__device__ __forceinline__ void bar_sync(int id, int cnt) { asm volatile("bar.sync %0, %1;" :: "r"(id), "r"(cnt) : "memory"); }
__device__ __forceinline__ void fence_async_smem() { asm volatile("fence.proxy.async.shared::cta;" ::: "memory"); }
__device__ __forceinline__ void fence_async_gmem() { asm volatile("fence.proxy.async.global;" ::: "memory"); }
__device__ __forceinline__ void bar_arrive(int id, int cnt) { asm volatile("bar.arrive %0, %1;" :: "r"(id), "r"(cnt) : "memory"); }
__device__ __forceinline__ void red_release(uint32_t* p) { asm volatile("red.release.gpu.global.add.u32 [%0], 1;" :: "l"(p) : "memory"); }
__device__ __forceinline__ void red_release_w(uint32_t* p) {
  __syncwarp();
  asm volatile("{\n.reg .pred q;\n.reg .b32 l;\nmov.u32 l, %%laneid;\nsetp.eq.u32 q, l, 0;\n@q fence.release.gpu;\n@q red.relaxed.gpu.global.add.u32 [%0], 1;\n}\n" :: "l"(p) : "memory");
}
__device__ __forceinline__ void mbar_wait_w(uint32_t bar, uint32_t parity) {
#pragma unroll 1
  for (uint32_t it = 0; it < (1u << 25); it++) if (__all_sync(0xffffffffu, mbar_try_wait(bar, parity))) break;
}
#define flag_release_w(f) red_release_w(g_flag + (f))
#define flag_wait_w(f, target) poll_acquire_w(g_flag + (f), target)
#define flag_release(f) red_release(g_flag + (f))
__device__ __forceinline__ uint32_t ld_relaxed(const uint32_t* p) {
  uint32_t v; asm volatile("ld.relaxed.gpu.global.u32 %0, [%1];" : "=r"(v) : "l"(p) : "memory"); return v;
}
#define flag_wait(f, target) poll_acquire(g_flag + (f), target)
__device__ __forceinline__ void poll_acquire(const uint32_t* p, uint32_t target) {
#pragma unroll 1
  for (uint32_t it = 0; it < (1u << 23); it++) if ((int)(ld_relaxed(p) - target) >= 0) break;
  asm volatile("fence.acquire.gpu;" ::: "memory");
}
__device__ __forceinline__ void poll_acquire_w(const uint32_t* p, uint32_t target) {
#pragma unroll 1
  for (uint32_t it = 0; it < (1u << 23); it++) {
    if (__all_sync(0xffffffffu, (int)(ld_relaxed(p) - target) >= 0)) break;
    if (BACKOFF) __nanosleep(BACKOFF);
  }
  asm volatile("fence.acquire.gpu;" ::: "memory");
}
template<int N> __device__ __forceinline__ void reg_fence(float (&d)[N]) {
#pragma unroll
  for (int i = 0; i < N; i++) asm volatile("" : "+f"(d[i]) :: "memory");
}
template<int N> __device__ __forceinline__ void reg_fence(uint32_t (&d)[N]) {
#pragma unroll
  for (int i = 0; i < N; i++) asm volatile("" : "+r"(d[i]) :: "memory");
}
__device__ __forceinline__ float ex2(float x) { float y; asm("ex2.approx.ftz.f32 %0, %1;" : "=f"(y) : "f"(x)); return y; }
__device__ __forceinline__ uint32_t pack_bf16(float lo, float hi) { uint32_t r; asm("cvt.rn.bf16x2.f32 %0, %1, %2;" : "=r"(r) : "f"(hi), "f"(lo)); return r; }
__device__ __forceinline__ float bf_lo(uint32_t w) { return __uint_as_float(w << 16); }
__device__ __forceinline__ float bf_hi(uint32_t w) { return __uint_as_float(w & 0xffff0000u); }
__device__ __forceinline__ uint64_t desc_k(uint32_t addr, uint32_t add) { return (uint64_t)((((addr & 0x3FFFF) >> 4) | (1u << 16)) + add) | (0x40000100ull << 32); }
__device__ __forceinline__ uint64_t desc_mn(uint32_t addr, uint32_t add) { return (uint64_t)((((addr & 0x3FFFF) >> 4) | ((1024u >> 4) << 16)) + add) | (0x40000100ull << 32); }
__device__ __forceinline__ void sts128(uint32_t a, uint4 v) { asm volatile("st.shared.v4.u32 [%0], {%1,%2,%3,%4};" :: "r"(a), "r"(v.x), "r"(v.y), "r"(v.z), "r"(v.w) : "memory"); }
__device__ __forceinline__ uint4 lds128(uint32_t a) { uint4 v; asm volatile("ld.shared.v4.u32 {%0,%1,%2,%3}, [%4];" : "=r"(v.x), "=r"(v.y), "=r"(v.z), "=r"(v.w) : "r"(a) : "memory"); return v; }
__device__ __forceinline__ void mma16816(float (&c)[4], uint32_t a0, uint32_t a1, uint32_t a2, uint32_t a3, uint32_t b0, uint32_t b1) {
  asm volatile("mma.sync.aligned.m16n8k16.row.col.f32.bf16.bf16.f32 {%0,%1,%2,%3}, {%4,%5,%6,%7}, {%8,%9}, {%0,%1,%2,%3};"
    : "+f"(c[0]), "+f"(c[1]), "+f"(c[2]), "+f"(c[3]) : "r"(a0), "r"(a1), "r"(a2), "r"(a3), "r"(b0), "r"(b1));
}
__device__ __forceinline__ uint32_t sw_byte(int r, int c) {
  return (uint32_t)((r >> 3) * 4096 + (c >> 6) * 1024 + (r & 7) * 128 + ((((c >> 3) & 7) ^ (r & 7)) << 4) + (c & 7) * 2);
}
__device__ __forceinline__ int cta_id() { int c; asm volatile("mov.u32 %0, %%ctaid.x;" : "=r"(c)); return c; }
__device__ __forceinline__ bool tid_is(int v) { int t; asm volatile("mov.u32 %0, %%tid.x;" : "=r"(t)); return t == v; }
#define STAMP(cond, who, i)
#define CSTAMP(cond, who, i)
#define DUMP(cond, who, i0, i1)
#define XSTAMP(cond, i)
#define SSTAMP(i)

template <int OA, int OB> __device__ __forceinline__ void wgmma_ss_n256_tb(float (&d)[128], uint64_t da, uint64_t db, int scale_d) {
  asm volatile("{\n.reg .pred p;\n.reg .b64 a, b;\nsetp.ne.b32 p, %130, 0;\nadd.s64 a, %128, %131;\nadd.s64 b, %129, %132;\n"
    "wgmma.mma_async.sync.aligned.m64n256k16.f32.bf16.bf16 "
    "{%0, %1, %2, %3, %4, %5, %6, %7, %8, %9, %10, %11, %12, %13, %14, %15, %16, %17, %18, %19, %20, %21, %22, %23, %24, %25, %26, %27, %28, %29, %30, %31, %32, %33, %34, %35, %36, %37, %38, %39, %40, %41, %42, %43, %44, %45, %46, %47, %48, %49, %50, %51, %52, %53, %54, %55, %56, %57, %58, %59, %60, %61, %62, %63, %64, %65, %66, %67, %68, %69, %70, %71, %72, %73, %74, %75, %76, %77, %78, %79, %80, %81, %82, %83, %84, %85, %86, %87, %88, %89, %90, %91, %92, %93, %94, %95, %96, %97, %98, %99, %100, %101, %102, %103, %104, %105, %106, %107, %108, %109, %110, %111, %112, %113, %114, %115, %116, %117, %118, %119, %120, %121, %122, %123, %124, %125, %126, %127}, "
    "a, b, p, 1, 1, 0, 1;\n}\n"
    : "+f"(d[0]), "+f"(d[1]), "+f"(d[2]), "+f"(d[3]), "+f"(d[4]), "+f"(d[5]), "+f"(d[6]), "+f"(d[7]), "+f"(d[8]), "+f"(d[9]), "+f"(d[10]), "+f"(d[11]), "+f"(d[12]), "+f"(d[13]), "+f"(d[14]), "+f"(d[15]), "+f"(d[16]), "+f"(d[17]), "+f"(d[18]), "+f"(d[19]), "+f"(d[20]), "+f"(d[21]), "+f"(d[22]), "+f"(d[23]), "+f"(d[24]), "+f"(d[25]), "+f"(d[26]), "+f"(d[27]), "+f"(d[28]), "+f"(d[29]), "+f"(d[30]), "+f"(d[31]), "+f"(d[32]), "+f"(d[33]), "+f"(d[34]), "+f"(d[35]), "+f"(d[36]), "+f"(d[37]), "+f"(d[38]), "+f"(d[39]), "+f"(d[40]), "+f"(d[41]), "+f"(d[42]), "+f"(d[43]), "+f"(d[44]), "+f"(d[45]), "+f"(d[46]), "+f"(d[47]), "+f"(d[48]), "+f"(d[49]), "+f"(d[50]), "+f"(d[51]), "+f"(d[52]), "+f"(d[53]), "+f"(d[54]), "+f"(d[55]), "+f"(d[56]), "+f"(d[57]), "+f"(d[58]), "+f"(d[59]), "+f"(d[60]), "+f"(d[61]), "+f"(d[62]), "+f"(d[63]), "+f"(d[64]), "+f"(d[65]), "+f"(d[66]), "+f"(d[67]), "+f"(d[68]), "+f"(d[69]), "+f"(d[70]), "+f"(d[71]), "+f"(d[72]), "+f"(d[73]), "+f"(d[74]), "+f"(d[75]), "+f"(d[76]), "+f"(d[77]), "+f"(d[78]), "+f"(d[79]), "+f"(d[80]), "+f"(d[81]), "+f"(d[82]), "+f"(d[83]), "+f"(d[84]), "+f"(d[85]), "+f"(d[86]), "+f"(d[87]), "+f"(d[88]), "+f"(d[89]), "+f"(d[90]), "+f"(d[91]), "+f"(d[92]), "+f"(d[93]), "+f"(d[94]), "+f"(d[95]), "+f"(d[96]), "+f"(d[97]), "+f"(d[98]), "+f"(d[99]), "+f"(d[100]), "+f"(d[101]), "+f"(d[102]), "+f"(d[103]), "+f"(d[104]), "+f"(d[105]), "+f"(d[106]), "+f"(d[107]), "+f"(d[108]), "+f"(d[109]), "+f"(d[110]), "+f"(d[111]), "+f"(d[112]), "+f"(d[113]), "+f"(d[114]), "+f"(d[115]), "+f"(d[116]), "+f"(d[117]), "+f"(d[118]), "+f"(d[119]), "+f"(d[120]), "+f"(d[121]), "+f"(d[122]), "+f"(d[123]), "+f"(d[124]), "+f"(d[125]), "+f"(d[126]), "+f"(d[127])
    : "l"(da), "l"(db), "r"(scale_d), "n"(OA), "n"(OB));
}
template <int OA, int OB> __device__ __forceinline__ void wgmma_qk(float (&d)[64], uint64_t da, uint64_t db, int scale_d) {
  asm volatile("{\n.reg .pred p;\n.reg .b64 a, b;\nsetp.ne.b32 p, %66, 0;\nadd.s64 a, %64, %67;\nadd.s64 b, %65, %68;\n"
    "wgmma.mma_async.sync.aligned.m64n128k16.f32.bf16.bf16 "
    "{%0, %1, %2, %3, %4, %5, %6, %7, %8, %9, %10, %11, %12, %13, %14, %15, %16, %17, %18, %19, %20, %21, %22, %23, %24, %25, %26, %27, %28, %29, %30, %31, %32, %33, %34, %35, %36, %37, %38, %39, %40, %41, %42, %43, %44, %45, %46, %47, %48, %49, %50, %51, %52, %53, %54, %55, %56, %57, %58, %59, %60, %61, %62, %63}, "
    "a, b, p, 1, 1, 0, 0;\n}\n"
    : "+f"(d[0]), "+f"(d[1]), "+f"(d[2]), "+f"(d[3]), "+f"(d[4]), "+f"(d[5]), "+f"(d[6]), "+f"(d[7]), "+f"(d[8]), "+f"(d[9]), "+f"(d[10]), "+f"(d[11]), "+f"(d[12]), "+f"(d[13]), "+f"(d[14]), "+f"(d[15]), "+f"(d[16]), "+f"(d[17]), "+f"(d[18]), "+f"(d[19]), "+f"(d[20]), "+f"(d[21]), "+f"(d[22]), "+f"(d[23]), "+f"(d[24]), "+f"(d[25]), "+f"(d[26]), "+f"(d[27]), "+f"(d[28]), "+f"(d[29]), "+f"(d[30]), "+f"(d[31]), "+f"(d[32]), "+f"(d[33]), "+f"(d[34]), "+f"(d[35]), "+f"(d[36]), "+f"(d[37]), "+f"(d[38]), "+f"(d[39]), "+f"(d[40]), "+f"(d[41]), "+f"(d[42]), "+f"(d[43]), "+f"(d[44]), "+f"(d[45]), "+f"(d[46]), "+f"(d[47]), "+f"(d[48]), "+f"(d[49]), "+f"(d[50]), "+f"(d[51]), "+f"(d[52]), "+f"(d[53]), "+f"(d[54]), "+f"(d[55]), "+f"(d[56]), "+f"(d[57]), "+f"(d[58]), "+f"(d[59]), "+f"(d[60]), "+f"(d[61]), "+f"(d[62]), "+f"(d[63])
    : "l"(da), "l"(db), "r"(scale_d), "n"(OA), "n"(OB));
}
template <int OA, int OB> __device__ __forceinline__ void wgmma_qk(float (&d)[56], uint64_t da, uint64_t db, int scale_d) {
  asm volatile("{\n.reg .pred p;\n.reg .b64 a, b;\nsetp.ne.b32 p, %58, 0;\nadd.s64 a, %56, %59;\nadd.s64 b, %57, %60;\n"
    "wgmma.mma_async.sync.aligned.m64n112k16.f32.bf16.bf16 "
    "{%0, %1, %2, %3, %4, %5, %6, %7, %8, %9, %10, %11, %12, %13, %14, %15, %16, %17, %18, %19, %20, %21, %22, %23, %24, %25, %26, %27, %28, %29, %30, %31, %32, %33, %34, %35, %36, %37, %38, %39, %40, %41, %42, %43, %44, %45, %46, %47, %48, %49, %50, %51, %52, %53, %54, %55}, "
    "a, b, p, 1, 1, 0, 0;\n}\n"
    : "+f"(d[0]), "+f"(d[1]), "+f"(d[2]), "+f"(d[3]), "+f"(d[4]), "+f"(d[5]), "+f"(d[6]), "+f"(d[7]), "+f"(d[8]), "+f"(d[9]), "+f"(d[10]), "+f"(d[11]), "+f"(d[12]), "+f"(d[13]), "+f"(d[14]), "+f"(d[15]), "+f"(d[16]), "+f"(d[17]), "+f"(d[18]), "+f"(d[19]), "+f"(d[20]), "+f"(d[21]), "+f"(d[22]), "+f"(d[23]), "+f"(d[24]), "+f"(d[25]), "+f"(d[26]), "+f"(d[27]), "+f"(d[28]), "+f"(d[29]), "+f"(d[30]), "+f"(d[31]), "+f"(d[32]), "+f"(d[33]), "+f"(d[34]), "+f"(d[35]), "+f"(d[36]), "+f"(d[37]), "+f"(d[38]), "+f"(d[39]), "+f"(d[40]), "+f"(d[41]), "+f"(d[42]), "+f"(d[43]), "+f"(d[44]), "+f"(d[45]), "+f"(d[46]), "+f"(d[47]), "+f"(d[48]), "+f"(d[49]), "+f"(d[50]), "+f"(d[51]), "+f"(d[52]), "+f"(d[53]), "+f"(d[54]), "+f"(d[55])
    : "l"(da), "l"(db), "r"(scale_d), "n"(OA), "n"(OB));
}
template <int OB> __device__ __forceinline__ void wgmma_rs_n256_tb(float (&d)[128], uint32_t a0, uint32_t a1, uint32_t a2, uint32_t a3, uint64_t db, int scale_d) {
  asm volatile("{\n.reg .pred p;\n.reg .b64 b;\nsetp.ne.b32 p, %133, 0;\nadd.s64 b, %132, %134;\n"
    "wgmma.mma_async.sync.aligned.m64n256k16.f32.bf16.bf16 "
    "{%0, %1, %2, %3, %4, %5, %6, %7, %8, %9, %10, %11, %12, %13, %14, %15, %16, %17, %18, %19, %20, %21, %22, %23, %24, %25, %26, %27, %28, %29, %30, %31, %32, %33, %34, %35, %36, %37, %38, %39, %40, %41, %42, %43, %44, %45, %46, %47, %48, %49, %50, %51, %52, %53, %54, %55, %56, %57, %58, %59, %60, %61, %62, %63, %64, %65, %66, %67, %68, %69, %70, %71, %72, %73, %74, %75, %76, %77, %78, %79, %80, %81, %82, %83, %84, %85, %86, %87, %88, %89, %90, %91, %92, %93, %94, %95, %96, %97, %98, %99, %100, %101, %102, %103, %104, %105, %106, %107, %108, %109, %110, %111, %112, %113, %114, %115, %116, %117, %118, %119, %120, %121, %122, %123, %124, %125, %126, %127}, "
    "{%128, %129, %130, %131}, b, p, 1, 1, 1;\n}\n"
    : "+f"(d[0]), "+f"(d[1]), "+f"(d[2]), "+f"(d[3]), "+f"(d[4]), "+f"(d[5]), "+f"(d[6]), "+f"(d[7]), "+f"(d[8]), "+f"(d[9]), "+f"(d[10]), "+f"(d[11]), "+f"(d[12]), "+f"(d[13]), "+f"(d[14]), "+f"(d[15]), "+f"(d[16]), "+f"(d[17]), "+f"(d[18]), "+f"(d[19]), "+f"(d[20]), "+f"(d[21]), "+f"(d[22]), "+f"(d[23]), "+f"(d[24]), "+f"(d[25]), "+f"(d[26]), "+f"(d[27]), "+f"(d[28]), "+f"(d[29]), "+f"(d[30]), "+f"(d[31]), "+f"(d[32]), "+f"(d[33]), "+f"(d[34]), "+f"(d[35]), "+f"(d[36]), "+f"(d[37]), "+f"(d[38]), "+f"(d[39]), "+f"(d[40]), "+f"(d[41]), "+f"(d[42]), "+f"(d[43]), "+f"(d[44]), "+f"(d[45]), "+f"(d[46]), "+f"(d[47]), "+f"(d[48]), "+f"(d[49]), "+f"(d[50]), "+f"(d[51]), "+f"(d[52]), "+f"(d[53]), "+f"(d[54]), "+f"(d[55]), "+f"(d[56]), "+f"(d[57]), "+f"(d[58]), "+f"(d[59]), "+f"(d[60]), "+f"(d[61]), "+f"(d[62]), "+f"(d[63]), "+f"(d[64]), "+f"(d[65]), "+f"(d[66]), "+f"(d[67]), "+f"(d[68]), "+f"(d[69]), "+f"(d[70]), "+f"(d[71]), "+f"(d[72]), "+f"(d[73]), "+f"(d[74]), "+f"(d[75]), "+f"(d[76]), "+f"(d[77]), "+f"(d[78]), "+f"(d[79]), "+f"(d[80]), "+f"(d[81]), "+f"(d[82]), "+f"(d[83]), "+f"(d[84]), "+f"(d[85]), "+f"(d[86]), "+f"(d[87]), "+f"(d[88]), "+f"(d[89]), "+f"(d[90]), "+f"(d[91]), "+f"(d[92]), "+f"(d[93]), "+f"(d[94]), "+f"(d[95]), "+f"(d[96]), "+f"(d[97]), "+f"(d[98]), "+f"(d[99]), "+f"(d[100]), "+f"(d[101]), "+f"(d[102]), "+f"(d[103]), "+f"(d[104]), "+f"(d[105]), "+f"(d[106]), "+f"(d[107]), "+f"(d[108]), "+f"(d[109]), "+f"(d[110]), "+f"(d[111]), "+f"(d[112]), "+f"(d[113]), "+f"(d[114]), "+f"(d[115]), "+f"(d[116]), "+f"(d[117]), "+f"(d[118]), "+f"(d[119]), "+f"(d[120]), "+f"(d[121]), "+f"(d[122]), "+f"(d[123]), "+f"(d[124]), "+f"(d[125]), "+f"(d[126]), "+f"(d[127])
    : "r"(a0), "r"(a1), "r"(a2), "r"(a3), "l"(db), "r"(scale_d), "n"(OB));
}
template <int OB> __device__ __forceinline__ void wgmma_rs_n256_tb_first(float (&d)[128], uint32_t a0, uint32_t a1, uint32_t a2, uint32_t a3, uint64_t db) {
  asm volatile("{\n.reg .pred p;\n.reg .b64 b;\nsetp.ne.b32 p, 0, 0;\nadd.s64 b, %132, %133;\n"
    "wgmma.mma_async.sync.aligned.m64n256k16.f32.bf16.bf16 "
    "{%0, %1, %2, %3, %4, %5, %6, %7, %8, %9, %10, %11, %12, %13, %14, %15, %16, %17, %18, %19, %20, %21, %22, %23, %24, %25, %26, %27, %28, %29, %30, %31, %32, %33, %34, %35, %36, %37, %38, %39, %40, %41, %42, %43, %44, %45, %46, %47, %48, %49, %50, %51, %52, %53, %54, %55, %56, %57, %58, %59, %60, %61, %62, %63, %64, %65, %66, %67, %68, %69, %70, %71, %72, %73, %74, %75, %76, %77, %78, %79, %80, %81, %82, %83, %84, %85, %86, %87, %88, %89, %90, %91, %92, %93, %94, %95, %96, %97, %98, %99, %100, %101, %102, %103, %104, %105, %106, %107, %108, %109, %110, %111, %112, %113, %114, %115, %116, %117, %118, %119, %120, %121, %122, %123, %124, %125, %126, %127}, "
    "{%128, %129, %130, %131}, b, p, 1, 1, 1;\n}\n"
    : "=f"(d[0]), "=f"(d[1]), "=f"(d[2]), "=f"(d[3]), "=f"(d[4]), "=f"(d[5]), "=f"(d[6]), "=f"(d[7]), "=f"(d[8]), "=f"(d[9]), "=f"(d[10]), "=f"(d[11]), "=f"(d[12]), "=f"(d[13]), "=f"(d[14]), "=f"(d[15]), "=f"(d[16]), "=f"(d[17]), "=f"(d[18]), "=f"(d[19]), "=f"(d[20]), "=f"(d[21]), "=f"(d[22]), "=f"(d[23]), "=f"(d[24]), "=f"(d[25]), "=f"(d[26]), "=f"(d[27]), "=f"(d[28]), "=f"(d[29]), "=f"(d[30]), "=f"(d[31]), "=f"(d[32]), "=f"(d[33]), "=f"(d[34]), "=f"(d[35]), "=f"(d[36]), "=f"(d[37]), "=f"(d[38]), "=f"(d[39]), "=f"(d[40]), "=f"(d[41]), "=f"(d[42]), "=f"(d[43]), "=f"(d[44]), "=f"(d[45]), "=f"(d[46]), "=f"(d[47]), "=f"(d[48]), "=f"(d[49]), "=f"(d[50]), "=f"(d[51]), "=f"(d[52]), "=f"(d[53]), "=f"(d[54]), "=f"(d[55]), "=f"(d[56]), "=f"(d[57]), "=f"(d[58]), "=f"(d[59]), "=f"(d[60]), "=f"(d[61]), "=f"(d[62]), "=f"(d[63]), "=f"(d[64]), "=f"(d[65]), "=f"(d[66]), "=f"(d[67]), "=f"(d[68]), "=f"(d[69]), "=f"(d[70]), "=f"(d[71]), "=f"(d[72]), "=f"(d[73]), "=f"(d[74]), "=f"(d[75]), "=f"(d[76]), "=f"(d[77]), "=f"(d[78]), "=f"(d[79]), "=f"(d[80]), "=f"(d[81]), "=f"(d[82]), "=f"(d[83]), "=f"(d[84]), "=f"(d[85]), "=f"(d[86]), "=f"(d[87]), "=f"(d[88]), "=f"(d[89]), "=f"(d[90]), "=f"(d[91]), "=f"(d[92]), "=f"(d[93]), "=f"(d[94]), "=f"(d[95]), "=f"(d[96]), "=f"(d[97]), "=f"(d[98]), "=f"(d[99]), "=f"(d[100]), "=f"(d[101]), "=f"(d[102]), "=f"(d[103]), "=f"(d[104]), "=f"(d[105]), "=f"(d[106]), "=f"(d[107]), "=f"(d[108]), "=f"(d[109]), "=f"(d[110]), "=f"(d[111]), "=f"(d[112]), "=f"(d[113]), "=f"(d[114]), "=f"(d[115]), "=f"(d[116]), "=f"(d[117]), "=f"(d[118]), "=f"(d[119]), "=f"(d[120]), "=f"(d[121]), "=f"(d[122]), "=f"(d[123]), "=f"(d[124]), "=f"(d[125]), "=f"(d[126]), "=f"(d[127])
    : "r"(a0), "r"(a1), "r"(a2), "r"(a3), "l"(db), "n"(OB));
}
template <int OB> __device__ __forceinline__ void wgmma_rs_n128_tb(float (&d)[64], uint32_t a0, uint32_t a1, uint32_t a2, uint32_t a3, uint64_t db, int scale_d) {
  asm volatile("{\n.reg .pred p;\n.reg .b64 b;\nsetp.ne.b32 p, %69, 0;\nadd.s64 b, %68, %70;\n"
    "wgmma.mma_async.sync.aligned.m64n128k16.f32.bf16.bf16 "
    "{%0, %1, %2, %3, %4, %5, %6, %7, %8, %9, %10, %11, %12, %13, %14, %15, %16, %17, %18, %19, %20, %21, %22, %23, %24, %25, %26, %27, %28, %29, %30, %31, %32, %33, %34, %35, %36, %37, %38, %39, %40, %41, %42, %43, %44, %45, %46, %47, %48, %49, %50, %51, %52, %53, %54, %55, %56, %57, %58, %59, %60, %61, %62, %63}, "
    "{%64, %65, %66, %67}, b, p, 1, 1, 1;\n}\n"
    : "+f"(d[0]), "+f"(d[1]), "+f"(d[2]), "+f"(d[3]), "+f"(d[4]), "+f"(d[5]), "+f"(d[6]), "+f"(d[7]), "+f"(d[8]), "+f"(d[9]), "+f"(d[10]), "+f"(d[11]), "+f"(d[12]), "+f"(d[13]), "+f"(d[14]), "+f"(d[15]), "+f"(d[16]), "+f"(d[17]), "+f"(d[18]), "+f"(d[19]), "+f"(d[20]), "+f"(d[21]), "+f"(d[22]), "+f"(d[23]), "+f"(d[24]), "+f"(d[25]), "+f"(d[26]), "+f"(d[27]), "+f"(d[28]), "+f"(d[29]), "+f"(d[30]), "+f"(d[31]), "+f"(d[32]), "+f"(d[33]), "+f"(d[34]), "+f"(d[35]), "+f"(d[36]), "+f"(d[37]), "+f"(d[38]), "+f"(d[39]), "+f"(d[40]), "+f"(d[41]), "+f"(d[42]), "+f"(d[43]), "+f"(d[44]), "+f"(d[45]), "+f"(d[46]), "+f"(d[47]), "+f"(d[48]), "+f"(d[49]), "+f"(d[50]), "+f"(d[51]), "+f"(d[52]), "+f"(d[53]), "+f"(d[54]), "+f"(d[55]), "+f"(d[56]), "+f"(d[57]), "+f"(d[58]), "+f"(d[59]), "+f"(d[60]), "+f"(d[61]), "+f"(d[62]), "+f"(d[63])
    : "r"(a0), "r"(a1), "r"(a2), "r"(a3), "l"(db), "r"(scale_d), "n"(OB));
}
template <int V> using IC = std::integral_constant<int, V>;
template <int I, int N, class F> __device__ __forceinline__ void static_for(F&& f) {
  if constexpr (I < N) { f(std::integral_constant<int, I>{}); static_for<I + 1, N>(f); }
}

constexpr uint32_t SM_Q = 0, SM_BAR = 7 * 32768;
constexpr uint32_t B_FULL = SM_BAR, B_EMPTY = B_FULL + 24, B_WF = B_EMPTY + 24, B_QFULL = B_WF + 32, B_QEMPTY = B_QFULL + 16,
                   B_EVH = B_QEMPTY + 16, B_EVQ = B_EVH + 8, B_EVP0 = B_EVQ + 8, B_BG = B_EVP0 + 16, B_M0 = B_BG + 8, B_HALF = B_M0 + 8,
                   B_HRD = B_HALF + 8, SM_UNSAFE = B_HRD + 8, SM_TS = SM_UNSAFE + 8, SM_ML = (SM_TS + 192 + 15) / 16 * 16, SM_EPOCH = SM_ML + 1024, SM_END = SM_EPOCH + 16;
constexpr uint32_t POS_M = 0x5462;
constexpr int SMEM_BYTES = SM_END;

#define ROW0(u) make_uint4(pack_bf16(o[16 * u], o[16 * u + 1]), pack_bf16(o[16 * u + 4], o[16 * u + 5]), \
                           pack_bf16(o[16 * u + 8], o[16 * u + 9]), pack_bf16(o[16 * u + 12], o[16 * u + 13]))
#define ROW1(u) make_uint4(pack_bf16(o[16 * u + 2], o[16 * u + 3]), pack_bf16(o[16 * u + 6], o[16 * u + 7]), \
                           pack_bf16(o[16 * u + 10], o[16 * u + 11]), pack_bf16(o[16 * u + 14], o[16 * u + 15]))

__global__ void __launch_bounds__(384, 1) gps_kernel(const __grid_constant__ Params P) {
  extern __shared__ __align__(1024) uint8_t smem_raw[];
  constexpr uint32_t sb = 1024;
  if (smem_u32(smem_raw) != sb) return;
  const int cta = blockIdx.x;
  const int wg = __shfl_sync(0xffffffffu, (int)threadIdx.x >> 7, 0);
  const int warp = __shfl_sync(0xffffffffu, ((int)threadIdx.x >> 5) & 3, 0);
  const int lane = threadIdx.x & 31;
#define ROLE                                                                                       \
  const Work& W = P.w[cta_id()];                                                                   \
  [[maybe_unused]] const int n0 = W.nb0 + W.na0, n1 = W.nb1 + W.na1, total = n0 + n1;              \
  [[maybe_unused]] const bool fin = W.role & R_FIN, tail = W.role & R_TAIL;                        \
  [[maybe_unused]] const uint32_t posw = total == 0 || tail ? POS_M : ((total & 1) ? 0x2546 : 0x4326)
  const int g = lane >> 2, t = lane & 3;
  if (wg < 2) {
    const int tid = threadIdx.x & 127;
    ROLE;
    const uint32_t sQ = sb + SM_Q + wg * 32768;
#define st0 tid_is(wg * 128)
    STAMP(st0, wg, 0);
    const int rr = lane >> 3, j = lane & 7;
    const uint32_t c0 = clk();
    while (clk() - c0 < XDELAY) {}
    const uint4* px[4];
#pragma unroll
    for (int i = 0; i < 4; i++) px[i] = (const uint4*)(P.x + (size_t)min(W.q0 * 128 + wg * 64 + warp * 16 + i * 4 + rr, NN - 1) * 256) + j;
    auto x_load = [&](int c) {
      if (c < 4) {
#pragma unroll
        for (int i = 0; i < 4; i++)
          cp_async16(sQ + warp * 8192 + (i >> 1) * 4096 + c * 1024 + ((i & 1) * 4 + rr) * 128 + ((j ^ ((i & 1) * 4 + rr)) << 4), px[i] + c * 8);
      }
      cp_commit();
    };
    if (total > 0) {
#pragma unroll
      for (int c = 0; c < XD; c++) x_load(c);
    }
    bar_sync(4, 384);
    if (wg == 1) bar_arrive(5, 256);

    const uint32_t sF = sQ + warp * 8192 + ((lane >> 3) & 1) * 4096 + (lane & 7) * 128;
    auto frag = [&](int k) { return sF + (k >> 2) * 1024 + ((((k & 3) * 2 + (lane >> 4)) ^ (lane & 7)) << 4); };
    uint32_t hq[64];
    const bool own = (W.own >> wg) & 1;
    if (total > 0) {
      float c1[4] = {0.f, 0.f, 0.f, 0.f}, ca[4] = {0.f, 0.f, 0.f, 0.f}, cb[4] = {0.f, 0.f, 0.f, 0.f};
#pragma unroll
      for (int k = 0; k < 16; k++) {
        if ((k & 3) == 0) {
          asm volatile("cp.async.wait_group %0;" :: "n"(XD - 1) : "memory");
          __syncwarp();
          x_load(k / 4 + XD);
        }
        ldsm4(frag(k), hq[4 * k], hq[4 * k + 1], hq[4 * k + 2], hq[4 * k + 3]);
        mma16816(c1, hq[4 * k], hq[4 * k + 1], hq[4 * k + 2], hq[4 * k + 3], 0x3f803f80u, 0x3f803f80u);
        mma16816(ca, hq[4 * k], hq[4 * k + 1], hq[4 * k + 2], hq[4 * k + 3], hq[4 * k], hq[4 * k + 2]);
        mma16816(cb, hq[4 * k], hq[4 * k + 1], hq[4 * k + 2], hq[4 * k + 3], hq[4 * k + 1], hq[4 * k + 3]);
      }
      const float mu0 = c1[0] * (1.0f / 256.0f), mu1 = c1[2] * (1.0f / 256.0f);
      const float v0 = fmaf(__shfl_sync(0xffffffffu, g & 1 ? ca[1] : ca[0], g * 4 + (g >> 1)), 1.0f / 256.0f, 1e-5f - mu0 * mu0);
      const float v1 = fmaf(__shfl_sync(0xffffffffu, g & 1 ? cb[3] : cb[2], g * 4 + (g >> 1)), 1.0f / 256.0f, 1e-5f - mu1 * mu1);
      float rs0, rs1;
      asm("rsqrt.approx.ftz.f32 %0, %1;" : "=f"(rs0) : "f"(v0)); asm("rsqrt.approx.ftz.f32 %0, %1;" : "=f"(rs1) : "f"(v1));
      if (W.q0 * 128 + wg * 64 + warp * 16 >= NN) rs0 = rs1 = 0.f;
      float nb0 = -mu0 * rs0, nb1 = -mu1 * rs1;
      const uint32_t sS = sb + SM_ML + (wg * 64 + warp * 16) * 8;
      if (t == 0) {
        asm volatile("st.shared.v2.f32 [%0], {%1,%2};" :: "r"(sS + g * 8), "f"(rs0), "f"(nb0) : "memory");
        asm volatile("st.shared.v2.f32 [%0], {%1,%2};" :: "r"(sS + g * 8 + 64), "f"(rs1), "f"(nb1) : "memory");
      }
      if (__any_sync(0xffffffffu, !(4.f * mu0 * mu0 <= v0) || !(4.f * mu1 * mu1 <= v1))) {
#pragma unroll 1
        for (int r = 0; r < 16; r++) {
          const uint32_t ad = sQ + warp * 8192 + (r >> 3) * 4096 + rr * 1024 + (r & 7) * 128 + ((j ^ (r & 7)) << 4);
          const uint4 v = lds128(ad);
          float f[8] = {bf_lo(v.x), bf_hi(v.x), bf_lo(v.y), bf_hi(v.y), bf_lo(v.z), bf_hi(v.z), bf_lo(v.w), bf_hi(v.w)};
          float sum = 0.f, ss = 0.f, rs;
#pragma unroll
          for (int i = 0; i < 8; i++) sum += f[i];
#pragma unroll 1
          for (int k = 1; k < 32; k *= 2) sum += __shfl_xor_sync(0xffffffffu, sum, k);
          sum *= 1.0f / 256.0f;
#pragma unroll
          for (int i = 0; i < 8; i++) { f[i] -= sum; ss += f[i] * f[i]; }
#pragma unroll 1
          for (int k = 1; k < 32; k *= 2) ss += __shfl_xor_sync(0xffffffffu, ss, k);
          asm("rsqrt.approx.ftz.f32 %0, %1;" : "=f"(rs) : "f"(fmaf(ss, 1.0f / 256.0f, 1e-5f)));
          if (W.q0 * 128 + wg * 64 + warp * 16 >= NN) rs = 0.f;
          sts128(ad, make_uint4(pack_bf16(f[0] * rs, f[1] * rs), pack_bf16(f[2] * rs, f[3] * rs), pack_bf16(f[4] * rs, f[5] * rs), pack_bf16(f[6] * rs, f[7] * rs)));
          if (lane == 0) asm volatile("st.shared.v2.f32 [%0], {%1,%2};" :: "r"(sS + r * 8), "f"(rs), "f"(-sum * rs) : "memory");
        }
        __syncwarp();
#pragma unroll
        for (int k = 0; k < 16; k++) ldsm4(frag(k), hq[4 * k], hq[4 * k + 1], hq[4 * k + 2], hq[4 * k + 3]);
        rs0 = rs1 = 1.f; nb0 = nb1 = 0.f;
      }
      asm volatile("setmaxnreg.inc.sync.aligned.u32 %0;" :: "n"(CREG));
      const uint32_t ah0 = pack_bf16(rs0, rs0), ah1 = pack_bf16(rs1, rs1), n0_ = pack_bf16(nb0, nb0), n1_ = pack_bf16(nb1, nb1);
      const uint32_t al0 = pack_bf16(rs0 - bf_lo(ah0), rs0 - bf_lo(ah0)), al1 = pack_bf16(rs1 - bf_lo(ah1), rs1 - bf_lo(ah1));
#pragma unroll
      for (int i = 0; i < 32; i++) {
        hq[2 * i] = hfma2(hq[2 * i], ah0, hfma2(hq[2 * i], al0, n0_));
        hq[2 * i + 1] = hfma2(hq[2 * i + 1], ah1, hfma2(hq[2 * i + 1], al1, n1_));
      }
      if (own) {
        const float e0 = fmaf(bf_hi(__shfl_sync(0xffffffffu, hq[62], lane | 3)), -0.5f * KS, KC), e1 = fmaf(bf_hi(__shfl_sync(0xffffffffu, hq[63], lane | 3)), -0.5f * KS, KC);
#pragma unroll
        for (int k = 0; k < 16; k++)
          stsm4(frag(k), hfma2(hq[4 * k], KS2, KC2), hfma2(hq[4 * k + 1], KS2, KC2),
                k < 15 ? hfma2(hq[4 * k + 2], KS2, KC2) : pack_bf16(fmaf(bf_lo(hq[62]), KS, e0), t == 3 ? KC : fmaf(bf_hi(hq[62]), KS, e0)),
                k < 15 ? hfma2(hq[4 * k + 3], KS2, KC2) : pack_bf16(fmaf(bf_lo(hq[63]), KS, e1), t == 3 ? KC : fmaf(bf_hi(hq[63]), KS, e1)));
      }
      __syncwarp();
      if (lane == 0) mbar_arrive(sb + B_EVH);
    } else {
      asm volatile("setmaxnreg.inc.sync.aligned.u32 %0;" :: "n"(CREG));
    }
    STAMP(st0, wg, 1);

    float o[128];
    int qph = 0, st = tail ? wg : 0, ph = 0;
    auto release = [&](int stg) { if (lane == 0) mbar_arrive(sb + B_EMPTY + 8 * stg); };
    int resume = total > 0 ? -1 : 0;
    auto fill = [&]() __attribute__((always_inline)) {
#pragma unroll
      for (int i = 0; i < 32; i++)
        asm volatile("ld.volatile.shared.v4.f32 {%0,%1,%2,%3}, [%4];" : "=f"(o[4 * i]), "=f"(o[4 * i + 1]), "=f"(o[4 * i + 2]), "=f"(o[4 * i + 3]) : "r"(sb) : "memory");
    };
    auto finish = [&]() __attribute__((always_inline)) {
      STAMP(st0, wg, 11);
      DUMP(st0, wg, 0, 16);
      if (!P.zero) { asm volatile("exit;"); __builtin_unreachable(); }
      fill();
    };
    auto run = [&](auto hot_) __attribute__((always_inline)) {
    constexpr bool HOT = hot_.value;
    const int nloc = P.w[cta_id()].nloc;
    if (!HOT && resume == 0) {
#pragma unroll 1
      for (int i = 0; i < 32; i++) {
        const int r = i * 8 + wg * 4 + warp;
        cp_async16(sb + ((POS_M >> (r >> 6) * 4) & 15) * 32768 + sw_byte(r & 63, lane * 8), (const uint4*)P.wout + r * 32 + lane);
      }
    }
    bool wide = false;
    if (HOT) {
      reg_fence(hq);
      auto qstep = [&](auto k_) {
        constexpr int k = k_.value;
        if (k < 2 || k % 4 == 0) { mbar_wait(k == 0 ? sb + B_M0 : sb + B_WF + 2 * (k & ~3), 0); if (k == 0 || k == 4) bar_sync(5 + wg, 256); wg_fence(); }
        if constexpr (k == 0) wgmma_rs_n256_tb_first<0>(o, hq[0], hq[1], hq[2], hq[3], desc_mn(sb, (POS_M & 15) * 2048));
        else wgmma_rs_n256_tb<(k & 3) * 512>(o, hq[4 * k], hq[4 * k + 1], hq[4 * k + 2], hq[4 * k + 3], desc_mn(sb, ((POS_M >> (k & ~3)) & 15) * 2048), 1);
      };
      static_for<0, 4>(qstep);
      wg_commit();
      bar_arrive(6 - wg, 256);
      wg_wait<0>();
      if (!tail) release(0);
      static_for<4, 16>(qstep);
      wg_commit();
      bar_arrive(6 - wg, 256);
      wg_wait<0>();
      reg_fence(o); reg_fence(hq);
      if (!tail) release(1);
      STAMP(st0, wg, 2);
      float c0 = (o[124] + (t == 3 ? 2.f : 1.f) * o[125]) * (-0.5f / 4.5f), c1 = (o[126] + (t == 3 ? 2.f : 1.f) * o[127]) * (-0.5f / 4.5f);
      c0 += __shfl_xor_sync(0xffffffffu, c0, 1); c1 += __shfl_xor_sync(0xffffffffu, c1, 1);
      c0 += __shfl_xor_sync(0xffffffffu, c0, 2); c1 += __shfl_xor_sync(0xffffffffu, c1, 2);
      float r0 = t == 3 ? 0.f : o[125], r1 = t == 3 ? 0.f : o[127], r2 = o[124], r3 = o[126];
#pragma unroll
      for (int i = 0; i < 31; i++) { r2 += o[4 * i]; r0 += o[4 * i + 1]; r3 += o[4 * i + 2]; r1 += o[4 * i + 3]; }
      r0 += r2; r1 += r3;
      r0 += __shfl_xor_sync(0xffffffffu, r0, 1); r1 += __shfl_xor_sync(0xffffffffu, r1, 1);
      r0 += __shfl_xor_sync(0xffffffffu, r0, 2); r1 += __shfl_xor_sync(0xffffffffu, r1, 2);
      r0 = fmaf(c0, -255.f, PSH / KC - r0); r1 = fmaf(c1, -255.f, PSH / KC - r1);
      wide = !(fabsf(c0) <= SAFE_C / KS) || !(fabsf(c1) <= SAFE_C / KS);
      if (own) mbar_wait(sb + B_HRD, 0);
#pragma unroll
      for (int k = 0; k < 16; k++)
        stsm4(frag(k),
              pack_bf16(o[8 * k] + c0, o[8 * k + 1] + c0), pack_bf16(o[8 * k + 2] + c1, o[8 * k + 3] + c1),
              pack_bf16(o[8 * k + 4] + c0, k == 15 && t == 3 ? r0 : o[8 * k + 5] + c0), pack_bf16(o[8 * k + 6] + c1, k == 15 && t == 3 ? r1 : o[8 * k + 7] + c1));
      fence_async_smem();
      __syncwarp();
      STAMP(st0, wg, 3);
      if (tail) { bar_sync(7, 256); if (wg == 0) { release(0); release(1); release(2); } }
      }

    if (HOT || (resume && resume < 4)) {
      ROLE;
      float m0, m1;
      const int qh = tail ? 0 : wg, tl = tail;
      uint32_t qo = qh * 2048;
      const uint32_t ko = (2 - tl) * 2048, stop = 1 + tl + (uint32_t)P.zero;
      float l0, l1;
      auto row_sums = [&]() { l0 = __shfl_sync(0xffffffffu, o[125] + 0.f, lane | 3); l1 = __shfl_sync(0xffffffffu, o[127] + 0.f, lane | 3); };
#define PART(u) make_uint4(pack_bf16(o[8 * u] - l0, o[8 * u + 1] - l0), pack_bf16(o[8 * u + 2] - l1, o[8 * u + 3] - l1), \
                           pack_bf16(o[8 * u + 4] - l0, o[8 * u + 5] - l0), pack_bf16(o[8 * u + 6] - l1, o[8 * u + 7] - l1))
      bool unsafe = !HOT;
      m0 = m1 = 0.f;
#pragma unroll 1
      for (int seg = HOT ? 0 : resume - 1; seg < 2; seg++) {
        ROLE;
        const bool last = __any_sync(0xffffffffu, seg || n1 == 0);
        m0 = m1 = !HOT && unsafe ? -INFINITY : 0.f;
        int first = 1;
        auto tile = [&](auto n_, bool endseg) __attribute__((always_inline)) -> bool {
          constexpr int N = n_.value;
          float s[N / 2]; uint32_t p[N / 4];
          if (!mbar_try_wait(sb + B_FULL + 8 * st, ph)) mbar_wait(sb + B_FULL + 8 * st, ph);
          const bool again = !HOT && N == 112 && first && !seg;
          if (HOT || N == 128) bar_sync(5 + wg, 256);
          else asm volatile("{\n.reg .pred p;\nsetp.eq.u32 p, %1, 0;\n@p bar.sync %0, 256;\n}\n" :: "r"(5 + wg), "r"((uint32_t)again) : "memory");
          wg_fence();
          const uint64_t dQ = desc_k(sb + SM_Q, qo), dK = desc_k(sb, ko + st * 4096);
          qo += (uint32_t)P.zero;
          static_for<0, 16>([&](auto k) { constexpr int kk = (k.value + KROT) & 15, off = (kk >> 2) * 64 + (kk & 3) * 2; wgmma_qk<off, off>(s, dQ, dK, k.value > 0); });
          wg_commit();
          if (HOT || N == 128) bar_arrive(6 - wg, 256);
          else asm volatile("{\n.reg .pred p;\nsetp.eq.u32 p, %1, 0;\n@p bar.arrive %0, 256;\n}\n" :: "r"(6 - wg), "r"((uint32_t)again) : "memory");
          if (HOT && N == 112 && first && !seg) {
            float a0 = 0.f, a1 = 0.f, a2 = 0.f, a3 = 0.f;
#pragma unroll
            for (int i = 0; i < 32; i++) { a0 += o[4 * i] * o[4 * i]; a2 += o[4 * i + 1] * o[4 * i + 1]; a1 += o[4 * i + 2] * o[4 * i + 2]; a3 += o[4 * i + 3] * o[4 * i + 3]; }
            a0 += a2; a1 += a3;
            a0 += __shfl_xor_sync(0xffffffffu, a0, 1); a1 += __shfl_xor_sync(0xffffffffu, a1, 1);
            a0 += __shfl_xor_sync(0xffffffffu, a0, 2); a1 += __shfl_xor_sync(0xffffffffu, a1, 2);
            unsafe = __any_sync(0xffffffffu, bar_red_or(tail ? 7 : 1 + wg, tail ? 256 : 128, wide || !(a0 <= SAFE_N2 / (KS * KS)) || !(a1 <= SAFE_N2 / (KS * KS))));
            if (lane == 0) { asm volatile("st.shared.u8 [%0], %1;" :: "r"(sb + SM_UNSAFE + wg), "r"((uint32_t)unsafe) : "memory"); mbar_arrive(sb + B_EVQ); }
          }
          STAMP(N == 112 && first && !seg && st0, wg, 0);
          wg_wait<0>();
          reg_fence(s);
          if (HOT && N == 112 && unsafe) return true;
          if (endseg) { if (lane == 0) mbar_arrive(sb + B_QEMPTY + 8 * wg); }
          if (!HOT && unsafe) {
            float a0 = fmaxf(s[0], s[1]), a1 = fmaxf(s[2], s[3]);
#pragma unroll
            for (int i = 1; i < N / 8; i++) { a0 = fmaxf(a0, fmaxf(s[4 * i], s[4 * i + 1])); a1 = fmaxf(a1, fmaxf(s[4 * i + 2], s[4 * i + 3])); }
            if (__any_sync(0xffffffffu, (a0 > m0 + TAU) || (a1 > m1 + TAU))) {
              a0 = fmaxf(a0, __shfl_xor_sync(0xffffffffu, a0, 1)); a1 = fmaxf(a1, __shfl_xor_sync(0xffffffffu, a1, 1));
              a0 = fmaxf(a0, __shfl_xor_sync(0xffffffffu, a0, 2)); a1 = fmaxf(a1, __shfl_xor_sync(0xffffffffu, a1, 2));
              const float x0 = ceilf(fmaxf(m0, a0)), x1 = ceilf(fmaxf(m1, a1)), sc0 = ex2(m0 - x0), sc1 = ex2(m1 - x1);
              m0 = x0; m1 = x1;
#pragma unroll
              for (int i = 0; i < 32; i++) { o[4 * i] *= sc0; o[4 * i + 1] *= sc0; o[4 * i + 2] *= sc1; o[4 * i + 3] *= sc1; }
            }
#pragma unroll
            for (int i = 0; i < N / 8; i++) { s[4 * i] -= m0; s[4 * i + 1] -= m0; s[4 * i + 2] -= m1; s[4 * i + 3] -= m1; }
          }
          auto pv = [&](auto k) { wgmma_rs_n256_tb<k.value * 512 + (63 << 16)>(o, p[4 * k.value], p[4 * k.value + 1], p[4 * k.value + 2], p[4 * k.value + 3], dK, k.value > 0 || N == 128 ? 1 : !first); };
#pragma unroll
          for (int i = 0; i < 16; i++) { p[i] = pack_bf16(ex2(s[2 * i]), ex2(s[2 * i + 1])); asm volatile("" : "+r"(p[i]) :: "memory"); }
          reg_fence(o);
          do bar_sync(5 + wg, 256); while (P.zero);
          wg_fence();
          static_for<0, 4>(pv);
          wg_commit();
#pragma unroll
          for (int i = 16; i < N / 4; i++) { p[i] = pack_bf16(ex2(s[2 * i]), ex2(s[2 * i + 1])); asm volatile("" : "+r"(p[i]) :: "memory"); }
          wg_fence();
          static_for<4, N / 16>(pv);
          wg_commit();
          bar_arrive(6 - wg, 256);
          if (N == 128) { wg_wait<1>(); if (endseg && last) { if (lane == 0) mbar_arrive(sb + B_HALF); } }
          wg_wait<0>();
          reg_fence(o); reg_fence(p);
          release(st);
          if (st) { st--; ph ^= 1; } else st = stop;
          return false;
        };
#pragma unroll 1
        for (int left = tail ? 8 - wg : (seg ? W.nb1 : W.nb0); left > 0; left--) { if (tile(IC<112>{}, false)) { resume = 1; return; } STAMP(first && !seg && st0, wg, 4); first = 0; }
#pragma unroll 1
        for (int left = tail ? 32 + wg : (seg ? W.na1 : W.na0); left > 0; left--) tile(IC<128>{}, left == 1);
        STAMP(st0 && last, wg, 6);
        {
        ROLE;
        if (last && fin && !(tail && wg == 1)) break;
        row_sums();
        if (last) mbar_wait(sb + (tail ? B_QEMPTY : B_HALF), 0);
        const uint32_t sp = sb + (tail ? 0 : (last ? (posw >> 12) + wg : (wg ? 4 - 2 * st : 6))) * 32768, sm = sb + SM_ML + (tail ? 0 : wg) * 512;
#pragma unroll
        for (int u = 0; u < 16; u++) sts128(sp + (u * 128 + tid) * 16, PART(u));
        if (t == 0) {
          asm volatile("st.shared.v2.f32 [%0], {%1,%2};" :: "r"(sm + (warp * 16 + g) * 8), "f"(m0), "f"(l0) : "memory");
          asm volatile("st.shared.v2.f32 [%0], {%1,%2};" :: "r"(sm + (warp * 16 + g) * 8 + 64), "f"(m1), "f"(l1) : "memory");
        }
        __syncwarp();
        if (lane == 0) mbar_arrive(sb + B_EVP0 + 8 * wg);
        STAMP(st0 && last, wg, 7);
        if (last) break;
        mbar_wait(sb + B_QFULL + 8 * wg, qph); qph ^= 1;
        uint32_t u; asm volatile("ld.shared.u8 %0, [%1];" : "=r"(u) : "r"(sb + SM_UNSAFE + wg) : "memory");
        unsafe = __any_sync(0xffffffffu, u != 0);
        if (HOT && unsafe) { resume = 2; return; }
        }
      }

      if (P.w[cta_id()].role & R_FIN) {
        ROLE;
        if (!(tail && wg == 1)) {
        row_sums();
        const int rl = wg * 64 + warp * 16 + g;
        uint32_t a[64];
#pragma unroll
        for (int i = 0; i < 64; i++) a[i] = pack_bf16(o[2 * i] - (i & 1 ? l1 : l0), o[2 * i + 1] - (i & 1 ? l1 : l0));
        reg_fence(a);
        {
          float2 e0, e1;
          mbar_wait(sb + B_QFULL + 8 * wg, qph);
          asm volatile("ld.shared.v2.f32 {%0,%1}, [%2];" : "=f"(e0.x), "=f"(e0.y) : "r"(sb + SM_ML + rl * 8) : "memory");
          asm volatile("ld.shared.v2.f32 {%0,%1}, [%2];" : "=f"(e1.x), "=f"(e1.y) : "r"(sb + SM_ML + rl * 8 + 64) : "memory");
          STAMP(st0, wg, 7);
          uint32_t fb0 = 0x3f803f80u, fb1 = 0x3f803f80u;
          const float s0 = l0 + e0.y, s1 = l1 + e1.y;
          const bool odd = __any_sync(0xffffffffu, m0 != e0.x || m1 != e1.x || !(fmaxf(s0, s1) < 0x1p40f) || !(fminf(s0, s1) > 0x1p-40f));
          if (HOT && odd) { resume = 3; return; }
          uint4 v[16];
#pragma unroll
          for (int u = 0; u < 16; u++) v[u] = lds128(sQ + (u * 128 + tid) * 16);
          if (!HOT && odd) {
            const float x0 = fmaxf(m0, e0.x), x1 = fmaxf(m1, e1.x);
            const float d0 = fmaxf(m0 - x0, -1000.f), d1 = fmaxf(m1 - x1, -1000.f), f0 = fmaxf(e0.x - x0, -1000.f), f1 = fmaxf(e1.x - x1, -1000.f);
            l0 = l0 * ex2(d0) + e0.y * ex2(f0); l1 = l1 * ex2(d1) + e1.y * ex2(f1);
            const int E0 = fexp(l0), E1 = fexp(l1);
            const uint32_t fa0 = pow2_bf2((int)d0 - E0), fa1 = pow2_bf2((int)d1 - E1);
            fb0 = pow2_bf2((int)f0 - E0); fb1 = pow2_bf2((int)f1 - E1);
            l0 = __uint_as_float(__float_as_uint(l0) - (E0 << 23)); l1 = __uint_as_float(__float_as_uint(l1) - (E1 << 23));
#pragma unroll
            for (int i = 0; i < 32; i++) { a[2 * i] = hmul2(a[2 * i], fa0); a[2 * i + 1] = hmul2(a[2 * i + 1], fa1); }
          } else { l0 = s0; l1 = s1; }
#pragma unroll
          for (int u = 0; u < 16; u++) {
            a[4 * u] = hfma2(v[u].x, fb0, a[4 * u]); a[4 * u + 1] = hfma2(v[u].y, fb1, a[4 * u + 1]);
            a[4 * u + 2] = hfma2(v[u].z, fb0, a[4 * u + 2]); a[4 * u + 3] = hfma2(v[u].w, fb1, a[4 * u + 3]);
          }
        }
        float fs0, fs1;
        asm("rcp.approx.ftz.f32 %0, %1;" : "=f"(fs0) : "f"(l0 * (KS / KC))); asm("rcp.approx.ftz.f32 %0, %1;" : "=f"(fs1) : "f"(l1 * (KS / KC)));
        STAMP(st0, wg, 8);
        reg_fence(a);
        bar_sync(5 + wg, 256);
        uint64_t dW[4];
        float y0[64], y1[64];
        auto half0 = [&](auto u_) {
          constexpr int u = u_.value;
          if (u % 4 == 0) { mbar_wait(sb + B_WF + 2 * u, 1); wg_fence(); dW[u / 4] = desc_mn(sb, ((posw >> u) & 15) * 2048); }
          wgmma_rs_n128_tb<(u & 3) * 512>(y0, a[4 * u], a[4 * u + 1], a[4 * u + 2], a[4 * u + 3], dW[u / 4], u != 0);
        };
        auto half1 = [&](auto u_) {
          constexpr int u = u_.value;
          wgmma_rs_n128_tb<(u & 3) * 512 + 128>(y1, a[4 * u], a[4 * u + 1], a[4 * u + 2], a[4 * u + 3], dW[u / 4], u != 0);
        };
        const bool wr = W.q0 * 128 + wg * 64 + warp * 16 < NN;
        uint4* po = (uint4*)(P.out + (size_t)(W.q0 * 128 + rl) * 256) + t;
        auto emit = [&](const float* y, uint4* dst) {
          if (wr) {
            red_bf16x8(dst, make_uint4(pack_bf16(y[0] * fs0, y[1] * fs0), pack_bf16(y[4] * fs0, y[5] * fs0), pack_bf16(y[8] * fs0, y[9] * fs0), pack_bf16(y[12] * fs0, y[13] * fs0)));
            red_bf16x8(dst + 8 * 32, make_uint4(pack_bf16(y[2] * fs1, y[3] * fs1), pack_bf16(y[6] * fs1, y[7] * fs1), pack_bf16(y[10] * fs1, y[11] * fs1), pack_bf16(y[14] * fs1, y[15] * fs1)));
          }
          wg_fence();
        };
        static_for<0, 16>(half0);
        wg_commit();
        static_for<0, 4>(half1);
        wg_commit();
        wg_wait<1>();
        reg_fence(y0);
        emit(y0, po); static_for<4, 8>(half1);
        emit(y0 + 16, po + 4); static_for<8, 12>(half1);
        emit(y0 + 32, po + 8); static_for<12, 16>(half1);
        wg_commit();
        bar_arrive(6 - wg, 256);
        emit(y0 + 48, po + 12);
        wg_wait<0>();
        reg_fence(a); reg_fence(y1);
        STAMP(st0, wg, 9);
#pragma unroll
        for (int u = 0; u < 4; u++) emit(y1 + 16 * u, po + 16 + 4 * u);
        }
        if (!tail) { STAMP(st0, wg, 11); DUMP(st0, wg, 0, 16); asm volatile("exit;"); __builtin_unreachable(); }
        if (wg == 1) { bar_sync(6, 256); bar_arrive(5, 256); } else qph ^= 1;
        __syncwarp();
        if (lane == 0) mbar_arrive(sb + B_QEMPTY + 8 * wg);
        fill();
        resume = 4;
      }
        }
#pragma unroll 1
    for (int step = HOT || resume ? 0 : -4; step < (HOT && resume == 4 ? 0 : nloc); step++) {
      ROLE;
      const bool helper = HOT || (resume && resume < 4);
      const bool isw = !HOT && step < 0;
      if (isw) {
        const uint4* src = (const uint4*)(step < -2 ? P.wmsg : P.wv) + ((step & 1) * 128 + wg * 64 + warp) * 32 + lane;
        float cw[8] = {0.f, 0.f, 0.f, 0.f, 0.f, 0.f, 0.f, 0.f};
#pragma unroll 1
        for (int i = 0; i < 16; i++) cp_async16(sQ + sw_byte(i * 4 + warp, lane * 8), src + i * 128);
        cp_commit();
#pragma unroll
        for (int i = 0; i < 8; i++) {
          const uint4 v = __ldg((const uint4*)(step < -2 ? P.wmsg : P.wv) + (248 + i) * 32 + lane);
          const float k = step < -2 ? 0.f : (i == 7 ? -1.0f / 4.5f : -0.5f / 4.5f);
          cw[0] += bf_lo(v.x) * k; cw[1] += bf_hi(v.x) * k; cw[2] += bf_lo(v.y) * k; cw[3] += bf_hi(v.y) * k;
          cw[4] += bf_lo(v.z) * k; cw[5] += bf_hi(v.z) * k; cw[6] += bf_lo(v.w) * k; cw[7] += bf_hi(v.w) * k;
        }
        asm volatile("cp.async.wait_group 0;" ::: "memory");
#pragma unroll 1
        for (int i = 0; i < 16; i++) {
          const uint32_t ad = sQ + sw_byte(i * 4 + warp, lane * 8);
          const uint4 v = lds128(ad);
          uint4 w4 = make_uint4(pack_bf16(bf_lo(v.x) + cw[0], bf_hi(v.x) + cw[1]), pack_bf16(bf_lo(v.y) + cw[2], bf_hi(v.y) + cw[3]),
                                pack_bf16(bf_lo(v.z) + cw[4], bf_hi(v.z) + cw[5]), pack_bf16(bf_lo(v.w) + cw[6], bf_hi(v.w) + cw[7]));
          if (step == -1 && wg * 64 + i * 4 + warp == 127) w4 = make_uint4(0, 0, 0, 0);
          sts128(ad, w4);
        }
        fence_async_smem();
        bar_sync(7, 256);
      } else {
        SSTAMP(0);
        mbar_wait(sb + B_QFULL + 8 * wg, qph); qph ^= 1;
        STAMP(st0 && step == 0, wg, 8);
        SSTAMP(1);
        bar_sync(5 + wg, 256);
        SSTAMP(2);
      }
#pragma unroll 1
      for (int c = 0; c < 4; c++) {
        if (step == 0) mbar_wait(sb + B_WF + 8 * c, helper);
        const int turn2 = helper ? 3 : 4;
        if (c == turn2) bar_sync(5 + wg, 256);
        wg_fence();
        const uint64_t dA = desc_k(sb + SM_Q, wg * 2048 + c * 64), dW = desc_mn(sb, ((posw >> c * 4) & 15) * 2048);
        static_for<0, 4>([&](auto k) { wgmma_ss_n256_tb<k.value * 2, k.value * 512>(o, dA, dW, k.value > 0 ? 1 : c); });
        wg_commit();
        if ((c == 3 || c == turn2 - 1) && !isw) bar_arrive(6 - wg, 256);
        wg_wait<1>();
      }
      wg_wait<0>();
      reg_fence(o);
      {
        STAMP(st0 && step == 0, wg, 9);
        SSTAMP(3);
        if (isw) bar_sync(1 + wg, 128); else if (lane == 0) mbar_arrive(sb + B_QEMPTY + 8 * wg);
        uint8_t* dw = (uint8_t*)(step < -2 ? g_Wmo : g_Wvo) + ((step & 1) * 2 + wg) * 32768 + warp * 8192 + g * 128;
        const int row0 = (W.loc0 + step) * 128 + wg * 64 + warp * 16;
        uint4 r[16];
#pragma unroll
        for (int u = 0; u < 8; u++) { r[2 * u] = ROW0(u); r[2 * u + 1] = ROW1(u); }
        if (isw) {
#pragma unroll
          for (int u = 0; u < 16; u++) *(uint4*)(dw + (u >> 2) * 1024 + ((((u & 2) * 2 + t) ^ g) << 4) + (u & 1) * 4096) = r[u];
        } else if (row0 < NN) {
          uint4* po = (uint4*)(P.out + (size_t)(row0 + g) * 256) + t;
          uint32_t c1 = clk();
#pragma unroll
          for (int u = 0; u < 16; u++) {
            red_bf16x8(po + (u >> 1) * 4 + (u & 1) * 256, r[u]);
            if (!HOT) { c1 += PACE; while ((int)(clk() - c1) < 0) {} }
          }
        }
        if (!HOT && step == -1) { bar_sync(7, 256); if (tid_is(0)) flag_release(F_W); __syncwarp(); STAMP(st0, wg, 3); }
      }
    }
    if (HOT && resume == 4) return;
    finish();
    };
    if (resume < 0) run(std::true_type{});
    else fill();
    run(std::false_type{});
    asm volatile("setmaxnreg.dec.sync.aligned.u32 %0;" :: "n"(504 - 2 * CREG));
  } else {
    STAMP(lane == 0 && warp == 0, 2, 0);
        const int mi = cta >> 3;
    const uint32_t sW = sb + 3 * 32768;
    uint4 wa[4], wb[8];
    {
      const uint4* pq = (const uint4*)(P.wq + ((mi & 15) * 16 + g) * 256) + warp * 8 + t;
      const uint4* pk = (const uint4*)(P.wk + ((cta & 7) * 32 + g) * 256) + warp * 8 + t;
#pragma unroll
      for (int i = 0; i < 4; i++) wa[i] = __ldg(pq + (i >> 1) * 256 + (i & 1) * 4);
#pragma unroll
      for (int i = 0; i < 8; i++) wb[i] = __ldg(pk + (i >> 1) * 256 + (i & 1) * 4);
    }
    if (threadIdx.x == 352) {
      for (int i = 0; i < 3; i++) { mbar_init(sb + B_FULL + 8 * i, 1); mbar_init(sb + B_EMPTY + 8 * i, cta == 130 ? 4 : 8); }
      for (int i = 0; i < 4; i++) mbar_init(sb + B_WF + 8 * i, 1);
      for (int i = 0; i < 2; i++) { mbar_init(sb + B_QFULL + 8 * i, 1); mbar_init(sb + B_QEMPTY + 8 * i, 4); mbar_init(sb + B_EVP0 + 8 * i, 4); }
      mbar_init(sb + B_EVH, 8); mbar_init(sb + B_EVQ, 8); mbar_init(sb + B_HALF, 8); mbar_init(sb + B_BG, 1); mbar_init(sb + B_M0, 1); mbar_init(sb + B_HRD, 1);
      asm volatile("fence.mbarrier_init.release.cluster;" ::: "memory");
    }
    __syncwarp();
    do bar_sync(4, 384); while (P.zero);
    {
#pragma unroll
      for (int n = 0; n < 4; n++) {
        float c[4] = {0.f, 0.f, 0.f, 0.f};
#pragma unroll
        for (int u = 0; u < 2; u++) {
          mma16816(c, wa[u].x, wa[2 + u].x, wa[u].y, wa[2 + u].y, wb[2 * n + u].x, wb[2 * n + u].y);
          mma16816(c, wa[u].z, wa[2 + u].z, wa[u].w, wa[2 + u].w, wb[2 * n + u].z, wb[2 * n + u].w);
        }
        asm volatile("st.shared.v2.f32 [%0], {%1,%2};" :: "r"(sW + ((warp * 16 + g) * 40 + n * 8 + 2 * t) * 4), "f"(c[0]), "f"(c[1]) : "memory");
        asm volatile("st.shared.v2.f32 [%0], {%1,%2};" :: "r"(sW + ((warp * 16 + g + 8) * 40 + n * 8 + 2 * t) * 4), "f"(c[2]), "f"(c[3]) : "memory");
      }
      STAMP(lane == 0 && warp == 0, 2, 7);
      bar_sync(3, 128);
      if (warp < 2) {
        float c[8] = {0.f, 0.f, 0.f, 0.f, 0.f, 0.f, 0.f, 0.f};
#pragma unroll
        for (int k = 0; k < 4; k++) {
          const uint4 v = lds128(sW + ((k * 16 + warp * 8 + g) * 40 + t * 8) * 4), w = lds128(sW + ((k * 16 + warp * 8 + g) * 40 + t * 8 + 4) * 4);
          c[0] += __uint_as_float(v.x); c[1] += __uint_as_float(v.y); c[2] += __uint_as_float(v.z); c[3] += __uint_as_float(v.w);
          c[4] += __uint_as_float(w.x); c[5] += __uint_as_float(w.y); c[6] += __uint_as_float(w.z); c[7] += __uint_as_float(w.w);
        }
        const float ms = 1.4426950408889634f / 16.0f / KS;
        const uint4 m4 = make_uint4(pack_bf16(c[0] * ms, c[1] * ms), pack_bf16(c[2] * ms, c[3] * ms), pack_bf16(c[4] * ms, c[5] * ms), pack_bf16(c[6] * ms, c[7] * ms));
        sts128(sW + 16384 + (warp * 8 + g) * 64 + ((t ^ (g & 3)) << 4), m4);
      }
    }
    asm volatile("setmaxnreg.dec.sync.aligned.u32 %0;" :: "n"(504 - 2 * CREG));
    STAMP(lane == 0 && warp == 0, 2, 13);
    bar_sync(3, 128);
#define ep1 (lds32(sb + SM_EPOCH) + 1)
    if (threadIdx.x == 256 && cta < 128) {
      {
        fence_async_smem();
#pragma unroll 1
        for (int r = 0; r < 16; r++)
          bulk_s2g((uint8_t*)g_M + (mi * 2 + (r >> 3)) * 4096 + ((cta & 7) >> 1) * 1024 + (r & 7) * 128 + ((((cta & 1) * 4) ^ (r & 4)) << 4), sW + 16384 + r * 64, 64);
        bulk_commit();
        bulk_wait_all();
        red_relaxed(g_flag + F_M + (cta >> 5));
      }
    }
    __syncwarp();
    ROLE;
    if (warp == 3 && W.own) {
      mbar_wait_w(sb + B_EVH, 0);
      if (W.role < R_SIG) mbar_wait_w(sb + B_WF + 8, 0);
      if (lane == 0) {
        fence_async_smem();
        const int h0 = W.own == 2, nh = W.own == 3 ? 2 : 1;
        bulk_s2g(g_h + W.hp * 4096 + h0 * 2048, sb + SM_Q + h0 * 32768, nh * 32768);
        bulk_s2g(g_stat + W.q0 * 128 + h0 * 64, sb + SM_ML + h0 * 512, nh * 512);
        bulk_commit();
        bulk_wait_read();
        mbar_arrive(sb + B_HRD);
        bulk_wait_all();
        if (W.role >= R_SIG) red_relaxed(g_flag + F_H1 - 1 + W.role / R_SIG);
        red_relaxed(g_flag + F_H);
      }
      __syncwarp();
      STAMP(lane == 0, 2, 6);
    }
    if (warp == 0) {
      if (lane == 0) {
        STAMP(true, 2, 1);
        const uint32_t epoch = ld_relaxed(g_flag + F_EPOCH);
        if (total > 0) {
#pragma unroll
          for (int c = 0; c < 3; c++) mbar_expect_tx(sb + B_WF + 8 * c, c == 0 ? WCH_B - 8192 : WCH_B);
          mbar_expect_tx(sb + B_M0, 8192);
          int c = 0;
#pragma unroll 1
          for (uint32_t it = 0; c < 4; it++) {
            uint4 f;
            asm volatile("ld.relaxed.gpu.global.v4.u32 {%0,%1,%2,%3}, [%4];" : "=r"(f.x), "=r"(f.y), "=r"(f.z), "=r"(f.w) : "l"(g_flag + F_M) : "memory");
            uint32_t tm;
            asm volatile("mad.lo.u32 %0, %1, 32, 32;" : "=r"(tm) : "r"(epoch));
            int ok = (int)(f.x - tm) < 0 ? 0 : (int)(f.y - tm) < 0 ? 1 : (int)(f.z - tm) < 0 ? 2 : (int)(f.w - tm) < 0 ? 3 : 4;
            if (it > (1u << 23)) ok = 4;
            if (ok > c) {
              asm volatile("fence.acquire.gpu;" ::: "memory"); fence_async_gmem();
              if (c == 0) bulk_g2s(sb + (POS_M & 15) * 32768, g_M, 8192, sb + B_M0);
            }
#pragma unroll 1
            for (; c < ok; c++) {
              const uint32_t skip = c == 0 ? 8192 : 0;
              bulk_g2s(sb + ((POS_M >> c * 4) & 15) * 32768 + skip, pofs<const uint8_t>(g_M, c * WCH_B + skip), WCH_B - skip, sb + B_WF + 8 * c);
              STAMP(c == 0, 2, 2);
            }
          }
        }
        asm volatile("st.shared.u32 [%0], %1;" :: "r"(sb + SM_EPOCH), "r"(epoch) : "memory");
        if (total > 0) mbar_expect_tx(sb + B_WF + 24, WCH_B);
        int st = 0, ph = 0, qph = 0;
        const int nsl = tail ? 3 : 2;
        auto next_slot = [&]() { mbar_wait(sb + B_EMPTY + 8 * st, ph); if (++st == nsl) { st = 0; ph ^= 1; } };
        const uint4* wsrc = fin ? g_Wvo : g_Wmo;
        auto w_load = [&](int c0, int c1) {
#pragma unroll 1
          for (int c = c0; c < c1; c++) {
            mbar_expect_tx(sb + B_WF + 8 * c, WCH_B);
            bulk_g2s(sb + ((posw >> c * 4) & 15) * 32768, pofs<const uint8_t>(wsrc, c * WCH_B), WCH_B, sb + B_WF + 8 * c);
          }
        };
        auto q_load = [&](const uint4* src, bool wait_empty) {
#pragma unroll 1
          for (int h = 0; h < 2; h++) {
            if (wait_empty) mbar_wait(sb + B_QEMPTY + 8 * h, qph);
            mbar_expect_tx(sb + B_QFULL + 8 * h, 32768);
            bulk_g2s_last(sb + SM_Q + h * 32768, src + h * 2048, 32768, sb + B_QFULL + 8 * h);
          }
          if (wait_empty) qph ^= 1;
        };
        auto part_out = [&](int slot, int h, uint32_t region, int parity) {
          mbar_wait(sb + B_EVP0 + 8 * h, parity);
          fence_async_smem();
          bulk_s2g(g_part + slot * 4096 + h * 2048, sb + region * 32768, 32768);
          bulk_s2g(g_ml + slot * 128 + h * 64, sb + SM_ML + h * 512, 512);
          bulk_commit();
        };
        auto announce = [&](int f) {
          red_relaxed(g_flag + f);
        };
        if (total > 0) {
          STAMP(true, 2, 3);
          const int q1 = W.q0 + 2 * W.own - 3;
          if (!tail) { flag_wait(F_H1 + (fin ? 0 : W.own), (epoch + 1) * (fin ? NH1_0 : (W.own == 1 ? NH1_1 : NH1_2))); fence_async_gmem(); }
          STAMP(true, 2, 4);
          uint32_t ko = W.k0 * 8192;
#pragma unroll 1
          for (int j = 0; j < total; j++) {
            if (j == (tail ? 0 : 1)) { flag_wait(F_H, (epoch + 1) * NHSIG); fence_async_gmem(); }
            if (j == n0) {
              flag_wait(F_QP + q1 * LN_, (epoch + 1)); fence_async_gmem();
              const uint32_t u = __ldcg(g_unsafe + q1);
              asm volatile("st.shared.u32 [%0], %1;" :: "r"(sb + SM_UNSAFE), "r"(u) : "memory");
              ko = W.k1 * 8192;
            }
            if (j == n0 + 1) q_load(g_qp + q1 * 4096, true);
            if (j == total - 1) { flag_wait(F_W, (epoch + 1)); fence_async_gmem(); if (!tail) w_load(0, 1); }
            const uint32_t bytes = (j < n0 ? j < W.nb0 : j - n0 < W.nb1) ? 112 * 512 : 128 * 512, s0 = st;
            const uint32_t region = (tail ? 1 : 2) + 2 * s0, skip = j == n0 + 1 ? 32768 : 0;
            if (skip) part_out(W.slotA, 0, 6, 0);
            next_slot();
            mbar_expect_tx(sb + B_FULL + 8 * s0, bytes);
            bulk_g2s(sb + region * 32768 + skip, pofs<const uint8_t>(g_h, ko + skip), bytes - skip, sb + B_FULL + 8 * s0);
            if (skip) {
              part_out(W.slotA, 1, region, 0);
              bulk_wait_read();
              bulk_g2s(sb + region * 32768, pofs<const uint8_t>(g_h, ko), skip, sb + B_FULL + 8 * s0);
              bulk_wait_all();
              announce(F_PART + W.slotA * LN_);
            }
            ko += bytes;
          }
          next_slot();
          if (tail) { next_slot(); next_slot(); }
        } else { flag_wait(F_W, (epoch + 1)); fence_async_gmem(); }
        STAMP(true, 2, 5);
        const bool staged = total > 0 && !tail;
        w_load(staged, staged ? (fin ? 2 : 3) : 4);
        if (tail) {
          mbar_wait(sb + B_BG, 0); mbar_wait(sb + B_EVP0 + 8, 0); mbar_arrive(sb + B_QFULL);
          qph = 1; wsrc = g_Wmo;
          mbar_wait(sb + B_QEMPTY, 1);
          w_load(0, 4);
        }
#pragma unroll 1
        for (int i = 0; i < W.nloc; i++) {
          const int tl = W.loc0 + i, last = tl * 128 + 127 < NN ? tl * 128 + 127 : NN - 1;
          flag_wait(F_AGG + ((last >= NGW) + (last >= 4 * NGW) + (last >= 9 * NGW)) * LN_, (epoch + 1) * NGW); fence_async_gmem();
          if (total == 0) g_flag[F_EPOCH] = epoch + 1;
          q_load(g_agg + tl * 4096, total > 0 || i > 0);
        }
        if (fin && !tail) {
          int h = 0, c = 2, have = W.slotB >= 0 ? 2 : 0;
          mbar_wait(sb + B_BG, 0);
#pragma unroll 1
          for (uint32_t it = 0; (h < 2 || c < 4) && it < (1u << 23); it++) {
            if (have < 2) {
              uint2 f;
              asm volatile("ld.relaxed.gpu.global.v2.u32 {%0,%1}, [%2];" : "=r"(f.x), "=r"(f.y) : "l"(g_flag + F_PART + W.slotA * LN_) : "memory");
              have = (int)(f.x - (epoch + 1)) < 0 ? 0 : ((int)(f.y - (epoch + 1)) < 0 ? 1 : 2);
            }
            if (h < have && mbar_try_wait_nb(sb + B_QEMPTY + 8 * h, 0)) {
              asm volatile("fence.acquire.gpu;" ::: "memory"); fence_async_gmem();
              STAMP(true, 2, 14 + h);
              mbar_expect_tx(sb + B_QFULL + 8 * h, 32768 + 512);
              bulk_g2s(sb + SM_ML + h * 512, g_ml + W.slotA * 128 + h * 64, 512, sb + B_QFULL + 8 * h);
              bulk_g2s(sb + SM_Q + h * 32768, g_part + W.slotA * 4096 + h * 2048, 32768, sb + B_QFULL + 8 * h);
              h++;
            }
            const bool half = mbar_try_wait_nb(sb + B_HALF, 0);
            const int c1 = half ? 4 : (h > 0 ? 3 : 2);
            if (c < c1) { w_load(c, c1); c = c1; }
          }
        } else if (!fin && total > 0) {
#pragma unroll 1
          for (int h = 0; h < 2; h++) part_out(W.slotB, h, (posw >> 12) + h, 1);
          asm volatile("cp.async.bulk.wait_group.read 1;" ::: "memory");
          w_load(3, 4);
          asm volatile("cp.async.bulk.wait_group 1;" ::: "memory");
          announce(F_PART + W.slotB * LN_);
          STAMP(true, 2, 14);
          bulk_wait_all();
          announce(F_PART + W.slotB * LN_ + 1);
          STAMP(true, 2, 15);
        }
        DUMP(true, 2, 14, 16);
        DUMP(true, 2, 0, 8);
      }
      return;
    }
  }
    {
      const int gw = cta * 3 + warp - 1;
      ROLE;
      if (total > 0) {
        mbar_wait_w(sb + B_EVQ, 0);
        const uint32_t c0 = clk();
        if (warp == 1 && (W.role & R_PUB)) {
          g_unsafe[W.q0] = lds32(sb + SM_UNSAFE);
#pragma unroll 1
          for (int k = 0; k < 4; k++) {
            __nanosleep(2000);
            if (lane == 0) bulk_s2g(pofs<uint4>(g_qp, W.q0 * 65536 + k * 16384), sb + SM_Q + k * 16384, 16384);
            bulk_commit();
          }
          bulk_wait_all();
          flag_release_w(F_QP + W.q0 * LN_);
        }
        while (__any_sync(0xffffffffu, clk() - c0 < GSTART)) __nanosleep(500);
        STAMP(lane == 0 && warp == 1, 2, 8);
#define ovf_cnt pofs<uint32_t>(g_flag, (F_OVF + (ep1 & 1) * LN_) * 4)
        if (gw == 0) g_flag[F_OVF + ((ep1 + 1) & 1) * LN_] = 0;
#pragma unroll 1
        for (int e0 = gw * 32; e0 < NE; e0 += NGW * 32 * 7) {
          int d[7], s[7], pos[7];
          const int* pd = pofs<const int>(P.dst, (e0 + lane) * 4);
          const int* ps = pofs<const int>(P.src, (e0 + lane) * 4);
#pragma unroll
          for (int k = 0; k < 7; k++) { const bool ok = e0 + k * NGW * 32 < NE; d[k] = ok ? __ldcs(pd + k * NGW * 32) : -1; s[k] = ok ? __ldcs(ps + k * NGW * 32) : 0; }
          uint32_t ov = 0;
#pragma unroll
          for (int k = 0; k < 7; k++) {
            pos[k] = 0;
            if (d[k] >= 0) asm volatile("atom.relaxed.gpu.global.add.u32 %0, [%1], 1;" : "=r"(pos[k]) : "l"(pofs<int>(g_cnt, d[k] << 2)) : "memory");
            s[k] = (uint32_t)(uintptr_t)g_u + s[k] * 512;
            if (d[k] >= 0 && pos[k] < CAP) asm volatile("st.volatile.global.u32 [%0], %1;" :: "l"(pofs<int>(g_bin, (d[k] * CAPS + pos[k]) << 2)), "r"(s[k]) : "memory");
            ov |= (pos[k] >= CAP) << k;
          }
          if (__any_sync(0xffffffffu, ov != 0)) {
            uint32_t at;
            asm volatile("atom.relaxed.gpu.global.add.u32 %0, [%1], %2;" : "=r"(at) : "l"(ovf_cnt), "r"(__popc(ov)) : "memory");
#pragma unroll
            for (int k = 0; k < 7; k++) if ((ov >> k) & 1) g_ovf[at++] = make_int2(d[k], s[k]);
          }
        }
        flag_wait_w(F_H, ep1 * NHSIG);
#pragma unroll 1
        for (int n0 = gw; n0 < NN; n0 += 4 * NGW) {
          uint4 xv[4]; float2 st[4];
#pragma unroll
          for (int k = 0; k < 4; k++) {
            const int n = n0 + k * NGW < NN ? n0 + k * NGW : n0;
            xv[k] = ldcs_v(pofs<const uint4>(P.x, n * 512 + lane * 16));
            st[k] = __ldcg(pofs<const float2>(g_stat, n * 8));
          }
#pragma unroll
          for (int k = 3; k >= 0; k--) {
            const int n = n0 + k * NGW;
            const float a = st[k].x * US, c = fmaf(st[k].y, US, UB + 8388608.0f);
#define FIX(w) __byte_perm(__float_as_uint(fmaf(bf_lo(w), a, c)), __float_as_uint(fmaf(bf_hi(w), a, c)), 0x5410)
            if (n < NN) {
              *pofs<uint4>(P.out, n * 512 + lane * 16) = xv[k];
              *pofs<uint4>(g_u, n * 512 + lane * 16) = make_uint4(FIX(xv[k].x), FIX(xv[k].y), FIX(xv[k].z), FIX(xv[k].w));
            }
          }
        }
        flag_release_w(F_BIN);
        STAMP(lane == 0 && warp == 1, 2, 9);
        flag_wait_w(F_BIN, ep1 * NGW);
        STAMP(lane == 0 && warp == 1, 2, 10);
        const int myn = gw + lane * NGW < NN ? gw + lane * NGW : gw;
        int cnts = __ldcg(g_cnt + myn);
        cnts = gw + lane * NGW < NN ? (cnts > CAP ? CAP + 1 : cnts) | ((int)__ldg((const unsigned short*)P.dinv + myn) << 16) : 0;
        __syncwarp();
        g_cnt[myn] = 0;
        const uint32_t uhi = (uintptr_t)g_u >> 32, lx = lane * 16;
        uint32_t obin = gw * CAPS * 4;
        uint32_t ent = __ldcg(pofs<const uint32_t>(g_bin, obin + lane * 4)), entn = __ldcg(pofs<const uint32_t>(g_bin, obin + NGW * CAPS * 4 + lane * 4));
        int cd = __shfl_sync(0xffffffffu, cnts, 0), cb = min(cd & 0xffff, CAP), e = 0;
        uint32_t sa[4] = {0, 0, 0, 0}, sh[4] = {0, 0, 0, 0};
        auto add = [&](uint32_t x, uint32_t y, uint32_t z, uint32_t w) {
          sa[0] += x; sa[1] += y; sa[2] += z; sa[3] += w;
          sh[0] += x >> 16; sh[1] += y >> 16; sh[2] += z >> 16; sh[3] += w >> 16;
        };
        int rnd = -1, rows = -1, cdo = 0;
#pragma unroll 1
        for (;;) {
          const bool hold = rows >= 0 && rnd == 8;
          const int m = hold ? 0 : cb - e;
          uint4 v[8];
          if (m >= 8) {
#pragma unroll
            for (int k = 0; k < 8; k++) v[k] = ldcg_v(addr64(__shfl_sync(0xffffffffu, ent, k) + lx, uhi));
          } else {
#pragma unroll
            for (int k = 0; k < 8; k++) {
              v[k] = make_uint4(0, 0, 0, 0);
              if (k < 7) ldcg_if(v[k], addr64(__shfl_sync(0xffffffffu, ent, k) + lx, uhi), k < m);
            }
          }
          if (rows >= 0) {
            const int n = gw + rnd * NGW;
            if (n < NN) {
              const float di = __uint_as_float(cdo & 0xffff0000u) * (1.0f / US), nl = -di * UB * (float)rows;
#define AGG(k) pack_bf16(fmaf((float)(sa[k] - (sh[k] << 16)), di, nl), fmaf((float)sh[k], di, nl))
              *pofs<uint4>(g_agg, ((n >> 3) * 4096 + (n & 7) * 144) ^ ((lx & 0x70) | ((lx & 0x180) << 3))) = make_uint4(AGG(0), AGG(1), AGG(2), AGG(3));
            }
#pragma unroll
            for (int k = 0; k < 4; k++) sa[k] = sh[k] = 0;
            rows = -1;
            if (rnd == 0 || rnd == 3 || rnd == 8 || rnd == NRND - 1) flag_release_w(F_AGG + ((rnd > 0) + (rnd > 3) + (rnd > 8)) * LN_);
            if (rnd == NRND - 1) break;
            if (hold) {
              if (fin && W.slotB >= 0) {
        #pragma unroll 1
                for (int k = 0; k < 2; k++) flag_wait_w(F_PART + (k ? W.slotB : W.slotA) * LN_, ep1);
        #pragma unroll 1
                for (int b = warp - 1; b < 8; b += 3) {
                  float2* ma = g_ml + W.slotA * 128 + b * 16 + g;
                  const float2* mb = g_ml + W.slotB * 128 + b * 16 + g;
                  const float2 a0 = __ldcg(ma), a1 = __ldcg(ma + 8), b0 = __ldcg(mb), b1 = __ldcg(mb + 8);
                  const float x0 = fmaxf(a0.x, b0.x), x1 = fmaxf(a1.x, b1.x);
                  const float fa0 = ex2(a0.x - x0), fa1 = ex2(a1.x - x1), fb0 = ex2(b0.x - x0), fb1 = ex2(b1.x - x1);
                  __syncwarp();
                  if (t == 0) { ma[0] = make_float2(x0, a0.y * fa0 + b0.y * fb0); ma[8] = make_float2(x1, a1.y * fa1 + b1.y * fb1); }
                  const uint32_t ofs = ((b >> 2) * 2048 + (b & 3) * 32 + lane) * 16;
        #pragma unroll 1
                  for (int u = 0; u < 16; u += 4) {
                    uint4* pa = pofs<uint4>(g_part, W.slotA * 65536 + ofs + u * 2048);
                    const uint4* pb = pofs<const uint4>(g_part, W.slotB * 65536 + ofs + u * 2048);
                    uint4 va[4], vb[4];
        #pragma unroll
                    for (int k = 0; k < 4; k++) { va[k] = ldcg_v(pa + k * 128); vb[k] = ldcs_v(pb + k * 128); }
        #define FOLD(w, fa, fb) pack_bf16(bf_lo(va[k].w) * fa + bf_lo(vb[k].w) * fb, bf_hi(va[k].w) * fa + bf_hi(vb[k].w) * fb)
        #pragma unroll
                    for (int k = 3; k >= 0; k--) pa[k * 128] = make_uint4(FOLD(x, fa0, fb0), FOLD(y, fa1, fb1), FOLD(z, fa0, fb0), FOLD(w, fa1, fb1));
                  }
                }
                bar_sync(3, 96);
                if (warp == 1) asm volatile("fence.acq_rel.gpu;" ::: "memory");
              }
              if (fin && warp == 1 && lane == 0) mbar_arrive(sb + B_BG);
              while (__any_sync(0xffffffffu, clk() - c0 < GPAUSE)) __nanosleep(500);
              continue;
            }
          }
#define SUM8(f) (v[7].f + v[6].f + v[5].f + v[4].f + v[3].f + v[2].f + v[1].f + v[0].f)
          add(SUM8(x), SUM8(y), SUM8(z), SUM8(w));
          e += 8;
          if (e < cb) {
            ent = __shfl_down_sync(0xffffffffu, ent, 8);
            if (e == 32) ent = __ldcg(pofs<const uint32_t>(g_bin, obin + 128 + lx / 4));
            continue;
          }
          rnd++; rows = cb; cdo = cd;
          if ((cd & 0xffff) > CAP) {
            const int no = __shfl_sync(0xffffffffu, (int)ld_relaxed(ovf_cnt), 0);
#pragma unroll 1
            for (int i0 = 0; i0 < no; i0 += 32) {
              int2 en = __ldcg(g_ovf + min(i0 + lane, no - 1));
              uint32_t mk = __ballot_sync(0xffffffffu, en.x == gw + rnd * NGW && i0 + lane < no);
              rows += __popc(mk);
#pragma unroll 1
              while (mk) {
                const int bit = __ffs(mk) - 1; mk &= mk - 1;
                const uint4 r = ldcg_v(addr64((uint32_t)__shfl_sync(0xffffffffu, en.y, bit) + lx, uhi));
                add(r.x, r.y, r.z, r.w);
              }
            }
          }
          obin += NGW * CAPS * 4;
          ent = entn; entn = __ldcg(pofs<const uint32_t>(g_bin, obin + NGW * CAPS * 4 + lx / 4));
          cd = __shfl_sync(0xffffffffu, cnts, rnd + 1); cb = min(cd & 0xffff, CAP); e = 0;
        }
      }
      STAMP(lane == 0 && warp == 1, 2, 11);
      if (warp == 2 && fin && lane == 0) {
        prefetch_l2(pofs<uint8_t>(P.out, W.q0 * 65536), tail ? 8192 : 65536);
        if (W.slotB >= 0) prefetch_l2(pofs<uint8_t>(g_part, W.slotA * 65536), 65536);
        prefetch_l2(pofs<uint8_t>(g_Wvo, (cta & 63) * 4096), 4096);
      }
      DUMP(warp == 1 && lane == 0, 2, 8, 14);
    }
}

}

extern "C" void kernel_launch(void* const* d_in, const int* in_sizes, int n_in, void* d_out, int out_size) {
  Params P;
  P.x = (const __nv_bfloat16*)d_in[0];
  P.src = (const int*)d_in[1];
  P.dst = (const int*)d_in[2];
  P.dinv = (const __nv_bfloat16*)d_in[3];
  P.wmsg = (const __nv_bfloat16*)d_in[4];
  P.wq = (const __nv_bfloat16*)d_in[5];
  P.wk = (const __nv_bfloat16*)d_in[6];
  P.wv = (const __nv_bfloat16*)d_in[7];
  P.wout = (const __nv_bfloat16*)d_in[8];
  P.out = (__nv_bfloat16*)d_out;
  P.zero = 0;
  for (int c = 0; c < NCTA; c++) P.w[c] = make_work(c);
  static void* scr = nullptr;
  if (!scr) {
    cudaFuncSetAttribute(gps_kernel, cudaFuncAttributeMaxDynamicSharedMemorySize, SMEM_BYTES);
    cudaGetSymbolAddress(&scr, g_scr);
  }
  P.s = (Scratch*)((((uintptr_t)scr + SCR_ALIGN - 1) & ~(uintptr_t)(SCR_ALIGN - 1)) + SCR_OFS);
  P.u = (uint4*)(((uintptr_t)P.s->u + 511) & ~(uintptr_t)511);
  if (((uintptr_t)P.u >> 32) != (((uintptr_t)(P.u + NN * 32) - 1) >> 32)) P.u += NN * 32;
  gps_kernel<<<NCTA, 384, SMEM_BYTES>>>(P);
}
```

```cpp
#include <cuda_runtime.h>
#include <cuda_bf16.h>
#include <stdint.h>
#include <stddef.h>
#include <type_traits>
#define FB 5
#define MB 5
#define GSTART 40000
#define XD 2
#define NTAIL 5
#define PACE 64
#define GPAUSE 112000
#define XDELAY 200
#define CREG 224
#define BACKOFF 1000

namespace {

constexpr int NN = 10000;
constexpr int NE = 160000;
constexpr int NQT = 79;
constexpr int NCTA = 132;
constexpr int CAP = 64;
constexpr int CAPS = 64;
constexpr int NHSIG = 105;
constexpr uint32_t WCH_B = 32768;
constexpr int NGW = (NCTA - 1) * 3;
constexpr float TAU = 16.0f;
constexpr float SAFE_N2 = 36.0f, SAFE_C = 0.6f;
#define KOFF 3
#define PSH -8.0f
#define KROT 15
constexpr float US = 256.0f, UB = 4095.0f;
constexpr float KS = 0.25f, KC = KOFF * KS;
constexpr uint32_t KS2 = 0x3e803e80u, KC2 = KOFF == 2 ? 0x3f003f00u : (KOFF == 1 ? 0x3e803e80u : 0x3f403f40u);

constexpr int NAGG = 4;
constexpr int NRND = (NN + NGW - 1) / NGW;
constexpr int NSLOT = 105;
constexpr int F_EPOCH = 0, F_H = 1, F_M = 4  , F_H1 = 8  , LN_ = 32;
constexpr int F_BIN = LN_, F_W = 2 * LN_, F_OVF = 3 * LN_  , F_QP = 5 * LN_, F_AGG = F_QP + NQT * LN_,
              F_PART = F_AGG + NAGG * LN_, F_END = F_PART + NSLOT * LN_;

struct Scratch {
  uint32_t flag[F_END];
  alignas(4096) uint4 M[8192];
  uint4 Wvo[8192], Wmo[8192];
  float2 ml[NSLOT * 128];
  uint32_t unsafe[96];
  int cnt[NN + 32];
  float2 stat[NQT * 128];
  alignas(4096) uint4 h[NQT * 4096];
  uint4 u[2 * NN * 32 + 32];
  uint4 qp[NQT * 4096];
  uint4 agg[NQT * 4096];
  uint4 part[NSLOT * 4096];
  int bin[(NRND + 2) * NGW * CAPS];
  int2 ovf[NE];
};
static_assert(offsetof(Scratch, h) % 128 == 0, "alignment");
#define SCR_ALIGN (2u << 20)
#define SCR_OFS 0
__device__ uint4 g_scr[(sizeof(Scratch) + SCR_ALIGN + SCR_OFS) / 16];
struct alignas(16) Work { short k0, k1; signed char q0, hp, nb0, na0, nb1, na1, slotA, slotB, loc0, nloc, own, role; };
constexpr int R_FIN = 1, R_PUB = 2, R_TAIL = 4, R_SIG = 8  ;
struct Params {
  const __nv_bfloat16 *x, *wq, *wk;
  Scratch* s;
  uint4* u;
  __nv_bfloat16* out;
  const __nv_bfloat16 *wout, *wmsg, *wv, *dinv;
  const int *src, *dst;
  long long zero;
  Work w[NCTA];
};
constexpr int first_cnt(int k) { return 2 * ((k + 6) / 8 - k / 8 + 1); }
constexpr int NH1_0 = 2, NH1_1 = first_cnt(48 * 8 - MB), NH1_2 = first_cnt(48 * 8 - MB + 16 * 8 - (15 - MB) / 2);
constexpr int NSERV = NQT - 52;
inline Work make_work(int c) {
  Work w;
  const int gi = c / 5, r = c % 5, q = gi * 3;
  const bool helper = r & 1, mid = r == 2;
  w.q0 = helper ? q + 1 : q + (r >> 1);
  const int hb1 = (15 - MB) / 2, hb3 = 15 - MB - hb1;
  w.nb0 = helper ? (r == 1 ? hb1 : hb3) : (mid ? MB : FB);
  w.na0 = (helper ? 16 : 48) - w.nb0;
  w.k0 = helper ? (48 * 8 - MB) + (r >> 1) * (16 * 8 - hb1) : 0;
  w.k1 = 48 * 8 - FB;
  w.nb1 = helper ? (FB < 7 ? 7 : 15) - FB : 0;
  w.na1 = helper ? (FB < 7 ? 31 : 32) - w.nb1 : 0;
  w.slotA = 4 * gi + (helper ? r - 1 : (mid ? 0 : (r >> 1) + 1));
  w.slotB = helper ? 4 * gi + r : (mid ? 4 * gi + 2 : -1);
  w.loc0 = NSERV + gi * 2 + (r >> 1);
  w.nloc = helper;
  w.own = helper ? (r + 1) >> 1 : (mid ? 0 : 3);
  w.role = helper ? 0 : (mid ? R_FIN : R_FIN | R_PUB);
  const int k1st[3] = {0, 48 * 8 - MB, 48 * 8 - MB + 16 * 8 - hb1};
  int pos[NQT], sig[NQT];
  for (int i = 0; i < NQT; i++) { pos[i] = i; sig[i] = 0; }
  for (int i = 0; i < 3; i++)
    for (int p = k1st[i] / 8; p <= (k1st[i] + 6) / 8; p++) {
      int m = 1, at = 0;
      while (sig[m]) m += 3;
      while (pos[at] != p) at++;
      pos[at] = pos[m]; pos[m] = p; sig[m] = 1 + i;
    }
  w.hp = c < 131 ? pos[w.q0] : 0;
  if (helper && c < 130) w.role |= sig[w.q0] * R_SIG;
  if (c == 130) { w.nb0 = 15; w.na0 = 65; w.slotA = NSLOT - 1; w.own = 1; w.role = R_FIN | R_TAIL; w.loc0 = NSERV - NTAIL; w.nloc = NTAIL; }
  if (c == 131) { w.nb0 = w.na0 = w.nb1 = w.na1 = 0; w.loc0 = 0; w.nloc = NSERV - NTAIL; w.own = 0; }
  return w;
}
#define g_flag P.s->flag
#define g_M P.s->M
#define g_Wvo P.s->Wvo
#define g_Wmo P.s->Wmo
#define g_ml P.s->ml
#define g_unsafe P.s->unsafe
#define g_cnt P.s->cnt
#define g_h P.s->h
#define g_u P.u
#define g_stat P.s->stat
#define g_qp P.s->qp
#define g_agg P.s->agg
#define g_part P.s->part
#define g_bin P.s->bin
#define g_ovf P.s->ovf

__device__ __forceinline__ uint32_t smem_u32(const void* p) { return (uint32_t)__cvta_generic_to_shared(p); }
__device__ __forceinline__ void mbar_init(uint32_t bar, uint32_t cnt) { asm volatile("mbarrier.init.shared::cta.b64 [%0], %1;" :: "r"(bar), "r"(cnt) : "memory"); }
__device__ __forceinline__ void mbar_arrive(uint32_t bar) { asm volatile("mbarrier.arrive.shared::cta.b64 _, [%0];" :: "r"(bar) : "memory"); }
__device__ __forceinline__ void mbar_expect_tx(uint32_t bar, uint32_t bytes) { asm volatile("mbarrier.arrive.expect_tx.shared::cta.b64 _, [%0], %1;" :: "r"(bar), "r"(bytes) : "memory"); }
__device__ __forceinline__ bool mbar_try_wait(uint32_t bar, uint32_t parity) {
  uint32_t ok;
  asm volatile("{\n.reg .pred p;\nmbarrier.try_wait.parity.shared::cta.b64 p, [%1], %2;\nselp.b32 %0, 1, 0, p;\n}\n" : "=r"(ok) : "r"(bar), "r"(parity) : "memory");
  return ok;
}
__device__ __forceinline__ bool mbar_try_wait_nb(uint32_t bar, uint32_t parity) {
  uint32_t ok;
  asm volatile("{\n.reg .pred p;\nmbarrier.test_wait.parity.shared::cta.b64 p, [%1], %2;\nselp.b32 %0, 1, 0, p;\n}\n" : "=r"(ok) : "r"(bar), "r"(parity) : "memory");
  return ok;
}
__device__ __forceinline__ void mbar_wait(uint32_t bar, uint32_t parity) {
#pragma unroll 1
  for (uint32_t it = 0; it < (1u << 25); it++) if (mbar_try_wait(bar, parity)) break;
}
__device__ __forceinline__ void bulk_s2g(void* dst, uint32_t src, uint32_t bytes) {
  asm volatile("cp.async.bulk.global.shared::cta.bulk_group [%0], [%1], %2;" :: "l"(dst), "r"(src), "r"(bytes) : "memory");
}
__device__ __forceinline__ void bulk_commit() { asm volatile("cp.async.bulk.commit_group;" ::: "memory"); }
__device__ __forceinline__ void bulk_wait_read() { asm volatile("cp.async.bulk.wait_group.read 0;" ::: "memory"); }
__device__ __forceinline__ void bulk_wait_all() { asm volatile("cp.async.bulk.wait_group 0;" ::: "memory"); }
__device__ __forceinline__ bool bar_red_or(int id, int cnt, bool c) {
  uint32_t r;
  asm volatile("{\n.reg .pred p, q;\nsetp.ne.b32 q, %3, 0;\nbar.red.or.pred p, %1, %2, q;\nselp.b32 %0, 1, 0, p;\n}\n"
               : "=r"(r) : "r"(id), "r"(cnt), "r"((uint32_t)c) : "memory");
  return r != 0;
}
template <class T> __device__ __forceinline__ T* pofs(const void* base, uint32_t off) {
  asm volatile("" : "+r"(off));
  return (T*)((uint8_t*)base + off);
}
__device__ __forceinline__ const void* addr64(uint32_t lo, uint32_t hi) { uint64_t a; asm("mov.b64 %0, {%1, %2};" : "=l"(a) : "r"(lo), "r"(hi)); return (const void*)a; }
__device__ __forceinline__ uint4 ldcg_v(const void* a) {
  uint4 v;
  asm volatile("ld.volatile.global.v4.u32 {%0,%1,%2,%3}, [%4];" : "=r"(v.x), "=r"(v.y), "=r"(v.z), "=r"(v.w) : "l"(a) : "memory");
  return v;
}
__device__ __forceinline__ uint4 ldcs_v(const void* a) {
  uint4 v;
  asm volatile("ld.global.cs.v4.u32 {%0,%1,%2,%3}, [%4];" : "=r"(v.x), "=r"(v.y), "=r"(v.z), "=r"(v.w) : "l"(a) : "memory");
  return v;
}
__device__ __forceinline__ void prefetch_l2(const void* a, uint32_t bytes) { asm volatile("cp.async.bulk.prefetch.L2.global [%0], %1;" :: "l"(a), "r"(bytes) : "memory"); }
__device__ __forceinline__ void ldcg_if(uint4& v, const void* a, bool c) {
  asm volatile("{\n.reg .pred p;\nsetp.ne.b32 p, %5, 0;\n@p ld.volatile.global.v4.u32 {%0,%1,%2,%3}, [%4];\n}\n"
               : "+r"(v.x), "+r"(v.y), "+r"(v.z), "+r"(v.w) : "l"(a), "r"((uint32_t)c) : "memory");
}
__device__ __forceinline__ void cp_async16(uint32_t dst, const void* src) {
  asm volatile("cp.async.cg.shared.global [%0], [%1], 16;" :: "r"(dst), "l"(src) : "memory");
}
__device__ __forceinline__ void red_bf16x8(void* a, uint4 v) {
  asm volatile("red.global.add.noftz.v4.bf16x2 [%0], {%1,%2,%3,%4};" :: "l"(a), "r"(v.x), "r"(v.y), "r"(v.z), "r"(v.w) : "memory");
}
__device__ __forceinline__ uint32_t clk() { uint32_t c; asm volatile("mov.u32 %0, %%clock;" : "=r"(c) :: "memory"); return c; }
__device__ __forceinline__ void stsm4(uint32_t a, uint32_t r0, uint32_t r1, uint32_t r2, uint32_t r3) {
  asm volatile("stmatrix.sync.aligned.m8n8.x4.shared.b16 [%0], {%1,%2,%3,%4};" :: "r"(a), "r"(r0), "r"(r1), "r"(r2), "r"(r3) : "memory");
}
__device__ __forceinline__ void ldsm4(uint32_t a, uint32_t& r0, uint32_t& r1, uint32_t& r2, uint32_t& r3) {
  asm volatile("ldmatrix.sync.aligned.m8n8.x4.shared.b16 {%0,%1,%2,%3}, [%4];" : "=r"(r0), "=r"(r1), "=r"(r2), "=r"(r3) : "r"(a) : "memory");
}
__device__ __forceinline__ void red_relaxed(uint32_t* p) { asm volatile("red.relaxed.gpu.global.add.u32 [%0], 1;" :: "l"(p) : "memory"); }
__device__ __forceinline__ uint32_t lds32(uint32_t a) { uint32_t v; asm volatile("ld.shared.u32 %0, [%1];" : "=r"(v) : "r"(a) : "memory"); return v; }
__device__ __forceinline__ void cp_commit() { asm volatile("cp.async.commit_group;" ::: "memory"); }
__device__ __forceinline__ uint32_t hmul2(uint32_t a, uint32_t b) { uint32_t d; asm("mul.rn.bf16x2 %0, %1, %2;" : "=r"(d) : "r"(a), "r"(b)); return d; }
__device__ __forceinline__ uint32_t hfma2(uint32_t a, uint32_t b, uint32_t c) { uint32_t d; asm("fma.rn.bf16x2 %0, %1, %2, %3;" : "=r"(d) : "r"(a), "r"(b), "r"(c)); return d; }
__device__ __forceinline__ uint32_t pow2_bf2(int n) { return (uint32_t)max(n + 127, 0) * 0x00800080u; }
__device__ __forceinline__ int fexp(float x) { return (int)(__float_as_uint(x) >> 23) - 127; }
__device__ __forceinline__ void bulk_g2s(uint32_t dst, const void* src, uint32_t bytes, uint32_t bar) {
  asm volatile("cp.async.bulk.shared::cta.global.mbarrier::complete_tx::bytes [%0], [%1], %2, [%3];"
    :: "r"(dst), "l"(src), "r"(bytes), "r"(bar) : "memory");
}
__device__ __forceinline__ void bulk_g2s_last(uint32_t dst, const void* src, uint32_t bytes, uint32_t bar) {
  asm volatile("{\n.reg .b64 p;\ncreatepolicy.fractional.L2::evict_first.b64 p;\n"
    "cp.async.bulk.shared::cta.global.mbarrier::complete_tx::bytes.L2::cache_hint [%0], [%1], %2, [%3], p;\n}\n"
    :: "r"(dst), "l"(src), "r"(bytes), "r"(bar) : "memory");
}
__device__ __forceinline__ void wg_fence() { asm volatile("wgmma.fence.sync.aligned;" ::: "memory"); }
__device__ __forceinline__ void wg_commit() { asm volatile("wgmma.commit_group.sync.aligned;" ::: "memory"); }
template<int N> __device__ __forceinline__ void wg_wait() { asm volatile("wgmma.wait_group.sync.aligned %0;" :: "n"(N) : "memory"); }
__device__ __forceinline__ void bar_sync(int id, int cnt) { asm volatile("bar.sync %0, %1;" :: "r"(id), "r"(cnt) : "memory"); }
__device__ __forceinline__ void fence_async_smem() { asm volatile("fence.proxy.async.shared::cta;" ::: "memory"); }
__device__ __forceinline__ void fence_async_gmem() { asm volatile("fence.proxy.async.global;" ::: "memory"); }
__device__ __forceinline__ void bar_arrive(int id, int cnt) { asm volatile("bar.arrive %0, %1;" :: "r"(id), "r"(cnt) : "memory"); }
__device__ __forceinline__ void red_release(uint32_t* p) { asm volatile("red.release.gpu.global.add.u32 [%0], 1;" :: "l"(p) : "memory"); }
__device__ __forceinline__ void red_release_w(uint32_t* p) {
  __syncwarp();
  asm volatile("{\n.reg .pred q;\n.reg .b32 l;\nmov.u32 l, %%laneid;\nsetp.eq.u32 q, l, 0;\n@q fence.release.gpu;\n@q red.relaxed.gpu.global.add.u32 [%0], 1;\n}\n" :: "l"(p) : "memory");
}
__device__ __forceinline__ void mbar_wait_w(uint32_t bar, uint32_t parity) {
#pragma unroll 1
  for (uint32_t it = 0; it < (1u << 25); it++) if (__all_sync(0xffffffffu, mbar_try_wait(bar, parity))) break;
}
#define flag_release_w(f) red_release_w(g_flag + (f))
#define flag_wait_w(f, target) poll_acquire_w(g_flag + (f), target)
#define flag_release(f) red_release(g_flag + (f))
__device__ __forceinline__ uint32_t ld_relaxed(const uint32_t* p) {
  uint32_t v; asm volatile("ld.relaxed.gpu.global.u32 %0, [%1];" : "=r"(v) : "l"(p) : "memory"); return v;
}
#define flag_wait(f, target) poll_acquire(g_flag + (f), target)
__device__ __forceinline__ void poll_acquire(const uint32_t* p, uint32_t target) {
#pragma unroll 1
  for (uint32_t it = 0; it < (1u << 23); it++) if ((int)(ld_relaxed(p) - target) >= 0) break;
  asm volatile("fence.acquire.gpu;" ::: "memory");
}
__device__ __forceinline__ void poll_acquire_w(const uint32_t* p, uint32_t target) {
#pragma unroll 1
  for (uint32_t it = 0; it < (1u << 23); it++) {
    if (__all_sync(0xffffffffu, (int)(ld_relaxed(p) - target) >= 0)) break;
    if (BACKOFF) __nanosleep(BACKOFF);
  }
  asm volatile("fence.acquire.gpu;" ::: "memory");
}
template<int N> __device__ __forceinline__ void reg_fence(float (&d)[N]) {
#pragma unroll
  for (int i = 0; i < N; i++) asm volatile("" : "+f"(d[i]) :: "memory");
}
template<int N> __device__ __forceinline__ void reg_fence(uint32_t (&d)[N]) {
#pragma unroll
  for (int i = 0; i < N; i++) asm volatile("" : "+r"(d[i]) :: "memory");
}
__device__ __forceinline__ float ex2(float x) { float y; asm("ex2.approx.ftz.f32 %0, %1;" : "=f"(y) : "f"(x)); return y; }
__device__ __forceinline__ uint32_t pack_bf16(float lo, float hi) { uint32_t r; asm("cvt.rn.bf16x2.f32 %0, %1, %2;" : "=r"(r) : "f"(hi), "f"(lo)); return r; }
__device__ __forceinline__ float bf_lo(uint32_t w) { return __uint_as_float(w << 16); }
__device__ __forceinline__ float bf_hi(uint32_t w) { return __uint_as_float(w & 0xffff0000u); }
__device__ __forceinline__ uint64_t desc_k(uint32_t addr, uint32_t add) { return (uint64_t)((((addr & 0x3FFFF) >> 4) | (1u << 16)) + add) | (0x40000100ull << 32); }
__device__ __forceinline__ uint64_t desc_mn(uint32_t addr, uint32_t add) { return (uint64_t)((((addr & 0x3FFFF) >> 4) | ((1024u >> 4) << 16)) + add) | (0x40000100ull << 32); }
__device__ __forceinline__ uint64_t desc_m(uint32_t addr, uint32_t add) { return (uint64_t)((((addr & 0x3FFFF) >> 4) | ((1024u >> 4) << 16)) + add) | (0x80000020ull << 32); }
__device__ __forceinline__ void sts128(uint32_t a, uint4 v) { asm volatile("st.shared.v4.u32 [%0], {%1,%2,%3,%4};" :: "r"(a), "r"(v.x), "r"(v.y), "r"(v.z), "r"(v.w) : "memory"); }
__device__ __forceinline__ uint4 lds128(uint32_t a) { uint4 v; asm volatile("ld.shared.v4.u32 {%0,%1,%2,%3}, [%4];" : "=r"(v.x), "=r"(v.y), "=r"(v.z), "=r"(v.w) : "r"(a) : "memory"); return v; }
__device__ __forceinline__ void mma16816(float (&c)[4], uint32_t a0, uint32_t a1, uint32_t a2, uint32_t a3, uint32_t b0, uint32_t b1) {
  asm volatile("mma.sync.aligned.m16n8k16.row.col.f32.bf16.bf16.f32 {%0,%1,%2,%3}, {%4,%5,%6,%7}, {%8,%9}, {%0,%1,%2,%3};"
    : "+f"(c[0]), "+f"(c[1]), "+f"(c[2]), "+f"(c[3]) : "r"(a0), "r"(a1), "r"(a2), "r"(a3), "r"(b0), "r"(b1));
}
__device__ __forceinline__ uint32_t sw_byte(int r, int c) {
  return (uint32_t)((r >> 3) * 4096 + (c >> 6) * 1024 + (r & 7) * 128 + ((((c >> 3) & 7) ^ (r & 7)) << 4) + (c & 7) * 2);
}
__device__ __forceinline__ int cta_id() { int c; asm volatile("mov.u32 %0, %%ctaid.x;" : "=r"(c)); return c; }
__device__ __forceinline__ bool tid_is(int v) { int t; asm volatile("mov.u32 %0, %%tid.x;" : "=r"(t)); return t == v; }
#define STAMP(cond, who, i)
#define CSTAMP(cond, who, i)
#define DUMP(cond, who, i0, i1)
#define XSTAMP(cond, i)
#define SSTAMP(i)

template <int OA, int OB> __device__ __forceinline__ void wgmma_ss_n256_tb(float (&d)[128], uint64_t da, uint64_t db, int scale_d) {
  asm volatile("{\n.reg .pred p;\n.reg .b64 a, b;\nsetp.ne.b32 p, %130, 0;\nadd.s64 a, %128, %131;\nadd.s64 b, %129, %132;\n"
    "wgmma.mma_async.sync.aligned.m64n256k16.f32.bf16.bf16 "
    "{%0, %1, %2, %3, %4, %5, %6, %7, %8, %9, %10, %11, %12, %13, %14, %15, %16, %17, %18, %19, %20, %21, %22, %23, %24, %25, %26, %27, %28, %29, %30, %31, %32, %33, %34, %35, %36, %37, %38, %39, %40, %41, %42, %43, %44, %45, %46, %47, %48, %49, %50, %51, %52, %53, %54, %55, %56, %57, %58, %59, %60, %61, %62, %63, %64, %65, %66, %67, %68, %69, %70, %71, %72, %73, %74, %75, %76, %77, %78, %79, %80, %81, %82, %83, %84, %85, %86, %87, %88, %89, %90, %91, %92, %93, %94, %95, %96, %97, %98, %99, %100, %101, %102, %103, %104, %105, %106, %107, %108, %109, %110, %111, %112, %113, %114, %115, %116, %117, %118, %119, %120, %121, %122, %123, %124, %125, %126, %127}, "
    "a, b, p, 1, 1, 0, 1;\n}\n"
    : "+f"(d[0]), "+f"(d[1]), "+f"(d[2]), "+f"(d[3]), "+f"(d[4]), "+f"(d[5]), "+f"(d[6]), "+f"(d[7]), "+f"(d[8]), "+f"(d[9]), "+f"(d[10]), "+f"(d[11]), "+f"(d[12]), "+f"(d[13]), "+f"(d[14]), "+f"(d[15]), "+f"(d[16]), "+f"(d[17]), "+f"(d[18]), "+f"(d[19]), "+f"(d[20]), "+f"(d[21]), "+f"(d[22]), "+f"(d[23]), "+f"(d[24]), "+f"(d[25]), "+f"(d[26]), "+f"(d[27]), "+f"(d[28]), "+f"(d[29]), "+f"(d[30]), "+f"(d[31]), "+f"(d[32]), "+f"(d[33]), "+f"(d[34]), "+f"(d[35]), "+f"(d[36]), "+f"(d[37]), "+f"(d[38]), "+f"(d[39]), "+f"(d[40]), "+f"(d[41]), "+f"(d[42]), "+f"(d[43]), "+f"(d[44]), "+f"(d[45]), "+f"(d[46]), "+f"(d[47]), "+f"(d[48]), "+f"(d[49]), "+f"(d[50]), "+f"(d[51]), "+f"(d[52]), "+f"(d[53]), "+f"(d[54]), "+f"(d[55]), "+f"(d[56]), "+f"(d[57]), "+f"(d[58]), "+f"(d[59]), "+f"(d[60]), "+f"(d[61]), "+f"(d[62]), "+f"(d[63]), "+f"(d[64]), "+f"(d[65]), "+f"(d[66]), "+f"(d[67]), "+f"(d[68]), "+f"(d[69]), "+f"(d[70]), "+f"(d[71]), "+f"(d[72]), "+f"(d[73]), "+f"(d[74]), "+f"(d[75]), "+f"(d[76]), "+f"(d[77]), "+f"(d[78]), "+f"(d[79]), "+f"(d[80]), "+f"(d[81]), "+f"(d[82]), "+f"(d[83]), "+f"(d[84]), "+f"(d[85]), "+f"(d[86]), "+f"(d[87]), "+f"(d[88]), "+f"(d[89]), "+f"(d[90]), "+f"(d[91]), "+f"(d[92]), "+f"(d[93]), "+f"(d[94]), "+f"(d[95]), "+f"(d[96]), "+f"(d[97]), "+f"(d[98]), "+f"(d[99]), "+f"(d[100]), "+f"(d[101]), "+f"(d[102]), "+f"(d[103]), "+f"(d[104]), "+f"(d[105]), "+f"(d[106]), "+f"(d[107]), "+f"(d[108]), "+f"(d[109]), "+f"(d[110]), "+f"(d[111]), "+f"(d[112]), "+f"(d[113]), "+f"(d[114]), "+f"(d[115]), "+f"(d[116]), "+f"(d[117]), "+f"(d[118]), "+f"(d[119]), "+f"(d[120]), "+f"(d[121]), "+f"(d[122]), "+f"(d[123]), "+f"(d[124]), "+f"(d[125]), "+f"(d[126]), "+f"(d[127])
    : "l"(da), "l"(db), "r"(scale_d), "n"(OA), "n"(OB));
}
template <int OA, int OB> __device__ __forceinline__ void wgmma_qk(float (&d)[64], uint64_t da, uint64_t db, int scale_d) {
  asm volatile("{\n.reg .pred p;\n.reg .b64 a, b;\nsetp.ne.b32 p, %66, 0;\nadd.s64 a, %64, %67;\nadd.s64 b, %65, %68;\n"
    "wgmma.mma_async.sync.aligned.m64n128k16.f32.bf16.bf16 "
    "{%0, %1, %2, %3, %4, %5, %6, %7, %8, %9, %10, %11, %12, %13, %14, %15, %16, %17, %18, %19, %20, %21, %22, %23, %24, %25, %26, %27, %28, %29, %30, %31, %32, %33, %34, %35, %36, %37, %38, %39, %40, %41, %42, %43, %44, %45, %46, %47, %48, %49, %50, %51, %52, %53, %54, %55, %56, %57, %58, %59, %60, %61, %62, %63}, "
    "a, b, p, 1, 1, 0, 0;\n}\n"
    : "+f"(d[0]), "+f"(d[1]), "+f"(d[2]), "+f"(d[3]), "+f"(d[4]), "+f"(d[5]), "+f"(d[6]), "+f"(d[7]), "+f"(d[8]), "+f"(d[9]), "+f"(d[10]), "+f"(d[11]), "+f"(d[12]), "+f"(d[13]), "+f"(d[14]), "+f"(d[15]), "+f"(d[16]), "+f"(d[17]), "+f"(d[18]), "+f"(d[19]), "+f"(d[20]), "+f"(d[21]), "+f"(d[22]), "+f"(d[23]), "+f"(d[24]), "+f"(d[25]), "+f"(d[26]), "+f"(d[27]), "+f"(d[28]), "+f"(d[29]), "+f"(d[30]), "+f"(d[31]), "+f"(d[32]), "+f"(d[33]), "+f"(d[34]), "+f"(d[35]), "+f"(d[36]), "+f"(d[37]), "+f"(d[38]), "+f"(d[39]), "+f"(d[40]), "+f"(d[41]), "+f"(d[42]), "+f"(d[43]), "+f"(d[44]), "+f"(d[45]), "+f"(d[46]), "+f"(d[47]), "+f"(d[48]), "+f"(d[49]), "+f"(d[50]), "+f"(d[51]), "+f"(d[52]), "+f"(d[53]), "+f"(d[54]), "+f"(d[55]), "+f"(d[56]), "+f"(d[57]), "+f"(d[58]), "+f"(d[59]), "+f"(d[60]), "+f"(d[61]), "+f"(d[62]), "+f"(d[63])
    : "l"(da), "l"(db), "r"(scale_d), "n"(OA), "n"(OB));
}
template <int OA, int OB> __device__ __forceinline__ void wgmma_qk(float (&d)[56], uint64_t da, uint64_t db, int scale_d) {
  asm volatile("{\n.reg .pred p;\n.reg .b64 a, b;\nsetp.ne.b32 p, %58, 0;\nadd.s64 a, %56, %59;\nadd.s64 b, %57, %60;\n"
    "wgmma.mma_async.sync.aligned.m64n112k16.f32.bf16.bf16 "
    "{%0, %1, %2, %3, %4, %5, %6, %7, %8, %9, %10, %11, %12, %13, %14, %15, %16, %17, %18, %19, %20, %21, %22, %23, %24, %25, %26, %27, %28, %29, %30, %31, %32, %33, %34, %35, %36, %37, %38, %39, %40, %41, %42, %43, %44, %45, %46, %47, %48, %49, %50, %51, %52, %53, %54, %55}, "
    "a, b, p, 1, 1, 0, 0;\n}\n"
    : "+f"(d[0]), "+f"(d[1]), "+f"(d[2]), "+f"(d[3]), "+f"(d[4]), "+f"(d[5]), "+f"(d[6]), "+f"(d[7]), "+f"(d[8]), "+f"(d[9]), "+f"(d[10]), "+f"(d[11]), "+f"(d[12]), "+f"(d[13]), "+f"(d[14]), "+f"(d[15]), "+f"(d[16]), "+f"(d[17]), "+f"(d[18]), "+f"(d[19]), "+f"(d[20]), "+f"(d[21]), "+f"(d[22]), "+f"(d[23]), "+f"(d[24]), "+f"(d[25]), "+f"(d[26]), "+f"(d[27]), "+f"(d[28]), "+f"(d[29]), "+f"(d[30]), "+f"(d[31]), "+f"(d[32]), "+f"(d[33]), "+f"(d[34]), "+f"(d[35]), "+f"(d[36]), "+f"(d[37]), "+f"(d[38]), "+f"(d[39]), "+f"(d[40]), "+f"(d[41]), "+f"(d[42]), "+f"(d[43]), "+f"(d[44]), "+f"(d[45]), "+f"(d[46]), "+f"(d[47]), "+f"(d[48]), "+f"(d[49]), "+f"(d[50]), "+f"(d[51]), "+f"(d[52]), "+f"(d[53]), "+f"(d[54]), "+f"(d[55])
    : "l"(da), "l"(db), "r"(scale_d), "n"(OA), "n"(OB));
}
template <int OB> __device__ __forceinline__ void wgmma_rs_n256_tb(float (&d)[128], uint32_t a0, uint32_t a1, uint32_t a2, uint32_t a3, uint64_t db, int scale_d) {
  asm volatile("{\n.reg .pred p;\n.reg .b64 b;\nsetp.ne.b32 p, %133, 0;\nadd.s64 b, %132, %134;\n"
    "wgmma.mma_async.sync.aligned.m64n256k16.f32.bf16.bf16 "
    "{%0, %1, %2, %3, %4, %5, %6, %7, %8, %9, %10, %11, %12, %13, %14, %15, %16, %17, %18, %19, %20, %21, %22, %23, %24, %25, %26, %27, %28, %29, %30, %31, %32, %33, %34, %35, %36, %37, %38, %39, %40, %41, %42, %43, %44, %45, %46, %47, %48, %49, %50, %51, %52, %53, %54, %55, %56, %57, %58, %59, %60, %61, %62, %63, %64, %65, %66, %67, %68, %69, %70, %71, %72, %73, %74, %75, %76, %77, %78, %79, %80, %81, %82, %83, %84, %85, %86, %87, %88, %89, %90, %91, %92, %93, %94, %95, %96, %97, %98, %99, %100, %101, %102, %103, %104, %105, %106, %107, %108, %109, %110, %111, %112, %113, %114, %115, %116, %117, %118, %119, %120, %121, %122, %123, %124, %125, %126, %127}, "
    "{%128, %129, %130, %131}, b, p, 1, 1, 1;\n}\n"
    : "+f"(d[0]), "+f"(d[1]), "+f"(d[2]), "+f"(d[3]), "+f"(d[4]), "+f"(d[5]), "+f"(d[6]), "+f"(d[7]), "+f"(d[8]), "+f"(d[9]), "+f"(d[10]), "+f"(d[11]), "+f"(d[12]), "+f"(d[13]), "+f"(d[14]), "+f"(d[15]), "+f"(d[16]), "+f"(d[17]), "+f"(d[18]), "+f"(d[19]), "+f"(d[20]), "+f"(d[21]), "+f"(d[22]), "+f"(d[23]), "+f"(d[24]), "+f"(d[25]), "+f"(d[26]), "+f"(d[27]), "+f"(d[28]), "+f"(d[29]), "+f"(d[30]), "+f"(d[31]), "+f"(d[32]), "+f"(d[33]), "+f"(d[34]), "+f"(d[35]), "+f"(d[36]), "+f"(d[37]), "+f"(d[38]), "+f"(d[39]), "+f"(d[40]), "+f"(d[41]), "+f"(d[42]), "+f"(d[43]), "+f"(d[44]), "+f"(d[45]), "+f"(d[46]), "+f"(d[47]), "+f"(d[48]), "+f"(d[49]), "+f"(d[50]), "+f"(d[51]), "+f"(d[52]), "+f"(d[53]), "+f"(d[54]), "+f"(d[55]), "+f"(d[56]), "+f"(d[57]), "+f"(d[58]), "+f"(d[59]), "+f"(d[60]), "+f"(d[61]), "+f"(d[62]), "+f"(d[63]), "+f"(d[64]), "+f"(d[65]), "+f"(d[66]), "+f"(d[67]), "+f"(d[68]), "+f"(d[69]), "+f"(d[70]), "+f"(d[71]), "+f"(d[72]), "+f"(d[73]), "+f"(d[74]), "+f"(d[75]), "+f"(d[76]), "+f"(d[77]), "+f"(d[78]), "+f"(d[79]), "+f"(d[80]), "+f"(d[81]), "+f"(d[82]), "+f"(d[83]), "+f"(d[84]), "+f"(d[85]), "+f"(d[86]), "+f"(d[87]), "+f"(d[88]), "+f"(d[89]), "+f"(d[90]), "+f"(d[91]), "+f"(d[92]), "+f"(d[93]), "+f"(d[94]), "+f"(d[95]), "+f"(d[96]), "+f"(d[97]), "+f"(d[98]), "+f"(d[99]), "+f"(d[100]), "+f"(d[101]), "+f"(d[102]), "+f"(d[103]), "+f"(d[104]), "+f"(d[105]), "+f"(d[106]), "+f"(d[107]), "+f"(d[108]), "+f"(d[109]), "+f"(d[110]), "+f"(d[111]), "+f"(d[112]), "+f"(d[113]), "+f"(d[114]), "+f"(d[115]), "+f"(d[116]), "+f"(d[117]), "+f"(d[118]), "+f"(d[119]), "+f"(d[120]), "+f"(d[121]), "+f"(d[122]), "+f"(d[123]), "+f"(d[124]), "+f"(d[125]), "+f"(d[126]), "+f"(d[127])
    : "r"(a0), "r"(a1), "r"(a2), "r"(a3), "l"(db), "r"(scale_d), "n"(OB));
}
template <int OB> __device__ __forceinline__ void wgmma_rs_n256_tb_first(float (&d)[128], uint32_t a0, uint32_t a1, uint32_t a2, uint32_t a3, uint64_t db) {
  asm volatile("{\n.reg .pred p;\n.reg .b64 b;\nsetp.ne.b32 p, 0, 0;\nadd.s64 b, %132, %133;\n"
    "wgmma.mma_async.sync.aligned.m64n256k16.f32.bf16.bf16 "
    "{%0, %1, %2, %3, %4, %5, %6, %7, %8, %9, %10, %11, %12, %13, %14, %15, %16, %17, %18, %19, %20, %21, %22, %23, %24, %25, %26, %27, %28, %29, %30, %31, %32, %33, %34, %35, %36, %37, %38, %39, %40, %41, %42, %43, %44, %45, %46, %47, %48, %49, %50, %51, %52, %53, %54, %55, %56, %57, %58, %59, %60, %61, %62, %63, %64, %65, %66, %67, %68, %69, %70, %71, %72, %73, %74, %75, %76, %77, %78, %79, %80, %81, %82, %83, %84, %85, %86, %87, %88, %89, %90, %91, %92, %93, %94, %95, %96, %97, %98, %99, %100, %101, %102, %103, %104, %105, %106, %107, %108, %109, %110, %111, %112, %113, %114, %115, %116, %117, %118, %119, %120, %121, %122, %123, %124, %125, %126, %127}, "
    "{%128, %129, %130, %131}, b, p, 1, 1, 1;\n}\n"
    : "=f"(d[0]), "=f"(d[1]), "=f"(d[2]), "=f"(d[3]), "=f"(d[4]), "=f"(d[5]), "=f"(d[6]), "=f"(d[7]), "=f"(d[8]), "=f"(d[9]), "=f"(d[10]), "=f"(d[11]), "=f"(d[12]), "=f"(d[13]), "=f"(d[14]), "=f"(d[15]), "=f"(d[16]), "=f"(d[17]), "=f"(d[18]), "=f"(d[19]), "=f"(d[20]), "=f"(d[21]), "=f"(d[22]), "=f"(d[23]), "=f"(d[24]), "=f"(d[25]), "=f"(d[26]), "=f"(d[27]), "=f"(d[28]), "=f"(d[29]), "=f"(d[30]), "=f"(d[31]), "=f"(d[32]), "=f"(d[33]), "=f"(d[34]), "=f"(d[35]), "=f"(d[36]), "=f"(d[37]), "=f"(d[38]), "=f"(d[39]), "=f"(d[40]), "=f"(d[41]), "=f"(d[42]), "=f"(d[43]), "=f"(d[44]), "=f"(d[45]), "=f"(d[46]), "=f"(d[47]), "=f"(d[48]), "=f"(d[49]), "=f"(d[50]), "=f"(d[51]), "=f"(d[52]), "=f"(d[53]), "=f"(d[54]), "=f"(d[55]), "=f"(d[56]), "=f"(d[57]), "=f"(d[58]), "=f"(d[59]), "=f"(d[60]), "=f"(d[61]), "=f"(d[62]), "=f"(d[63]), "=f"(d[64]), "=f"(d[65]), "=f"(d[66]), "=f"(d[67]), "=f"(d[68]), "=f"(d[69]), "=f"(d[70]), "=f"(d[71]), "=f"(d[72]), "=f"(d[73]), "=f"(d[74]), "=f"(d[75]), "=f"(d[76]), "=f"(d[77]), "=f"(d[78]), "=f"(d[79]), "=f"(d[80]), "=f"(d[81]), "=f"(d[82]), "=f"(d[83]), "=f"(d[84]), "=f"(d[85]), "=f"(d[86]), "=f"(d[87]), "=f"(d[88]), "=f"(d[89]), "=f"(d[90]), "=f"(d[91]), "=f"(d[92]), "=f"(d[93]), "=f"(d[94]), "=f"(d[95]), "=f"(d[96]), "=f"(d[97]), "=f"(d[98]), "=f"(d[99]), "=f"(d[100]), "=f"(d[101]), "=f"(d[102]), "=f"(d[103]), "=f"(d[104]), "=f"(d[105]), "=f"(d[106]), "=f"(d[107]), "=f"(d[108]), "=f"(d[109]), "=f"(d[110]), "=f"(d[111]), "=f"(d[112]), "=f"(d[113]), "=f"(d[114]), "=f"(d[115]), "=f"(d[116]), "=f"(d[117]), "=f"(d[118]), "=f"(d[119]), "=f"(d[120]), "=f"(d[121]), "=f"(d[122]), "=f"(d[123]), "=f"(d[124]), "=f"(d[125]), "=f"(d[126]), "=f"(d[127])
    : "r"(a0), "r"(a1), "r"(a2), "r"(a3), "l"(db), "n"(OB));
}
template <int OB> __device__ __forceinline__ void wgmma_rs_n128_tb(float (&d)[64], uint32_t a0, uint32_t a1, uint32_t a2, uint32_t a3, uint64_t db, int scale_d) {
  asm volatile("{\n.reg .pred p;\n.reg .b64 b;\nsetp.ne.b32 p, %69, 0;\nadd.s64 b, %68, %70;\n"
    "wgmma.mma_async.sync.aligned.m64n128k16.f32.bf16.bf16 "
    "{%0, %1, %2, %3, %4, %5, %6, %7, %8, %9, %10, %11, %12, %13, %14, %15, %16, %17, %18, %19, %20, %21, %22, %23, %24, %25, %26, %27, %28, %29, %30, %31, %32, %33, %34, %35, %36, %37, %38, %39, %40, %41, %42, %43, %44, %45, %46, %47, %48, %49, %50, %51, %52, %53, %54, %55, %56, %57, %58, %59, %60, %61, %62, %63}, "
    "{%64, %65, %66, %67}, b, p, 1, 1, 1;\n}\n"
    : "+f"(d[0]), "+f"(d[1]), "+f"(d[2]), "+f"(d[3]), "+f"(d[4]), "+f"(d[5]), "+f"(d[6]), "+f"(d[7]), "+f"(d[8]), "+f"(d[9]), "+f"(d[10]), "+f"(d[11]), "+f"(d[12]), "+f"(d[13]), "+f"(d[14]), "+f"(d[15]), "+f"(d[16]), "+f"(d[17]), "+f"(d[18]), "+f"(d[19]), "+f"(d[20]), "+f"(d[21]), "+f"(d[22]), "+f"(d[23]), "+f"(d[24]), "+f"(d[25]), "+f"(d[26]), "+f"(d[27]), "+f"(d[28]), "+f"(d[29]), "+f"(d[30]), "+f"(d[31]), "+f"(d[32]), "+f"(d[33]), "+f"(d[34]), "+f"(d[35]), "+f"(d[36]), "+f"(d[37]), "+f"(d[38]), "+f"(d[39]), "+f"(d[40]), "+f"(d[41]), "+f"(d[42]), "+f"(d[43]), "+f"(d[44]), "+f"(d[45]), "+f"(d[46]), "+f"(d[47]), "+f"(d[48]), "+f"(d[49]), "+f"(d[50]), "+f"(d[51]), "+f"(d[52]), "+f"(d[53]), "+f"(d[54]), "+f"(d[55]), "+f"(d[56]), "+f"(d[57]), "+f"(d[58]), "+f"(d[59]), "+f"(d[60]), "+f"(d[61]), "+f"(d[62]), "+f"(d[63])
    : "r"(a0), "r"(a1), "r"(a2), "r"(a3), "l"(db), "r"(scale_d), "n"(OB));
}
template <int V> using IC = std::integral_constant<int, V>;
template <int I, int N, class F> __device__ __forceinline__ void static_for(F&& f) {
  if constexpr (I < N) { f(std::integral_constant<int, I>{}); static_for<I + 1, N>(f); }
}

constexpr uint32_t SM_Q = 0, SM_BAR = 7 * 32768;
constexpr uint32_t B_FULL = SM_BAR, B_EMPTY = B_FULL + 24, B_WF = B_EMPTY + 24, B_QFULL = B_WF + 32, B_QEMPTY = B_QFULL + 16,
                   B_EVH = B_QEMPTY + 16, B_EVQ = B_EVH + 8, B_EVP0 = B_EVQ + 8, B_BG = B_EVP0 + 16, B_M0 = B_BG + 8, B_HALF = B_M0 + 8,
                   B_HRD = B_HALF + 8, SM_UNSAFE = B_HRD + 8, SM_TS = SM_UNSAFE + 8, SM_ML = (SM_TS + 192 + 15) / 16 * 16, SM_EPOCH = SM_ML + 1024, SM_END = SM_EPOCH + 16;
constexpr uint32_t POS_M = 0x5462;
constexpr int SMEM_BYTES = SM_END;

#define ROW0(u) make_uint4(pack_bf16(o[16 * u], o[16 * u + 1]), pack_bf16(o[16 * u + 4], o[16 * u + 5]), \
                           pack_bf16(o[16 * u + 8], o[16 * u + 9]), pack_bf16(o[16 * u + 12], o[16 * u + 13]))
#define ROW1(u) make_uint4(pack_bf16(o[16 * u + 2], o[16 * u + 3]), pack_bf16(o[16 * u + 6], o[16 * u + 7]), \
                           pack_bf16(o[16 * u + 10], o[16 * u + 11]), pack_bf16(o[16 * u + 14], o[16 * u + 15]))

__global__ void __launch_bounds__(384, 1) gps_kernel(const __grid_constant__ Params P) {
  extern __shared__ __align__(1024) uint8_t smem_raw[];
  constexpr uint32_t sb = 1024;
  if (smem_u32(smem_raw) != sb) return;
  const int cta = blockIdx.x;
  const int wg = __shfl_sync(0xffffffffu, (int)threadIdx.x >> 7, 0);
  const int warp = __shfl_sync(0xffffffffu, ((int)threadIdx.x >> 5) & 3, 0);
  const int lane = threadIdx.x & 31;
#define ROLE                                                                                       \
  const Work& W = P.w[cta_id()];                                                                   \
  [[maybe_unused]] const int n0 = W.nb0 + W.na0, n1 = W.nb1 + W.na1, total = n0 + n1;              \
  [[maybe_unused]] const bool fin = W.role & R_FIN, tail = W.role & R_TAIL;                        \
  [[maybe_unused]] const uint32_t posw = total == 0 || tail ? POS_M : ((total & 1) ? 0x2546 : 0x4326)
  const int g = lane >> 2, t = lane & 3;
  if (wg < 2) {
    const int tid = threadIdx.x & 127;
    ROLE;
    const uint32_t sQ = sb + SM_Q + wg * 32768;
#define st0 tid_is(wg * 128)
    STAMP(st0, wg, 0);
    const int rr = lane >> 3, j = lane & 7;
    const uint32_t c0 = clk();
    while (clk() - c0 < XDELAY) {}
    const uint4* px[4];
#pragma unroll
    for (int i = 0; i < 4; i++) px[i] = (const uint4*)(P.x + (size_t)min(W.q0 * 128 + wg * 64 + warp * 16 + i * 4 + rr, NN - 1) * 256) + j;
    auto x_load = [&](int c) {
      if (c < 4) {
#pragma unroll
        for (int i = 0; i < 4; i++)
          cp_async16(sQ + warp * 8192 + (i >> 1) * 4096 + c * 1024 + ((i & 1) * 4 + rr) * 128 + ((j ^ ((i & 1) * 4 + rr)) << 4), px[i] + c * 8);
      }
      cp_commit();
    };
    if (total > 0) {
#pragma unroll
      for (int c = 0; c < XD; c++) x_load(c);
    }
    bar_sync(4, 384);
    if (wg == 1) bar_arrive(5, 256);

    const uint32_t sF = sQ + warp * 8192 + ((lane >> 3) & 1) * 4096 + (lane & 7) * 128;
    auto frag = [&](int k) { return sF + (k >> 2) * 1024 + ((((k & 3) * 2 + (lane >> 4)) ^ (lane & 7)) << 4); };
    uint32_t hq[64];
    const bool own = (W.own >> wg) & 1;
    if (total > 0) {
      float c1[4] = {0.f, 0.f, 0.f, 0.f}, ca[4] = {0.f, 0.f, 0.f, 0.f}, cb[4] = {0.f, 0.f, 0.f, 0.f};
#pragma unroll
      for (int k = 0; k < 16; k++) {
        if ((k & 3) == 0) {
          asm volatile("cp.async.wait_group %0;" :: "n"(XD - 1) : "memory");
          __syncwarp();
          x_load(k / 4 + XD);
        }
        ldsm4(frag(k), hq[4 * k], hq[4 * k + 1], hq[4 * k + 2], hq[4 * k + 3]);
        mma16816(c1, hq[4 * k], hq[4 * k + 1], hq[4 * k + 2], hq[4 * k + 3], 0x3f803f80u, 0x3f803f80u);
        mma16816(ca, hq[4 * k], hq[4 * k + 1], hq[4 * k + 2], hq[4 * k + 3], hq[4 * k], hq[4 * k + 2]);
        mma16816(cb, hq[4 * k], hq[4 * k + 1], hq[4 * k + 2], hq[4 * k + 3], hq[4 * k + 1], hq[4 * k + 3]);
      }
      const float mu0 = c1[0] * (1.0f / 256.0f), mu1 = c1[2] * (1.0f / 256.0f);
      const float v0 = fmaf(__shfl_sync(0xffffffffu, g & 1 ? ca[1] : ca[0], g * 4 + (g >> 1)), 1.0f / 256.0f, 1e-5f - mu0 * mu0);
      const float v1 = fmaf(__shfl_sync(0xffffffffu, g & 1 ? cb[3] : cb[2], g * 4 + (g >> 1)), 1.0f / 256.0f, 1e-5f - mu1 * mu1);
      float rs0, rs1;
      asm("rsqrt.approx.ftz.f32 %0, %1;" : "=f"(rs0) : "f"(v0)); asm("rsqrt.approx.ftz.f32 %0, %1;" : "=f"(rs1) : "f"(v1));
      if (W.q0 * 128 + wg * 64 + warp * 16 >= NN) rs0 = rs1 = 0.f;
      float nb0 = -mu0 * rs0, nb1 = -mu1 * rs1;
      const uint32_t sS = sb + SM_ML + (wg * 64 + warp * 16) * 8;
      if (t == 0) {
        asm volatile("st.shared.v2.f32 [%0], {%1,%2};" :: "r"(sS + g * 8), "f"(rs0), "f"(nb0) : "memory");
        asm volatile("st.shared.v2.f32 [%0], {%1,%2};" :: "r"(sS + g * 8 + 64), "f"(rs1), "f"(nb1) : "memory");
      }
      if (__any_sync(0xffffffffu, !(4.f * mu0 * mu0 <= v0) || !(4.f * mu1 * mu1 <= v1))) {
#pragma unroll 1
        for (int r = 0; r < 16; r++) {
          const uint32_t ad = sQ + warp * 8192 + (r >> 3) * 4096 + rr * 1024 + (r & 7) * 128 + ((j ^ (r & 7)) << 4);
          const uint4 v = lds128(ad);
          float f[8] = {bf_lo(v.x), bf_hi(v.x), bf_lo(v.y), bf_hi(v.y), bf_lo(v.z), bf_hi(v.z), bf_lo(v.w), bf_hi(v.w)};
          float sum = 0.f, ss = 0.f, rs;
#pragma unroll
          for (int i = 0; i < 8; i++) sum += f[i];
#pragma unroll 1
          for (int k = 1; k < 32; k *= 2) sum += __shfl_xor_sync(0xffffffffu, sum, k);
          sum *= 1.0f / 256.0f;
#pragma unroll
          for (int i = 0; i < 8; i++) { f[i] -= sum; ss += f[i] * f[i]; }
#pragma unroll 1
          for (int k = 1; k < 32; k *= 2) ss += __shfl_xor_sync(0xffffffffu, ss, k);
          asm("rsqrt.approx.ftz.f32 %0, %1;" : "=f"(rs) : "f"(fmaf(ss, 1.0f / 256.0f, 1e-5f)));
          if (W.q0 * 128 + wg * 64 + warp * 16 >= NN) rs = 0.f;
          sts128(ad, make_uint4(pack_bf16(f[0] * rs, f[1] * rs), pack_bf16(f[2] * rs, f[3] * rs), pack_bf16(f[4] * rs, f[5] * rs), pack_bf16(f[6] * rs, f[7] * rs)));
          if (lane == 0) asm volatile("st.shared.v2.f32 [%0], {%1,%2};" :: "r"(sS + r * 8), "f"(rs), "f"(-sum * rs) : "memory");
        }
        __syncwarp();
#pragma unroll
        for (int k = 0; k < 16; k++) ldsm4(frag(k), hq[4 * k], hq[4 * k + 1], hq[4 * k + 2], hq[4 * k + 3]);
        rs0 = rs1 = 1.f; nb0 = nb1 = 0.f;
      }
      asm volatile("setmaxnreg.inc.sync.aligned.u32 %0;" :: "n"(CREG));
      const uint32_t ah0 = pack_bf16(rs0, rs0), ah1 = pack_bf16(rs1, rs1), n0_ = pack_bf16(nb0, nb0), n1_ = pack_bf16(nb1, nb1);
      const uint32_t al0 = pack_bf16(rs0 - bf_lo(ah0), rs0 - bf_lo(ah0)), al1 = pack_bf16(rs1 - bf_lo(ah1), rs1 - bf_lo(ah1));
#pragma unroll
      for (int i = 0; i < 32; i++) {
        hq[2 * i] = hfma2(hq[2 * i], ah0, hfma2(hq[2 * i], al0, n0_));
        hq[2 * i + 1] = hfma2(hq[2 * i + 1], ah1, hfma2(hq[2 * i + 1], al1, n1_));
      }
      if (own) {
        const float e0 = fmaf(bf_hi(__shfl_sync(0xffffffffu, hq[62], lane | 3)), -0.5f * KS, KC), e1 = fmaf(bf_hi(__shfl_sync(0xffffffffu, hq[63], lane | 3)), -0.5f * KS, KC);
#pragma unroll
        for (int k = 0; k < 16; k++)
          stsm4(frag(k), hfma2(hq[4 * k], KS2, KC2), hfma2(hq[4 * k + 1], KS2, KC2),
                k < 15 ? hfma2(hq[4 * k + 2], KS2, KC2) : pack_bf16(fmaf(bf_lo(hq[62]), KS, e0), t == 3 ? KC : fmaf(bf_hi(hq[62]), KS, e0)),
                k < 15 ? hfma2(hq[4 * k + 3], KS2, KC2) : pack_bf16(fmaf(bf_lo(hq[63]), KS, e1), t == 3 ? KC : fmaf(bf_hi(hq[63]), KS, e1)));
      }
      __syncwarp();
      if (lane == 0) mbar_arrive(sb + B_EVH);
    } else {
      asm volatile("setmaxnreg.inc.sync.aligned.u32 %0;" :: "n"(CREG));
    }
    STAMP(st0, wg, 1);

    float o[128];
    int qph = 0, st = tail ? wg : 0, ph = 0;
    auto release = [&](int stg) { if (lane == 0) mbar_arrive(sb + B_EMPTY + 8 * stg); };
    int resume = total > 0 ? -1 : 0;
    auto fill = [&]() __attribute__((always_inline)) {
#pragma unroll
      for (int i = 0; i < 32; i++)
        asm volatile("ld.volatile.shared.v4.f32 {%0,%1,%2,%3}, [%4];" : "=f"(o[4 * i]), "=f"(o[4 * i + 1]), "=f"(o[4 * i + 2]), "=f"(o[4 * i + 3]) : "r"(sb) : "memory");
    };
    auto finish = [&]() __attribute__((always_inline)) {
      STAMP(st0, wg, 11);
      DUMP(st0, wg, 0, 16);
      if (!P.zero) { asm volatile("exit;"); __builtin_unreachable(); }
      fill();
    };
    auto run = [&](auto hot_) __attribute__((always_inline)) {
    constexpr bool HOT = hot_.value;
    const int nloc = P.w[cta_id()].nloc;
    if (!HOT && resume == 0) {
#pragma unroll 1
      for (int i = 0; i < 32; i++) {
        const int r = i * 8 + wg * 4 + warp;
        cp_async16(sb + ((POS_M >> (r >> 6) * 4) & 15) * 32768 + sw_byte(r & 63, lane * 8), (const uint4*)P.wout + r * 32 + lane);
      }
    }
    bool wide = false;
    if (HOT) {
      reg_fence(hq);
      auto qstep = [&](auto k_) {
        constexpr int k = k_.value;
        if (k < 2 || k % 4 == 0) { mbar_wait(k == 0 ? sb + B_M0 : sb + B_WF + 2 * (k & ~3), 0); if (k == 0 || k == 4) bar_sync(5 + wg, 256); wg_fence(); }
        if constexpr (k == 0) wgmma_rs_n256_tb_first<0>(o, hq[0], hq[1], hq[2], hq[3], desc_m(sb, (POS_M & 15) * 2048));
        else wgmma_rs_n256_tb<(k & 3) * 512>(o, hq[4 * k], hq[4 * k + 1], hq[4 * k + 2], hq[4 * k + 3], desc_m(sb, ((POS_M >> (k & ~3)) & 15) * 2048), 1);
      };
      static_for<0, 4>(qstep);
      wg_commit();
      bar_arrive(6 - wg, 256);
      wg_wait<0>();
      if (!tail) release(0);
      static_for<4, 16>(qstep);
      wg_commit();
      bar_arrive(6 - wg, 256);
      wg_wait<0>();
      reg_fence(o); reg_fence(hq);
      if (!tail) release(1);
      STAMP(st0, wg, 2);
      float c0 = (o[124] + (t == 3 ? 2.f : 1.f) * o[125]) * (-0.5f / 4.5f), c1 = (o[126] + (t == 3 ? 2.f : 1.f) * o[127]) * (-0.5f / 4.5f);
      c0 += __shfl_xor_sync(0xffffffffu, c0, 1); c1 += __shfl_xor_sync(0xffffffffu, c1, 1);
      c0 += __shfl_xor_sync(0xffffffffu, c0, 2); c1 += __shfl_xor_sync(0xffffffffu, c1, 2);
      float r0 = t == 3 ? 0.f : o[125], r1 = t == 3 ? 0.f : o[127], r2 = o[124], r3 = o[126];
#pragma unroll
      for (int i = 0; i < 31; i++) { r2 += o[4 * i]; r0 += o[4 * i + 1]; r3 += o[4 * i + 2]; r1 += o[4 * i + 3]; }
      r0 += r2; r1 += r3;
      r0 += __shfl_xor_sync(0xffffffffu, r0, 1); r1 += __shfl_xor_sync(0xffffffffu, r1, 1);
      r0 += __shfl_xor_sync(0xffffffffu, r0, 2); r1 += __shfl_xor_sync(0xffffffffu, r1, 2);
      r0 = fmaf(c0, -255.f, PSH / KC - r0); r1 = fmaf(c1, -255.f, PSH / KC - r1);
      wide = !(fabsf(c0) <= SAFE_C / KS) || !(fabsf(c1) <= SAFE_C / KS);
      if (own) mbar_wait(sb + B_HRD, 0);
#pragma unroll
      for (int k = 0; k < 16; k++)
        stsm4(frag(k),
              pack_bf16(o[8 * k] + c0, o[8 * k + 1] + c0), pack_bf16(o[8 * k + 2] + c1, o[8 * k + 3] + c1),
              pack_bf16(o[8 * k + 4] + c0, k == 15 && t == 3 ? r0 : o[8 * k + 5] + c0), pack_bf16(o[8 * k + 6] + c1, k == 15 && t == 3 ? r1 : o[8 * k + 7] + c1));
      fence_async_smem();
      __syncwarp();
      STAMP(st0, wg, 3);
      if (tail) { bar_sync(7, 256); if (wg == 0) { release(0); release(1); release(2); } }
      }

    if (HOT || (resume && resume < 4)) {
      ROLE;
      float m0, m1;
      const int qh = tail ? 0 : wg, tl = tail;
      uint32_t qo = qh * 2048;
      const uint32_t ko = (2 - tl) * 2048, stop = 1 + tl + (uint32_t)P.zero;
      float l0, l1;
      auto row_sums = [&]() { l0 = __shfl_sync(0xffffffffu, o[125] + 0.f, lane | 3); l1 = __shfl_sync(0xffffffffu, o[127] + 0.f, lane | 3); };
#define PART(u) make_uint4(pack_bf16(o[8 * u] - l0, o[8 * u + 1] - l0), pack_bf16(o[8 * u + 2] - l1, o[8 * u + 3] - l1), \
                           pack_bf16(o[8 * u + 4] - l0, o[8 * u + 5] - l0), pack_bf16(o[8 * u + 6] - l1, o[8 * u + 7] - l1))
      bool unsafe = !HOT;
      m0 = m1 = 0.f;
#pragma unroll 1
      for (int seg = HOT ? 0 : resume - 1; seg < 2; seg++) {
        ROLE;
        const bool last = __any_sync(0xffffffffu, seg || n1 == 0);
        m0 = m1 = !HOT && unsafe ? -INFINITY : 0.f;
        int first = 1;
        auto tile = [&](auto n_, bool endseg) __attribute__((always_inline)) -> bool {
          constexpr int N = n_.value;
          float s[N / 2]; uint32_t p[N / 4];
          if (!mbar_try_wait(sb + B_FULL + 8 * st, ph)) mbar_wait(sb + B_FULL + 8 * st, ph);
          const bool again = !HOT && N == 112 && first && !seg;
          if (HOT || N == 128) bar_sync(5 + wg, 256);
          else asm volatile("{\n.reg .pred p;\nsetp.eq.u32 p, %1, 0;\n@p bar.sync %0, 256;\n}\n" :: "r"(5 + wg), "r"((uint32_t)again) : "memory");
          wg_fence();
          const uint64_t dQ = desc_k(sb + SM_Q, qo), dK = desc_k(sb, ko + st * 4096);
          qo += (uint32_t)P.zero;
          static_for<0, 16>([&](auto k) { constexpr int kk = (k.value + KROT) & 15, off = (kk >> 2) * 64 + (kk & 3) * 2; wgmma_qk<off, off>(s, dQ, dK, k.value > 0); });
          wg_commit();
          if (HOT || N == 128) bar_arrive(6 - wg, 256);
          else asm volatile("{\n.reg .pred p;\nsetp.eq.u32 p, %1, 0;\n@p bar.arrive %0, 256;\n}\n" :: "r"(6 - wg), "r"((uint32_t)again) : "memory");
          if (HOT && N == 112 && first && !seg) {
            float a0 = 0.f, a1 = 0.f, a2 = 0.f, a3 = 0.f;
#pragma unroll
            for (int i = 0; i < 32; i++) { a0 += o[4 * i] * o[4 * i]; a2 += o[4 * i + 1] * o[4 * i + 1]; a1 += o[4 * i + 2] * o[4 * i + 2]; a3 += o[4 * i + 3] * o[4 * i + 3]; }
            a0 += a2; a1 += a3;
            a0 += __shfl_xor_sync(0xffffffffu, a0, 1); a1 += __shfl_xor_sync(0xffffffffu, a1, 1);
            a0 += __shfl_xor_sync(0xffffffffu, a0, 2); a1 += __shfl_xor_sync(0xffffffffu, a1, 2);
            unsafe = __any_sync(0xffffffffu, bar_red_or(tail ? 7 : 1 + wg, tail ? 256 : 128, wide || !(a0 <= SAFE_N2 / (KS * KS)) || !(a1 <= SAFE_N2 / (KS * KS))));
            if (lane == 0) { asm volatile("st.shared.u8 [%0], %1;" :: "r"(sb + SM_UNSAFE + wg), "r"((uint32_t)unsafe) : "memory"); mbar_arrive(sb + B_EVQ); }
          }
          STAMP(N == 112 && first && !seg && st0, wg, 0);
          wg_wait<0>();
          reg_fence(s);
          if (HOT && N == 112 && unsafe) return true;
          if (endseg) { if (lane == 0) mbar_arrive(sb + B_QEMPTY + 8 * wg); }
          if (!HOT && unsafe) {
            float a0 = fmaxf(s[0], s[1]), a1 = fmaxf(s[2], s[3]);
#pragma unroll
            for (int i = 1; i < N / 8; i++) { a0 = fmaxf(a0, fmaxf(s[4 * i], s[4 * i + 1])); a1 = fmaxf(a1, fmaxf(s[4 * i + 2], s[4 * i + 3])); }
            if (__any_sync(0xffffffffu, (a0 > m0 + TAU) || (a1 > m1 + TAU))) {
              a0 = fmaxf(a0, __shfl_xor_sync(0xffffffffu, a0, 1)); a1 = fmaxf(a1, __shfl_xor_sync(0xffffffffu, a1, 1));
              a0 = fmaxf(a0, __shfl_xor_sync(0xffffffffu, a0, 2)); a1 = fmaxf(a1, __shfl_xor_sync(0xffffffffu, a1, 2));
              const float x0 = ceilf(fmaxf(m0, a0)), x1 = ceilf(fmaxf(m1, a1)), sc0 = ex2(m0 - x0), sc1 = ex2(m1 - x1);
              m0 = x0; m1 = x1;
#pragma unroll
              for (int i = 0; i < 32; i++) { o[4 * i] *= sc0; o[4 * i + 1] *= sc0; o[4 * i + 2] *= sc1; o[4 * i + 3] *= sc1; }
            }
#pragma unroll
            for (int i = 0; i < N / 8; i++) { s[4 * i] -= m0; s[4 * i + 1] -= m0; s[4 * i + 2] -= m1; s[4 * i + 3] -= m1; }
          }
          auto pv = [&](auto k) { wgmma_rs_n256_tb<k.value * 512 + (63 << 16)>(o, p[4 * k.value], p[4 * k.value + 1], p[4 * k.value + 2], p[4 * k.value + 3], dK, k.value > 0 || N == 128 ? 1 : !first); };
#pragma unroll
          for (int i = 0; i < 16; i++) { p[i] = pack_bf16(ex2(s[2 * i]), ex2(s[2 * i + 1])); asm volatile("" : "+r"(p[i]) :: "memory"); }
          reg_fence(o);
          do bar_sync(5 + wg, 256); while (P.zero);
          wg_fence();
          static_for<0, 4>(pv);
          wg_commit();
#pragma unroll
          for (int i = 16; i < N / 4; i++) { p[i] = pack_bf16(ex2(s[2 * i]), ex2(s[2 * i + 1])); asm volatile("" : "+r"(p[i]) :: "memory"); }
          wg_fence();
          static_for<4, N / 16>(pv);
          wg_commit();
          bar_arrive(6 - wg, 256);
          if (N == 128) { wg_wait<1>(); if (endseg && last) { if (lane == 0) mbar_arrive(sb + B_HALF); } }
          wg_wait<0>();
          reg_fence(o); reg_fence(p);
          release(st);
          if (st) { st--; ph ^= 1; } else st = stop;
          return false;
        };
#pragma unroll 1
        for (int left = tail ? 8 - wg : (seg ? W.nb1 : W.nb0); left > 0; left--) { if (tile(IC<112>{}, false)) { resume = 1; return; } STAMP(first && !seg && st0, wg, 4); first = 0; }
#pragma unroll 1
        for (int left = tail ? 32 + wg : (seg ? W.na1 : W.na0); left > 0; left--) tile(IC<128>{}, left == 1);
        STAMP(st0 && last, wg, 6);
        {
        ROLE;
        if (last && fin && !(tail && wg == 1)) break;
        row_sums();
        if (last) mbar_wait(sb + (tail ? B_QEMPTY : B_HALF), 0);
        const uint32_t sp = sb + (tail ? 0 : (last ? (posw >> 12) + wg : (wg ? 4 - 2 * st : 6))) * 32768, sm = sb + SM_ML + (tail ? 0 : wg) * 512;
#pragma unroll
        for (int u = 0; u < 16; u++) sts128(sp + (u * 128 + tid) * 16, PART(u));
        if (t == 0) {
          asm volatile("st.shared.v2.f32 [%0], {%1,%2};" :: "r"(sm + (warp * 16 + g) * 8), "f"(m0), "f"(l0) : "memory");
          asm volatile("st.shared.v2.f32 [%0], {%1,%2};" :: "r"(sm + (warp * 16 + g) * 8 + 64), "f"(m1), "f"(l1) : "memory");
        }
        __syncwarp();
        if (lane == 0) mbar_arrive(sb + B_EVP0 + 8 * wg);
        STAMP(st0 && last, wg, 7);
        if (last) break;
        mbar_wait(sb + B_QFULL + 8 * wg, qph); qph ^= 1;
        uint32_t u; asm volatile("ld.shared.u8 %0, [%1];" : "=r"(u) : "r"(sb + SM_UNSAFE + wg) : "memory");
        unsafe = __any_sync(0xffffffffu, u != 0);
        if (HOT && unsafe) { resume = 2; return; }
        }
      }

      if (P.w[cta_id()].role & R_FIN) {
        ROLE;
        if (!(tail && wg == 1)) {
        row_sums();
        const int rl = wg * 64 + warp * 16 + g;
        uint32_t a[64];
#pragma unroll
        for (int i = 0; i < 64; i++) a[i] = pack_bf16(o[2 * i] - (i & 1 ? l1 : l0), o[2 * i + 1] - (i & 1 ? l1 : l0));
        reg_fence(a);
        {
          float2 e0, e1;
          mbar_wait(sb + B_QFULL + 8 * wg, qph);
          asm volatile("ld.shared.v2.f32 {%0,%1}, [%2];" : "=f"(e0.x), "=f"(e0.y) : "r"(sb + SM_ML + rl * 8) : "memory");
          asm volatile("ld.shared.v2.f32 {%0,%1}, [%2];" : "=f"(e1.x), "=f"(e1.y) : "r"(sb + SM_ML + rl * 8 + 64) : "memory");
          STAMP(st0, wg, 7);
          uint32_t fb0 = 0x3f803f80u, fb1 = 0x3f803f80u;
          const float s0 = l0 + e0.y, s1 = l1 + e1.y;
          const bool odd = __any_sync(0xffffffffu, m0 != e0.x || m1 != e1.x || !(fmaxf(s0, s1) < 0x1p40f) || !(fminf(s0, s1) > 0x1p-40f));
          if (HOT && odd) { resume = 3; return; }
          uint4 v[16];
#pragma unroll
          for (int u = 0; u < 16; u++) v[u] = lds128(sQ + (u * 128 + tid) * 16);
          if (!HOT && odd) {
            const float x0 = fmaxf(m0, e0.x), x1 = fmaxf(m1, e1.x);
            const float d0 = fmaxf(m0 - x0, -1000.f), d1 = fmaxf(m1 - x1, -1000.f), f0 = fmaxf(e0.x - x0, -1000.f), f1 = fmaxf(e1.x - x1, -1000.f);
            l0 = l0 * ex2(d0) + e0.y * ex2(f0); l1 = l1 * ex2(d1) + e1.y * ex2(f1);
            const int E0 = fexp(l0), E1 = fexp(l1);
            const uint32_t fa0 = pow2_bf2((int)d0 - E0), fa1 = pow2_bf2((int)d1 - E1);
            fb0 = pow2_bf2((int)f0 - E0); fb1 = pow2_bf2((int)f1 - E1);
            l0 = __uint_as_float(__float_as_uint(l0) - (E0 << 23)); l1 = __uint_as_float(__float_as_uint(l1) - (E1 << 23));
#pragma unroll
            for (int i = 0; i < 32; i++) { a[2 * i] = hmul2(a[2 * i], fa0); a[2 * i + 1] = hmul2(a[2 * i + 1], fa1); }
          } else { l0 = s0; l1 = s1; }
#pragma unroll
          for (int u = 0; u < 16; u++) {
            a[4 * u] = hfma2(v[u].x, fb0, a[4 * u]); a[4 * u + 1] = hfma2(v[u].y, fb1, a[4 * u + 1]);
            a[4 * u + 2] = hfma2(v[u].z, fb0, a[4 * u + 2]); a[4 * u + 3] = hfma2(v[u].w, fb1, a[4 * u + 3]);
          }
        }
        float fs0, fs1;
        asm("rcp.approx.ftz.f32 %0, %1;" : "=f"(fs0) : "f"(l0 * (KS / KC))); asm("rcp.approx.ftz.f32 %0, %1;" : "=f"(fs1) : "f"(l1 * (KS / KC)));
        STAMP(st0, wg, 8);
        reg_fence(a);
        bar_sync(5 + wg, 256);
        uint64_t dW[4];
        float y0[64], y1[64];
        auto half0 = [&](auto u_) {
          constexpr int u = u_.value;
          if (u % 4 == 0) { mbar_wait(sb + B_WF + 2 * u, 1); wg_fence(); dW[u / 4] = desc_mn(sb, ((posw >> u) & 15) * 2048); }
          wgmma_rs_n128_tb<(u & 3) * 512>(y0, a[4 * u], a[4 * u + 1], a[4 * u + 2], a[4 * u + 3], dW[u / 4], u != 0);
        };
        auto half1 = [&](auto u_) {
          constexpr int u = u_.value;
          wgmma_rs_n128_tb<(u & 3) * 512 + 128>(y1, a[4 * u], a[4 * u + 1], a[4 * u + 2], a[4 * u + 3], dW[u / 4], u != 0);
        };
        const bool wr = W.q0 * 128 + wg * 64 + warp * 16 < NN;
        uint4* po = (uint4*)(P.out + (size_t)(W.q0 * 128 + rl) * 256) + t;
        auto emit = [&](const float* y, uint4* dst) {
          if (wr) {
            red_bf16x8(dst, make_uint4(pack_bf16(y[0] * fs0, y[1] * fs0), pack_bf16(y[4] * fs0, y[5] * fs0), pack_bf16(y[8] * fs0, y[9] * fs0), pack_bf16(y[12] * fs0, y[13] * fs0)));
            red_bf16x8(dst + 8 * 32, make_uint4(pack_bf16(y[2] * fs1, y[3] * fs1), pack_bf16(y[6] * fs1, y[7] * fs1), pack_bf16(y[10] * fs1, y[11] * fs1), pack_bf16(y[14] * fs1, y[15] * fs1)));
          }
          wg_fence();
        };
        static_for<0, 16>(half0);
        wg_commit();
        static_for<0, 4>(half1);
        wg_commit();
        wg_wait<1>();
        reg_fence(y0);
        emit(y0, po); static_for<4, 8>(half1);
        emit(y0 + 16, po + 4); static_for<8, 12>(half1);
        emit(y0 + 32, po + 8); static_for<12, 16>(half1);
        wg_commit();
        bar_arrive(6 - wg, 256);
        emit(y0 + 48, po + 12);
        wg_wait<0>();
        reg_fence(a); reg_fence(y1);
        STAMP(st0, wg, 9);
#pragma unroll
        for (int u = 0; u < 4; u++) emit(y1 + 16 * u, po + 16 + 4 * u);
        }
        if (!tail) { STAMP(st0, wg, 11); DUMP(st0, wg, 0, 16); asm volatile("exit;"); __builtin_unreachable(); }
        if (wg == 1) { bar_sync(6, 256); bar_arrive(5, 256); } else qph ^= 1;
        __syncwarp();
        if (lane == 0) mbar_arrive(sb + B_QEMPTY + 8 * wg);
        fill();
        resume = 4;
      }
        }
#pragma unroll 1
    for (int step = HOT || resume ? 0 : -4; step < (HOT && resume == 4 ? 0 : nloc); step++) {
      ROLE;
      const bool helper = HOT || (resume && resume < 4);
      const bool isw = !HOT && step < 0;
      if (isw) {
        const uint4* src = (const uint4*)(step < -2 ? P.wmsg : P.wv) + ((step & 1) * 128 + wg * 64 + warp) * 32 + lane;
        float cw[8] = {0.f, 0.f, 0.f, 0.f, 0.f, 0.f, 0.f, 0.f};
#pragma unroll 1
        for (int i = 0; i < 16; i++) cp_async16(sQ + sw_byte(i * 4 + warp, lane * 8), src + i * 128);
        cp_commit();
#pragma unroll
        for (int i = 0; i < 8; i++) {
          const uint4 v = __ldg((const uint4*)(step < -2 ? P.wmsg : P.wv) + (248 + i) * 32 + lane);
          const float k = step < -2 ? 0.f : (i == 7 ? -1.0f / 4.5f : -0.5f / 4.5f);
          cw[0] += bf_lo(v.x) * k; cw[1] += bf_hi(v.x) * k; cw[2] += bf_lo(v.y) * k; cw[3] += bf_hi(v.y) * k;
          cw[4] += bf_lo(v.z) * k; cw[5] += bf_hi(v.z) * k; cw[6] += bf_lo(v.w) * k; cw[7] += bf_hi(v.w) * k;
        }
        asm volatile("cp.async.wait_group 0;" ::: "memory");
#pragma unroll 1
        for (int i = 0; i < 16; i++) {
          const uint32_t ad = sQ + sw_byte(i * 4 + warp, lane * 8);
          const uint4 v = lds128(ad);
          uint4 w4 = make_uint4(pack_bf16(bf_lo(v.x) + cw[0], bf_hi(v.x) + cw[1]), pack_bf16(bf_lo(v.y) + cw[2], bf_hi(v.y) + cw[3]),
                                pack_bf16(bf_lo(v.z) + cw[4], bf_hi(v.z) + cw[5]), pack_bf16(bf_lo(v.w) + cw[6], bf_hi(v.w) + cw[7]));
          if (step == -1 && wg * 64 + i * 4 + warp == 127) w4 = make_uint4(0, 0, 0, 0);
          sts128(ad, w4);
        }
        fence_async_smem();
        bar_sync(7, 256);
      } else {
        SSTAMP(0);
        mbar_wait(sb + B_QFULL + 8 * wg, qph); qph ^= 1;
        STAMP(st0 && step == 0, wg, 8);
        SSTAMP(1);
        bar_sync(5 + wg, 256);
        SSTAMP(2);
      }
#pragma unroll 1
      for (int c = 0; c < 4; c++) {
        if (step == 0) mbar_wait(sb + B_WF + 8 * c, helper);
        const int turn2 = helper ? 3 : 4;
        if (c == turn2) bar_sync(5 + wg, 256);
        wg_fence();
        const uint64_t dA = desc_k(sb + SM_Q, wg * 2048 + c * 64), dW = desc_mn(sb, ((posw >> c * 4) & 15) * 2048);
        static_for<0, 4>([&](auto k) { wgmma_ss_n256_tb<k.value * 2, k.value * 512>(o, dA, dW, k.value > 0 ? 1 : c); });
        wg_commit();
        if ((c == 3 || c == turn2 - 1) && !isw) bar_arrive(6 - wg, 256);
        wg_wait<1>();
      }
      wg_wait<0>();
      reg_fence(o);
      {
        STAMP(st0 && step == 0, wg, 9);
        SSTAMP(3);
        if (isw) bar_sync(1 + wg, 128); else if (lane == 0) mbar_arrive(sb + B_QEMPTY + 8 * wg);
        uint8_t* dw = (uint8_t*)(step < -2 ? g_Wmo : g_Wvo) + ((step & 1) * 2 + wg) * 32768 + warp * 8192 + g * 128;
        const int row0 = (W.loc0 + step) * 128 + wg * 64 + warp * 16;
        uint4 r[16];
#pragma unroll
        for (int u = 0; u < 8; u++) { r[2 * u] = ROW0(u); r[2 * u + 1] = ROW1(u); }
        if (isw) {
#pragma unroll
          for (int u = 0; u < 16; u++) *(uint4*)(dw + (u >> 2) * 1024 + ((((u & 2) * 2 + t) ^ g) << 4) + (u & 1) * 4096) = r[u];
        } else if (row0 < NN) {
          uint4* po = (uint4*)(P.out + (size_t)(row0 + g) * 256) + t;
          uint32_t c1 = clk();
#pragma unroll
          for (int u = 0; u < 16; u++) {
            red_bf16x8(po + (u >> 1) * 4 + (u & 1) * 256, r[u]);
            if (!HOT) { c1 += PACE; while ((int)(clk() - c1) < 0) {} }
          }
        }
        if (!HOT && step == -1) { bar_sync(7, 256); if (tid_is(0)) flag_release(F_W); __syncwarp(); STAMP(st0, wg, 3); }
      }
    }
    if (HOT && resume == 4) return;
    finish();
    };
    if (resume < 0) run(std::true_type{});
    else fill();
    run(std::false_type{});
    asm volatile("setmaxnreg.dec.sync.aligned.u32 %0;" :: "n"(504 - 2 * CREG));
  } else {
    STAMP(lane == 0 && warp == 0, 2, 0);
        const int mi = cta >> 3;
    const uint32_t sW = sb + 3 * 32768;
    uint4 wa[4], wb[8];
    {
      const uint4* pq = (const uint4*)(P.wq + ((mi & 15) * 16 + g) * 256) + warp * 8 + t;
      const uint4* pk = (const uint4*)(P.wk + ((cta & 7) * 32 + g) * 256) + warp * 8 + t;
#pragma unroll
      for (int i = 0; i < 4; i++) wa[i] = __ldg(pq + (i >> 1) * 256 + (i & 1) * 4);
#pragma unroll
      for (int i = 0; i < 8; i++) wb[i] = __ldg(pk + (i >> 1) * 256 + (i & 1) * 4);
    }
    if (threadIdx.x == 352) {
      for (int i = 0; i < 3; i++) { mbar_init(sb + B_FULL + 8 * i, 1); mbar_init(sb + B_EMPTY + 8 * i, cta == 130 ? 4 : 8); }
      for (int i = 0; i < 4; i++) mbar_init(sb + B_WF + 8 * i, 1);
      for (int i = 0; i < 2; i++) { mbar_init(sb + B_QFULL + 8 * i, 1); mbar_init(sb + B_QEMPTY + 8 * i, 4); mbar_init(sb + B_EVP0 + 8 * i, 4); }
      mbar_init(sb + B_EVH, 8); mbar_init(sb + B_EVQ, 8); mbar_init(sb + B_HALF, 8); mbar_init(sb + B_BG, 1); mbar_init(sb + B_M0, 1); mbar_init(sb + B_HRD, 1);
      asm volatile("fence.mbarrier_init.release.cluster;" ::: "memory");
    }
    __syncwarp();
    do bar_sync(4, 384); while (P.zero);
    {
#pragma unroll
      for (int n = 0; n < 4; n++) {
        float c[4] = {0.f, 0.f, 0.f, 0.f};
#pragma unroll
        for (int u = 0; u < 2; u++) {
          mma16816(c, wa[u].x, wa[2 + u].x, wa[u].y, wa[2 + u].y, wb[2 * n + u].x, wb[2 * n + u].y);
          mma16816(c, wa[u].z, wa[2 + u].z, wa[u].w, wa[2 + u].w, wb[2 * n + u].z, wb[2 * n + u].w);
        }
        asm volatile("st.shared.v2.f32 [%0], {%1,%2};" :: "r"(sW + ((warp * 16 + g) * 40 + n * 8 + 2 * t) * 4), "f"(c[0]), "f"(c[1]) : "memory");
        asm volatile("st.shared.v2.f32 [%0], {%1,%2};" :: "r"(sW + ((warp * 16 + g + 8) * 40 + n * 8 + 2 * t) * 4), "f"(c[2]), "f"(c[3]) : "memory");
      }
      STAMP(lane == 0 && warp == 0, 2, 7);
      bar_sync(3, 128);
      if (warp < 2) {
        float c[8] = {0.f, 0.f, 0.f, 0.f, 0.f, 0.f, 0.f, 0.f};
#pragma unroll
        for (int k = 0; k < 4; k++) {
          const uint4 v = lds128(sW + ((k * 16 + warp * 8 + g) * 40 + t * 8) * 4), w = lds128(sW + ((k * 16 + warp * 8 + g) * 40 + t * 8 + 4) * 4);
          c[0] += __uint_as_float(v.x); c[1] += __uint_as_float(v.y); c[2] += __uint_as_float(v.z); c[3] += __uint_as_float(v.w);
          c[4] += __uint_as_float(w.x); c[5] += __uint_as_float(w.y); c[6] += __uint_as_float(w.z); c[7] += __uint_as_float(w.w);
        }
        const float ms = 1.4426950408889634f / 16.0f / KS;
        const uint4 m4 = make_uint4(pack_bf16(c[0] * ms, c[1] * ms), pack_bf16(c[2] * ms, c[3] * ms), pack_bf16(c[4] * ms, c[5] * ms), pack_bf16(c[6] * ms, c[7] * ms));
        sts128(sW + 16384 + (warp * 8 + g) * 64 + ((t ^ (g >> 1)) << 4), m4);
      }
    }
    asm volatile("setmaxnreg.dec.sync.aligned.u32 %0;" :: "n"(504 - 2 * CREG));
    STAMP(lane == 0 && warp == 0, 2, 13);
    bar_sync(3, 128);
#define ep1 (lds32(sb + SM_EPOCH) + 1)
    if (threadIdx.x == 256 && cta < 128) {
      fence_async_smem();
      bulk_s2g(g_M + cta * 64, sW + 16384, 1024);
      bulk_commit();
      bulk_wait_all();
      red_relaxed(g_flag + F_M + (cta >> 5));
    }
    __syncwarp();
    ROLE;
    if (warp == 3 && W.own) {
      mbar_wait_w(sb + B_EVH, 0);
      if (W.role < R_SIG) mbar_wait_w(sb + B_WF + 8, 0);
      if (lane == 0) {
        fence_async_smem();
        const int h0 = W.own == 2, nh = W.own == 3 ? 2 : 1;
        bulk_s2g(g_h + W.hp * 4096 + h0 * 2048, sb + SM_Q + h0 * 32768, nh * 32768);
        bulk_s2g(g_stat + W.q0 * 128 + h0 * 64, sb + SM_ML + h0 * 512, nh * 512);
        bulk_commit();
        bulk_wait_read();
        mbar_arrive(sb + B_HRD);
        bulk_wait_all();
        if (W.role >= R_SIG) red_relaxed(g_flag + F_H1 - 1 + W.role / R_SIG);
        red_relaxed(g_flag + F_H);
      }
      __syncwarp();
      STAMP(lane == 0, 2, 6);
    }
    if (warp == 0) {
      if (lane == 0) {
        STAMP(true, 2, 1);
        const uint32_t epoch = ld_relaxed(g_flag + F_EPOCH);
        if (total > 0) {
#pragma unroll
          for (int c = 0; c < 3; c++) mbar_expect_tx(sb + B_WF + 8 * c, c == 0 ? WCH_B - 8192 : WCH_B);
          mbar_expect_tx(sb + B_M0, 8192);
          int c = 0;
#pragma unroll 1
          for (uint32_t it = 0; c < 4; it++) {
            uint4 f;
            asm volatile("ld.relaxed.gpu.global.v4.u32 {%0,%1,%2,%3}, [%4];" : "=r"(f.x), "=r"(f.y), "=r"(f.z), "=r"(f.w) : "l"(g_flag + F_M) : "memory");
            uint32_t tm;
            asm volatile("mad.lo.u32 %0, %1, 32, 32;" : "=r"(tm) : "r"(epoch));
            int ok = (int)(f.x - tm) < 0 ? 0 : (int)(f.y - tm) < 0 ? 1 : (int)(f.z - tm) < 0 ? 2 : (int)(f.w - tm) < 0 ? 3 : 4;
            if (it > (1u << 23)) ok = 4;
            if (ok > c) {
              asm volatile("fence.acquire.gpu;" ::: "memory"); fence_async_gmem();
              if (c == 0) bulk_g2s(sb + (POS_M & 15) * 32768, g_M, 8192, sb + B_M0);
            }
#pragma unroll 1
            for (; c < ok; c++) {
              const uint32_t skip = c == 0 ? 8192 : 0;
              bulk_g2s(sb + ((POS_M >> c * 4) & 15) * 32768 + skip, pofs<const uint8_t>(g_M, c * WCH_B + skip), WCH_B - skip, sb + B_WF + 8 * c);
              STAMP(c == 0, 2, 2);
            }
          }
        }
        asm volatile("st.shared.u32 [%0], %1;" :: "r"(sb + SM_EPOCH), "r"(epoch) : "memory");
        if (total > 0) mbar_expect_tx(sb + B_WF + 24, WCH_B);
        int st = 0, ph = 0, qph = 0;
        const int nsl = tail ? 3 : 2;
        auto next_slot = [&]() { mbar_wait(sb + B_EMPTY + 8 * st, ph); if (++st == nsl) { st = 0; ph ^= 1; } };
        const uint4* wsrc = fin ? g_Wvo : g_Wmo;
        auto w_load = [&](int c0, int c1) {
#pragma unroll 1
          for (int c = c0; c < c1; c++) {
            mbar_expect_tx(sb + B_WF + 8 * c, WCH_B);
            bulk_g2s(sb + ((posw >> c * 4) & 15) * 32768, pofs<const uint8_t>(wsrc, c * WCH_B), WCH_B, sb + B_WF + 8 * c);
          }
        };
        auto q_load = [&](const uint4* src, bool wait_empty) {
#pragma unroll 1
          for (int h = 0; h < 2; h++) {
            if (wait_empty) mbar_wait(sb + B_QEMPTY + 8 * h, qph);
            mbar_expect_tx(sb + B_QFULL + 8 * h, 32768);
            bulk_g2s_last(sb + SM_Q + h * 32768, src + h * 2048, 32768, sb + B_QFULL + 8 * h);
          }
          if (wait_empty) qph ^= 1;
        };
        auto part_out = [&](int slot, int h, uint32_t region, int parity) {
          mbar_wait(sb + B_EVP0 + 8 * h, parity);
          fence_async_smem();
          bulk_s2g(g_part + slot * 4096 + h * 2048, sb + region * 32768, 32768);
          bulk_s2g(g_ml + slot * 128 + h * 64, sb + SM_ML + h * 512, 512);
          bulk_commit();
        };
        auto announce = [&](int f) {
          red_relaxed(g_flag + f);
        };
        if (total > 0) {
          STAMP(true, 2, 3);
          const int q1 = W.q0 + 2 * W.own - 3;
          if (!tail) { flag_wait(F_H1 + (fin ? 0 : W.own), (epoch + 1) * (fin ? NH1_0 : (W.own == 1 ? NH1_1 : NH1_2))); fence_async_gmem(); }
          STAMP(true, 2, 4);
          uint32_t ko = W.k0 * 8192;
#pragma unroll 1
          for (int j = 0; j < total; j++) {
            if (j == (tail ? 0 : 1)) { flag_wait(F_H, (epoch + 1) * NHSIG); fence_async_gmem(); }
            if (j == n0) {
              flag_wait(F_QP + q1 * LN_, (epoch + 1)); fence_async_gmem();
              const uint32_t u = __ldcg(g_unsafe + q1);
              asm volatile("st.shared.u32 [%0], %1;" :: "r"(sb + SM_UNSAFE), "r"(u) : "memory");
              ko = W.k1 * 8192;
            }
            if (j == n0 + 1) q_load(g_qp + q1 * 4096, true);
            if (j == total - 1) { flag_wait(F_W, (epoch + 1)); fence_async_gmem(); if (!tail) w_load(0, 1); }
            const uint32_t bytes = (j < n0 ? j < W.nb0 : j - n0 < W.nb1) ? 112 * 512 : 128 * 512, s0 = st;
            const uint32_t region = (tail ? 1 : 2) + 2 * s0, skip = j == n0 + 1 ? 32768 : 0;
            if (skip) part_out(W.slotA, 0, 6, 0);
            next_slot();
            mbar_expect_tx(sb + B_FULL + 8 * s0, bytes);
            bulk_g2s(sb + region * 32768 + skip, pofs<const uint8_t>(g_h, ko + skip), bytes - skip, sb + B_FULL + 8 * s0);
            if (skip) {
              part_out(W.slotA, 1, region, 0);
              bulk_wait_read();
              bulk_g2s(sb + region * 32768, pofs<const uint8_t>(g_h, ko), skip, sb + B_FULL + 8 * s0);
              bulk_wait_all();
              announce(F_PART + W.slotA * LN_);
            }
            ko += bytes;
          }
          next_slot();
          if (tail) { next_slot(); next_slot(); }
        } else { flag_wait(F_W, (epoch + 1)); fence_async_gmem(); }
        STAMP(true, 2, 5);
        const bool staged = total > 0 && !tail;
        w_load(staged, staged ? (fin ? 2 : 3) : 4);
        if (tail) {
          mbar_wait(sb + B_BG, 0); mbar_wait(sb + B_EVP0 + 8, 0); mbar_arrive(sb + B_QFULL);
          qph = 1; wsrc = g_Wmo;
          mbar_wait(sb + B_QEMPTY, 1);
          w_load(0, 4);
        }
#pragma unroll 1
        for (int i = 0; i < W.nloc; i++) {
          const int tl = W.loc0 + i, last = tl * 128 + 127 < NN ? tl * 128 + 127 : NN - 1;
          flag_wait(F_AGG + ((last >= NGW) + (last >= 4 * NGW) + (last >= 9 * NGW)) * LN_, (epoch + 1) * NGW); fence_async_gmem();
          if (total == 0) g_flag[F_EPOCH] = epoch + 1;
          q_load(g_agg + tl * 4096, total > 0 || i > 0);
        }
        if (fin && !tail) {
          int h = 0, c = 2, have = W.slotB >= 0 ? 2 : 0;
          mbar_wait(sb + B_BG, 0);
#pragma unroll 1
          for (uint32_t it = 0; (h < 2 || c < 4) && it < (1u << 23); it++) {
            if (have < 2) {
              uint2 f;
              asm volatile("ld.relaxed.gpu.global.v2.u32 {%0,%1}, [%2];" : "=r"(f.x), "=r"(f.y) : "l"(g_flag + F_PART + W.slotA * LN_) : "memory");
              have = (int)(f.x - (epoch + 1)) < 0 ? 0 : ((int)(f.y - (epoch + 1)) < 0 ? 1 : 2);
            }
            if (h < have && mbar_try_wait_nb(sb + B_QEMPTY + 8 * h, 0)) {
              asm volatile("fence.acquire.gpu;" ::: "memory"); fence_async_gmem();
              STAMP(true, 2, 14 + h);
              mbar_expect_tx(sb + B_QFULL + 8 * h, 32768 + 512);
              bulk_g2s(sb + SM_ML + h * 512, g_ml + W.slotA * 128 + h * 64, 512, sb + B_QFULL + 8 * h);
              bulk_g2s(sb + SM_Q + h * 32768, g_part + W.slotA * 4096 + h * 2048, 32768, sb + B_QFULL + 8 * h);
              h++;
            }
            const bool half = mbar_try_wait_nb(sb + B_HALF, 0);
            const int c1 = half ? 4 : (h > 0 ? 3 : 2);
            if (c < c1) { w_load(c, c1); c = c1; }
          }
        } else if (!fin && total > 0) {
#pragma unroll 1
          for (int h = 0; h < 2; h++) part_out(W.slotB, h, (posw >> 12) + h, 1);
          asm volatile("cp.async.bulk.wait_group.read 1;" ::: "memory");
          w_load(3, 4);
          asm volatile("cp.async.bulk.wait_group 1;" ::: "memory");
          announce(F_PART + W.slotB * LN_);
          STAMP(true, 2, 14);
          bulk_wait_all();
          announce(F_PART + W.slotB * LN_ + 1);
          STAMP(true, 2, 15);
        }
        DUMP(true, 2, 14, 16);
        DUMP(true, 2, 0, 8);
      }
      return;
    }
  }
    {
      const int gw = cta * 3 + warp - 1;
      ROLE;
      if (total > 0) {
        mbar_wait_w(sb + B_EVQ, 0);
        const uint32_t c0 = clk();
        if (warp == 1 && (W.role & R_PUB)) {
          g_unsafe[W.q0] = lds32(sb + SM_UNSAFE);
#pragma unroll 1
          for (int k = 0; k < 4; k++) {
            __nanosleep(2000);
            if (lane == 0) bulk_s2g(pofs<uint4>(g_qp, W.q0 * 65536 + k * 16384), sb + SM_Q + k * 16384, 16384);
            bulk_commit();
          }
          bulk_wait_all();
          flag_release_w(F_QP + W.q0 * LN_);
        }
        while (__any_sync(0xffffffffu, clk() - c0 < GSTART)) __nanosleep(500);
        STAMP(lane == 0 && warp == 1, 2, 8);
#define ovf_cnt pofs<uint32_t>(g_flag, (F_OVF + (ep1 & 1) * LN_) * 4)
        if (gw == 0) g_flag[F_OVF + ((ep1 + 1) & 1) * LN_] = 0;
#pragma unroll 1
        for (int e0 = gw * 32; e0 < NE; e0 += NGW * 32 * 7) {
          int d[7], s[7], pos[7];
          const int* pd = pofs<const int>(P.dst, (e0 + lane) * 4);
          const int* ps = pofs<const int>(P.src, (e0 + lane) * 4);
#pragma unroll
          for (int k = 0; k < 7; k++) { const bool ok = e0 + k * NGW * 32 < NE; d[k] = ok ? __ldcs(pd + k * NGW * 32) : -1; s[k] = ok ? __ldcs(ps + k * NGW * 32) : 0; }
          uint32_t ov = 0;
#pragma unroll
          for (int k = 0; k < 7; k++) {
            pos[k] = 0;
            if (d[k] >= 0) asm volatile("atom.relaxed.gpu.global.add.u32 %0, [%1], 1;" : "=r"(pos[k]) : "l"(pofs<int>(g_cnt, d[k] << 2)) : "memory");
            s[k] = (uint32_t)(uintptr_t)g_u + s[k] * 512;
            if (d[k] >= 0 && pos[k] < CAP) asm volatile("st.volatile.global.u32 [%0], %1;" :: "l"(pofs<int>(g_bin, (d[k] * CAPS + pos[k]) << 2)), "r"(s[k]) : "memory");
            ov |= (pos[k] >= CAP) << k;
          }
          if (__any_sync(0xffffffffu, ov != 0)) {
            uint32_t at;
            asm volatile("atom.relaxed.gpu.global.add.u32 %0, [%1], %2;" : "=r"(at) : "l"(ovf_cnt), "r"(__popc(ov)) : "memory");
#pragma unroll
            for (int k = 0; k < 7; k++) if ((ov >> k) & 1) g_ovf[at++] = make_int2(d[k], s[k]);
          }
        }
        flag_wait_w(F_H, ep1 * NHSIG);
#pragma unroll 1
        for (int n0 = gw; n0 < NN; n0 += 4 * NGW) {
          uint4 xv[4]; float2 st[4];
#pragma unroll
          for (int k = 0; k < 4; k++) {
            const int n = n0 + k * NGW < NN ? n0 + k * NGW : n0;
            xv[k] = ldcs_v(pofs<const uint4>(P.x, n * 512 + lane * 16));
            st[k] = __ldcg(pofs<const float2>(g_stat, n * 8));
          }
#pragma unroll
          for (int k = 3; k >= 0; k--) {
            const int n = n0 + k * NGW;
            const float a = st[k].x * US, c = fmaf(st[k].y, US, UB + 8388608.0f);
#define FIX(w) __byte_perm(__float_as_uint(fmaf(bf_lo(w), a, c)), __float_as_uint(fmaf(bf_hi(w), a, c)), 0x5410)
            if (n < NN) {
              *pofs<uint4>(P.out, n * 512 + lane * 16) = xv[k];
              *pofs<uint4>(g_u, n * 512 + lane * 16) = make_uint4(FIX(xv[k].x), FIX(xv[k].y), FIX(xv[k].z), FIX(xv[k].w));
            }
          }
        }
        flag_release_w(F_BIN);
        STAMP(lane == 0 && warp == 1, 2, 9);
        flag_wait_w(F_BIN, ep1 * NGW);
        STAMP(lane == 0 && warp == 1, 2, 10);
        const int myn = gw + lane * NGW < NN ? gw + lane * NGW : gw;
        int cnts = __ldcg(g_cnt + myn);
        cnts = gw + lane * NGW < NN ? (cnts > CAP ? CAP + 1 : cnts) | ((int)__ldg((const unsigned short*)P.dinv + myn) << 16) : 0;
        __syncwarp();
        g_cnt[myn] = 0;
        const uint32_t uhi = (uintptr_t)g_u >> 32, lx = lane * 16;
        uint32_t obin = gw * CAPS * 4;
        uint32_t ent = __ldcg(pofs<const uint32_t>(g_bin, obin + lane * 4)), entn = __ldcg(pofs<const uint32_t>(g_bin, obin + NGW * CAPS * 4 + lane * 4));
        int cd = __shfl_sync(0xffffffffu, cnts, 0), cb = min(cd & 0xffff, CAP), e = 0;
        uint32_t sa[4] = {0, 0, 0, 0}, sh[4] = {0, 0, 0, 0};
        auto add = [&](uint32_t x, uint32_t y, uint32_t z, uint32_t w) {
          sa[0] += x; sa[1] += y; sa[2] += z; sa[3] += w;
          sh[0] += x >> 16; sh[1] += y >> 16; sh[2] += z >> 16; sh[3] += w >> 16;
        };
        int rnd = -1, rows = -1, cdo = 0;
#pragma unroll 1
        for (;;) {
          const bool hold = rows >= 0 && rnd == 8;
          const int m = hold ? 0 : cb - e;
          uint4 v[8];
          if (m >= 8) {
#pragma unroll
            for (int k = 0; k < 8; k++) v[k] = ldcg_v(addr64(__shfl_sync(0xffffffffu, ent, k) + lx, uhi));
          } else {
#pragma unroll
            for (int k = 0; k < 8; k++) {
              v[k] = make_uint4(0, 0, 0, 0);
              if (k < 7) ldcg_if(v[k], addr64(__shfl_sync(0xffffffffu, ent, k) + lx, uhi), k < m);
            }
          }
          if (rows >= 0) {
            const int n = gw + rnd * NGW;
            if (n < NN) {
              const float di = __uint_as_float(cdo & 0xffff0000u) * (1.0f / US), nl = -di * UB * (float)rows;
#define AGG(k) pack_bf16(fmaf((float)(sa[k] - (sh[k] << 16)), di, nl), fmaf((float)sh[k], di, nl))
              *pofs<uint4>(g_agg, ((n >> 3) * 4096 + (n & 7) * 144) ^ ((lx & 0x70) | ((lx & 0x180) << 3))) = make_uint4(AGG(0), AGG(1), AGG(2), AGG(3));
            }
#pragma unroll
            for (int k = 0; k < 4; k++) sa[k] = sh[k] = 0;
            rows = -1;
            if (rnd == 0 || rnd == 3 || rnd == 8 || rnd == NRND - 1) flag_release_w(F_AGG + ((rnd > 0) + (rnd > 3) + (rnd > 8)) * LN_);
            if (rnd == NRND - 1) break;
            if (hold) {
              if (fin && W.slotB >= 0) {
        #pragma unroll 1
                for (int k = 0; k < 2; k++) flag_wait_w(F_PART + (k ? W.slotB : W.slotA) * LN_, ep1);
        #pragma unroll 1
                for (int b = warp - 1; b < 8; b += 3) {
                  float2* ma = g_ml + W.slotA * 128 + b * 16 + g;
                  const float2* mb = g_ml + W.slotB * 128 + b * 16 + g;
                  const float2 a0 = __ldcg(ma), a1 = __ldcg(ma + 8), b0 = __ldcg(mb), b1 = __ldcg(mb + 8);
                  const float x0 = fmaxf(a0.x, b0.x), x1 = fmaxf(a1.x, b1.x);
                  const float fa0 = ex2(a0.x - x0), fa1 = ex2(a1.x - x1), fb0 = ex2(b0.x - x0), fb1 = ex2(b1.x - x1);
                  __syncwarp();
                  if (t == 0) { ma[0] = make_float2(x0, a0.y * fa0 + b0.y * fb0); ma[8] = make_float2(x1, a1.y * fa1 + b1.y * fb1); }
                  const uint32_t ofs = ((b >> 2) * 2048 + (b & 3) * 32 + lane) * 16;
        #pragma unroll 1
                  for (int u = 0; u < 16; u += 4) {
                    uint4* pa = pofs<uint4>(g_part, W.slotA * 65536 + ofs + u * 2048);
                    const uint4* pb = pofs<const uint4>(g_part, W.slotB * 65536 + ofs + u * 2048);
                    uint4 va[4], vb[4];
        #pragma unroll
                    for (int k = 0; k < 4; k++) { va[k] = ldcg_v(pa + k * 128); vb[k] = ldcs_v(pb + k * 128); }
        #define FOLD(w, fa, fb) pack_bf16(bf_lo(va[k].w) * fa + bf_lo(vb[k].w) * fb, bf_hi(va[k].w) * fa + bf_hi(vb[k].w) * fb)
        #pragma unroll
                    for (int k = 3; k >= 0; k--) pa[k * 128] = make_uint4(FOLD(x, fa0, fb0), FOLD(y, fa1, fb1), FOLD(z, fa0, fb0), FOLD(w, fa1, fb1));
                  }
                }
                bar_sync(3, 96);
                if (warp == 1) asm volatile("fence.acq_rel.gpu;" ::: "memory");
              }
              if (fin && warp == 1 && lane == 0) mbar_arrive(sb + B_BG);
              while (__any_sync(0xffffffffu, clk() - c0 < GPAUSE)) __nanosleep(500);
              continue;
            }
          }
#define SUM8(f) (v[7].f + v[6].f + v[5].f + v[4].f + v[3].f + v[2].f + v[1].f + v[0].f)
          add(SUM8(x), SUM8(y), SUM8(z), SUM8(w));
          e += 8;
          if (e < cb) {
            ent = __shfl_down_sync(0xffffffffu, ent, 8);
            if (e == 32) ent = __ldcg(pofs<const uint32_t>(g_bin, obin + 128 + lx / 4));
            continue;
          }
          rnd++; rows = cb; cdo = cd;
          if ((cd & 0xffff) > CAP) {
            const int no = __shfl_sync(0xffffffffu, (int)ld_relaxed(ovf_cnt), 0);
#pragma unroll 1
            for (int i0 = 0; i0 < no; i0 += 32) {
              int2 en = __ldcg(g_ovf + min(i0 + lane, no - 1));
              uint32_t mk = __ballot_sync(0xffffffffu, en.x == gw + rnd * NGW && i0 + lane < no);
              rows += __popc(mk);
#pragma unroll 1
              while (mk) {
                const int bit = __ffs(mk) - 1; mk &= mk - 1;
                const uint4 r = ldcg_v(addr64((uint32_t)__shfl_sync(0xffffffffu, en.y, bit) + lx, uhi));
                add(r.x, r.y, r.z, r.w);
              }
            }
          }
          obin += NGW * CAPS * 4;
          ent = entn; entn = __ldcg(pofs<const uint32_t>(g_bin, obin + NGW * CAPS * 4 + lx / 4));
          cd = __shfl_sync(0xffffffffu, cnts, rnd + 1); cb = min(cd & 0xffff, CAP); e = 0;
        }
      }
      STAMP(lane == 0 && warp == 1, 2, 11);
      if (warp == 2 && fin && lane == 0) {
        prefetch_l2(pofs<uint8_t>(P.out, W.q0 * 65536), tail ? 8192 : 65536);
        if (W.slotB >= 0) prefetch_l2(pofs<uint8_t>(g_part, W.slotA * 65536), 65536);
        prefetch_l2(pofs<uint8_t>(g_Wvo, (cta & 63) * 4096), 4096);
      }
      DUMP(warp == 1 && lane == 0, 2, 8, 14);
    }
}

}

extern "C" void kernel_launch(void* const* d_in, const int* in_sizes, int n_in, void* d_out, int out_size) {
  Params P;
  P.x = (const __nv_bfloat16*)d_in[0];
  P.src = (const int*)d_in[1];
  P.dst = (const int*)d_in[2];
  P.dinv = (const __nv_bfloat16*)d_in[3];
  P.wmsg = (const __nv_bfloat16*)d_in[4];
  P.wq = (const __nv_bfloat16*)d_in[5];
  P.wk = (const __nv_bfloat16*)d_in[6];
  P.wv = (const __nv_bfloat16*)d_in[7];
  P.wout = (const __nv_bfloat16*)d_in[8];
  P.out = (__nv_bfloat16*)d_out;
  P.zero = 0;
  for (int c = 0; c < NCTA; c++) P.w[c] = make_work(c);
  static void* scr = nullptr;
  if (!scr) {
    cudaFuncSetAttribute(gps_kernel, cudaFuncAttributeMaxDynamicSharedMemorySize, SMEM_BYTES);
    cudaGetSymbolAddress(&scr, g_scr);
  }
  P.s = (Scratch*)((((uintptr_t)scr + SCR_ALIGN - 1) & ~(uintptr_t)(SCR_ALIGN - 1)) + SCR_OFS);
  P.u = (uint4*)(((uintptr_t)P.s->u + 511) & ~(uintptr_t)511);
  if (((uintptr_t)P.u >> 32) != (((uintptr_t)(P.u + NN * 32) - 1) >> 32)) P.u += NN * 32;
  gps_kernel<<<NCTA, 384, SMEM_BYTES>>>(P);
}
```

```cpp
#include <cuda_runtime.h>
#include <cuda_bf16.h>
#include <stdint.h>
#include <stddef.h>
#include <type_traits>
#define FB 5
#define MB 5
#define GSTART 40000
#define XD 3
#define NTAIL 5
#define PACE 64
#define GPAUSE 112000
#define CREG 224
#define BACKOFF 1000

namespace {

constexpr int NN = 10000;
constexpr int NE = 160000;
constexpr int NQT = 79;
constexpr int NCTA = 132;
constexpr int CAP = 64;
constexpr int CAPS = 64;
constexpr int NHSIG = 105;
constexpr uint32_t WCH_B = 32768;
constexpr int NGW = (NCTA - 1) * 3;
constexpr float TAU = 16.0f;
constexpr float SAFE_N2 = 36.0f, SAFE_C = 0.6f;
#define KOFF 3
#define PSH -8.0f
#define KROT 15
constexpr float US = 256.0f, UB = 4095.0f;
constexpr float KS = 0.25f, KC = KOFF * KS;
constexpr uint32_t KS2 = 0x3e803e80u, KC2 = KOFF == 2 ? 0x3f003f00u : (KOFF == 1 ? 0x3e803e80u : 0x3f403f40u);

constexpr int NAGG = 4;
constexpr int NRND = (NN + NGW - 1) / NGW;
constexpr int NSLOT = 105;
constexpr int F_EPOCH = 0, F_H = 1, F_M = 4  , F_H1 = 8  , LN_ = 32;
constexpr int F_BIN = LN_, F_W = 2 * LN_, F_OVF = 3 * LN_  , F_QP = 5 * LN_, F_AGG = F_QP + NQT * LN_,
              F_PART = F_AGG + NAGG * LN_, F_END = F_PART + NSLOT * LN_;

struct Scratch {
  uint32_t flag[F_END];
  alignas(4096) uint4 M[8192];
  uint4 Wvo[8192], Wmo[8192];
  float2 ml[NSLOT * 128];
  uint32_t unsafe[96];
  int cnt[NN + 32];
  float2 stat[NQT * 128];
  alignas(4096) uint4 h[NQT * 4096];
  uint4 u[2 * NN * 32 + 32];
  uint4 qp[NQT * 4096];
  uint4 agg[NQT * 4096];
  uint4 part[NSLOT * 4096];
  int bin[(NRND + 2) * NGW * CAPS];
  int2 ovf[NE];
};
static_assert(offsetof(Scratch, h) % 128 == 0, "alignment");
#define SCR_ALIGN (2u << 20)
#define SCR_OFS 0
__device__ uint4 g_scr[(sizeof(Scratch) + SCR_ALIGN + SCR_OFS) / 16];
struct alignas(16) Work { short k0, k1; signed char q0, hp, nb0, na0, nb1, na1, slotA, slotB, loc0, nloc, own, role; };
constexpr int R_FIN = 1, R_PUB = 2, R_TAIL = 4, R_SIG = 8  ;
struct Params {
  const __nv_bfloat16 *x, *wq, *wk;
  Scratch* s;
  uint4* u;
  __nv_bfloat16* out;
  const __nv_bfloat16 *wout, *wmsg, *wv, *dinv;
  const int *src, *dst;
  long long zero;
  Work w[NCTA];
};
constexpr int first_cnt(int k) { return 2 * ((k + 6) / 8 - k / 8 + 1); }
constexpr int NH1_0 = 2, NH1_1 = first_cnt(48 * 8 - MB), NH1_2 = first_cnt(48 * 8 - MB + 16 * 8 - (15 - MB) / 2);
constexpr int NSERV = NQT - 52;
inline Work make_work(int c) {
  Work w;
  const int gi = c / 5, r = c % 5, q = gi * 3;
  const bool helper = r & 1, mid = r == 2;
  w.q0 = helper ? q + 1 : q + (r >> 1);
  const int hb1 = (15 - MB) / 2, hb3 = 15 - MB - hb1;
  w.nb0 = helper ? (r == 1 ? hb1 : hb3) : (mid ? MB : FB);
  w.na0 = (helper ? 16 : 48) - w.nb0;
  w.k0 = helper ? (48 * 8 - MB) + (r >> 1) * (16 * 8 - hb1) : 0;
  w.k1 = 48 * 8 - FB;
  w.nb1 = helper ? (FB < 7 ? 7 : 15) - FB : 0;
  w.na1 = helper ? (FB < 7 ? 31 : 32) - w.nb1 : 0;
  w.slotA = 4 * gi + (helper ? r - 1 : (mid ? 0 : (r >> 1) + 1));
  w.slotB = helper ? 4 * gi + r : (mid ? 4 * gi + 2 : -1);
  w.loc0 = NSERV + gi * 2 + (r >> 1);
  w.nloc = helper;
  w.own = helper ? (r + 1) >> 1 : (mid ? 0 : 3);
  w.role = helper ? 0 : (mid ? R_FIN : R_FIN | R_PUB);
  const int k1st[3] = {0, 48 * 8 - MB, 48 * 8 - MB + 16 * 8 - hb1};
  int pos[NQT], sig[NQT];
  for (int i = 0; i < NQT; i++) { pos[i] = i; sig[i] = 0; }
  for (int i = 0; i < 3; i++)
    for (int p = k1st[i] / 8; p <= (k1st[i] + 6) / 8; p++) {
      int m = 1, at = 0;
      while (sig[m]) m += 3;
      while (pos[at] != p) at++;
      pos[at] = pos[m]; pos[m] = p; sig[m] = 1 + i;
    }
  w.hp = c < 131 ? pos[w.q0] : 0;
  if (helper && c < 130) w.role |= sig[w.q0] * R_SIG;
  if (c == 130) { w.nb0 = 15; w.na0 = 65; w.slotA = NSLOT - 1; w.own = 1; w.role = R_FIN | R_TAIL; w.loc0 = NSERV - NTAIL; w.nloc = NTAIL; }
  if (c == 131) { w.nb0 = w.na0 = w.nb1 = w.na1 = 0; w.loc0 = 0; w.nloc = NSERV - NTAIL; w.own = 0; }
  return w;
}
#define g_flag P.s->flag
#define g_M P.s->M
#define g_Wvo P.s->Wvo
#define g_Wmo P.s->Wmo
#define g_ml P.s->ml
#define g_unsafe P.s->unsafe
#define g_cnt P.s->cnt
#define g_h P.s->h
#define g_u P.u
#define g_stat P.s->stat
#define g_qp P.s->qp
#define g_agg P.s->agg
#define g_part P.s->part
#define g_bin P.s->bin
#define g_ovf P.s->ovf

__device__ __forceinline__ uint32_t smem_u32(const void* p) { return (uint32_t)__cvta_generic_to_shared(p); }
__device__ __forceinline__ void mbar_init(uint32_t bar, uint32_t cnt) { asm volatile("mbarrier.init.shared::cta.b64 [%0], %1;" :: "r"(bar), "r"(cnt) : "memory"); }
__device__ __forceinline__ void mbar_arrive(uint32_t bar) { asm volatile("mbarrier.arrive.shared::cta.b64 _, [%0];" :: "r"(bar) : "memory"); }
__device__ __forceinline__ void mbar_expect_tx(uint32_t bar, uint32_t bytes) { asm volatile("mbarrier.arrive.expect_tx.shared::cta.b64 _, [%0], %1;" :: "r"(bar), "r"(bytes) : "memory"); }
__device__ __forceinline__ bool mbar_try_wait(uint32_t bar, uint32_t parity) {
  uint32_t ok;
  asm volatile("{\n.reg .pred p;\nmbarrier.try_wait.parity.shared::cta.b64 p, [%1], %2;\nselp.b32 %0, 1, 0, p;\n}\n" : "=r"(ok) : "r"(bar), "r"(parity) : "memory");
  return ok;
}
__device__ __forceinline__ bool mbar_try_wait_nb(uint32_t bar, uint32_t parity) {
  uint32_t ok;
  asm volatile("{\n.reg .pred p;\nmbarrier.test_wait.parity.shared::cta.b64 p, [%1], %2;\nselp.b32 %0, 1, 0, p;\n}\n" : "=r"(ok) : "r"(bar), "r"(parity) : "memory");
  return ok;
}
__device__ __forceinline__ void mbar_wait(uint32_t bar, uint32_t parity) {
#pragma unroll 1
  for (uint32_t it = 0; it < (1u << 25); it++) if (mbar_try_wait(bar, parity)) break;
}
__device__ __forceinline__ void bulk_s2g(void* dst, uint32_t src, uint32_t bytes) {
  asm volatile("cp.async.bulk.global.shared::cta.bulk_group [%0], [%1], %2;" :: "l"(dst), "r"(src), "r"(bytes) : "memory");
}
__device__ __forceinline__ void bulk_commit() { asm volatile("cp.async.bulk.commit_group;" ::: "memory"); }
__device__ __forceinline__ void bulk_wait_read() { asm volatile("cp.async.bulk.wait_group.read 0;" ::: "memory"); }
__device__ __forceinline__ void bulk_wait_all() { asm volatile("cp.async.bulk.wait_group 0;" ::: "memory"); }
__device__ __forceinline__ bool bar_red_or(int id, int cnt, bool c) {
  uint32_t r;
  asm volatile("{\n.reg .pred p, q;\nsetp.ne.b32 q, %3, 0;\nbar.red.or.pred p, %1, %2, q;\nselp.b32 %0, 1, 0, p;\n}\n"
               : "=r"(r) : "r"(id), "r"(cnt), "r"((uint32_t)c) : "memory");
  return r != 0;
}
template <class T> __device__ __forceinline__ T* pofs(const void* base, uint32_t off) {
  asm volatile("" : "+r"(off));
  return (T*)((uint8_t*)base + off);
}
__device__ __forceinline__ const void* addr64(uint32_t lo, uint32_t hi) { uint64_t a; asm("mov.b64 %0, {%1, %2};" : "=l"(a) : "r"(lo), "r"(hi)); return (const void*)a; }
__device__ __forceinline__ uint4 ldcg_v(const void* a) {
  uint4 v;
  asm volatile("ld.volatile.global.v4.u32 {%0,%1,%2,%3}, [%4];" : "=r"(v.x), "=r"(v.y), "=r"(v.z), "=r"(v.w) : "l"(a) : "memory");
  return v;
}
__device__ __forceinline__ uint4 ldcs_v(const void* a) {
  uint4 v;
  asm volatile("ld.global.cs.v4.u32 {%0,%1,%2,%3}, [%4];" : "=r"(v.x), "=r"(v.y), "=r"(v.z), "=r"(v.w) : "l"(a) : "memory");
  return v;
}
__device__ __forceinline__ void prefetch_l2(const void* a, uint32_t bytes) { asm volatile("cp.async.bulk.prefetch.L2.global [%0], %1;" :: "l"(a), "r"(bytes) : "memory"); }
__device__ __forceinline__ void ldcg_if(uint4& v, const void* a, bool c) {
  asm volatile("{\n.reg .pred p;\nsetp.ne.b32 p, %5, 0;\n@p ld.volatile.global.v4.u32 {%0,%1,%2,%3}, [%4];\n}\n"
               : "+r"(v.x), "+r"(v.y), "+r"(v.z), "+r"(v.w) : "l"(a), "r"((uint32_t)c) : "memory");
}
__device__ __forceinline__ void cp_async16(uint32_t dst, const void* src) {
  asm volatile("cp.async.cg.shared.global [%0], [%1], 16;" :: "r"(dst), "l"(src) : "memory");
}
__device__ __forceinline__ void red_bf16x8(void* a, uint4 v) {
  asm volatile("red.global.add.noftz.v4.bf16x2 [%0], {%1,%2,%3,%4};" :: "l"(a), "r"(v.x), "r"(v.y), "r"(v.z), "r"(v.w) : "memory");
}
__device__ __forceinline__ uint32_t clk() { uint32_t c; asm volatile("mov.u32 %0, %%clock;" : "=r"(c) :: "memory"); return c; }
__device__ __forceinline__ void stsm4(uint32_t a, uint32_t r0, uint32_t r1, uint32_t r2, uint32_t r3) {
  asm volatile("stmatrix.sync.aligned.m8n8.x4.shared.b16 [%0], {%1,%2,%3,%4};" :: "r"(a), "r"(r0), "r"(r1), "r"(r2), "r"(r3) : "memory");
}
__device__ __forceinline__ void ldsm4(uint32_t a, uint32_t& r0, uint32_t& r1, uint32_t& r2, uint32_t& r3) {
  asm volatile("ldmatrix.sync.aligned.m8n8.x4.shared.b16 {%0,%1,%2,%3}, [%4];" : "=r"(r0), "=r"(r1), "=r"(r2), "=r"(r3) : "r"(a) : "memory");
}
__device__ __forceinline__ void red_relaxed(uint32_t* p) { asm volatile("red.relaxed.gpu.global.add.u32 [%0], 1;" :: "l"(p) : "memory"); }
__device__ __forceinline__ uint32_t lds32(uint32_t a) { uint32_t v; asm volatile("ld.shared.u32 %0, [%1];" : "=r"(v) : "r"(a) : "memory"); return v; }
__device__ __forceinline__ void cp_commit() { asm volatile("cp.async.commit_group;" ::: "memory"); }
__device__ __forceinline__ uint32_t hmul2(uint32_t a, uint32_t b) { uint32_t d; asm("mul.rn.bf16x2 %0, %1, %2;" : "=r"(d) : "r"(a), "r"(b)); return d; }
__device__ __forceinline__ uint32_t hfma2(uint32_t a, uint32_t b, uint32_t c) { uint32_t d; asm("fma.rn.bf16x2 %0, %1, %2, %3;" : "=r"(d) : "r"(a), "r"(b), "r"(c)); return d; }
__device__ __forceinline__ uint32_t pow2_bf2(int n) { return (uint32_t)max(n + 127, 0) * 0x00800080u; }
__device__ __forceinline__ int fexp(float x) { return (int)(__float_as_uint(x) >> 23) - 127; }
__device__ __forceinline__ void bulk_g2s(uint32_t dst, const void* src, uint32_t bytes, uint32_t bar) {
  asm volatile("cp.async.bulk.shared::cta.global.mbarrier::complete_tx::bytes [%0], [%1], %2, [%3];"
    :: "r"(dst), "l"(src), "r"(bytes), "r"(bar) : "memory");
}
__device__ __forceinline__ void bulk_g2s_last(uint32_t dst, const void* src, uint32_t bytes, uint32_t bar) {
  asm volatile("{\n.reg .b64 p;\ncreatepolicy.fractional.L2::evict_first.b64 p;\n"
    "cp.async.bulk.shared::cta.global.mbarrier::complete_tx::bytes.L2::cache_hint [%0], [%1], %2, [%3], p;\n}\n"
    :: "r"(dst), "l"(src), "r"(bytes), "r"(bar) : "memory");
}
__device__ __forceinline__ void wg_fence() { asm volatile("wgmma.fence.sync.aligned;" ::: "memory"); }
__device__ __forceinline__ void wg_commit() { asm volatile("wgmma.commit_group.sync.aligned;" ::: "memory"); }
template<int N> __device__ __forceinline__ void wg_wait() { asm volatile("wgmma.wait_group.sync.aligned %0;" :: "n"(N) : "memory"); }
__device__ __forceinline__ void bar_sync(int id, int cnt) { asm volatile("bar.sync %0, %1;" :: "r"(id), "r"(cnt) : "memory"); }
__device__ __forceinline__ void fence_async_smem() { asm volatile("fence.proxy.async.shared::cta;" ::: "memory"); }
__device__ __forceinline__ void fence_async_gmem() { asm volatile("fence.proxy.async.global;" ::: "memory"); }
__device__ __forceinline__ void bar_arrive(int id, int cnt) { asm volatile("bar.arrive %0, %1;" :: "r"(id), "r"(cnt) : "memory"); }
__device__ __forceinline__ void red_release(uint32_t* p) { asm volatile("red.release.gpu.global.add.u32 [%0], 1;" :: "l"(p) : "memory"); }
__device__ __forceinline__ void red_release_w(uint32_t* p) {
  __syncwarp();
  asm volatile("{\n.reg .pred q;\n.reg .b32 l;\nmov.u32 l, %%laneid;\nsetp.eq.u32 q, l, 0;\n@q fence.release.gpu;\n@q red.relaxed.gpu.global.add.u32 [%0], 1;\n}\n" :: "l"(p) : "memory");
}
__device__ __forceinline__ void mbar_wait_w(uint32_t bar, uint32_t parity) {
#pragma unroll 1
  for (uint32_t it = 0; it < (1u << 25); it++) if (__all_sync(0xffffffffu, mbar_try_wait(bar, parity))) break;
}
#define flag_release_w(f) red_release_w(g_flag + (f))
#define flag_wait_w(f, target) poll_acquire_w(g_flag + (f), target)
#define flag_release(f) red_release(g_flag + (f))
__device__ __forceinline__ uint32_t ld_relaxed(const uint32_t* p) {
  uint32_t v; asm volatile("ld.relaxed.gpu.global.u32 %0, [%1];" : "=r"(v) : "l"(p) : "memory"); return v;
}
#define flag_wait(f, target) poll_acquire(g_flag + (f), target)
__device__ __forceinline__ void poll_acquire(const uint32_t* p, uint32_t target) {
#pragma unroll 1
  for (uint32_t it = 0; it < (1u << 23); it++) if ((int)(ld_relaxed(p) - target) >= 0) break;
  asm volatile("fence.acquire.gpu;" ::: "memory");
}
__device__ __forceinline__ void poll_acquire_w(const uint32_t* p, uint32_t target) {
#pragma unroll 1
  for (uint32_t it = 0; it < (1u << 23); it++) {
    if (__all_sync(0xffffffffu, (int)(ld_relaxed(p) - target) >= 0)) break;
    if (BACKOFF) __nanosleep(BACKOFF);
  }
  asm volatile("fence.acquire.gpu;" ::: "memory");
}
template<int N> __device__ __forceinline__ void reg_fence(float (&d)[N]) {
#pragma unroll
  for (int i = 0; i < N; i++) asm volatile("" : "+f"(d[i]) :: "memory");
}
template<int N> __device__ __forceinline__ void reg_fence(uint32_t (&d)[N]) {
#pragma unroll
  for (int i = 0; i < N; i++) asm volatile("" : "+r"(d[i]) :: "memory");
}
__device__ __forceinline__ float ex2(float x) { float y; asm("ex2.approx.ftz.f32 %0, %1;" : "=f"(y) : "f"(x)); return y; }
__device__ __forceinline__ uint32_t pack_bf16(float lo, float hi) { uint32_t r; asm("cvt.rn.bf16x2.f32 %0, %1, %2;" : "=r"(r) : "f"(hi), "f"(lo)); return r; }
__device__ __forceinline__ float bf_lo(uint32_t w) { return __uint_as_float(w << 16); }
__device__ __forceinline__ float bf_hi(uint32_t w) { return __uint_as_float(w & 0xffff0000u); }
__device__ __forceinline__ uint64_t desc_k(uint32_t addr, uint32_t add) { return (uint64_t)((((addr & 0x3FFFF) >> 4) | (1u << 16)) + add) | (0x40000100ull << 32); }
__device__ __forceinline__ uint64_t desc_mn(uint32_t addr, uint32_t add) { return (uint64_t)((((addr & 0x3FFFF) >> 4) | ((1024u >> 4) << 16)) + add) | (0x40000100ull << 32); }
__device__ __forceinline__ uint64_t desc_m(uint32_t addr, uint32_t add) { return (uint64_t)((((addr & 0x3FFFF) >> 4) | ((1024u >> 4) << 16)) + add) | (0x80000020ull << 32); }
__device__ __forceinline__ void sts128(uint32_t a, uint4 v) { asm volatile("st.shared.v4.u32 [%0], {%1,%2,%3,%4};" :: "r"(a), "r"(v.x), "r"(v.y), "r"(v.z), "r"(v.w) : "memory"); }
__device__ __forceinline__ uint4 lds128(uint32_t a) { uint4 v; asm volatile("ld.shared.v4.u32 {%0,%1,%2,%3}, [%4];" : "=r"(v.x), "=r"(v.y), "=r"(v.z), "=r"(v.w) : "r"(a) : "memory"); return v; }
__device__ __forceinline__ void mma16816(float (&c)[4], uint32_t a0, uint32_t a1, uint32_t a2, uint32_t a3, uint32_t b0, uint32_t b1) {
  asm volatile("mma.sync.aligned.m16n8k16.row.col.f32.bf16.bf16.f32 {%0,%1,%2,%3}, {%4,%5,%6,%7}, {%8,%9}, {%0,%1,%2,%3};"
    : "+f"(c[0]), "+f"(c[1]), "+f"(c[2]), "+f"(c[3]) : "r"(a0), "r"(a1), "r"(a2), "r"(a3), "r"(b0), "r"(b1));
}
__device__ __forceinline__ uint32_t sw_byte(int r, int c) {
  return (uint32_t)((r >> 3) * 4096 + (c >> 6) * 1024 + (r & 7) * 128 + ((((c >> 3) & 7) ^ (r & 7)) << 4) + (c & 7) * 2);
}
__device__ __forceinline__ int cta_id() { int c; asm volatile("mov.u32 %0, %%ctaid.x;" : "=r"(c)); return c; }
__device__ __forceinline__ bool tid_is(int v) { int t; asm volatile("mov.u32 %0, %%tid.x;" : "=r"(t)); return t == v; }
#define STAMP(cond, who, i)
#define CSTAMP(cond, who, i)
#define DUMP(cond, who, i0, i1)
#define XSTAMP(cond, i)
#define SSTAMP(i)

template <int OA, int OB> __device__ __forceinline__ void wgmma_ss_n256_tb(float (&d)[128], uint64_t da, uint64_t db, int scale_d) {
  asm volatile("{\n.reg .pred p;\n.reg .b64 a, b;\nsetp.ne.b32 p, %130, 0;\nadd.s64 a, %128, %131;\nadd.s64 b, %129, %132;\n"
    "wgmma.mma_async.sync.aligned.m64n256k16.f32.bf16.bf16 "
    "{%0, %1, %2, %3, %4, %5, %6, %7, %8, %9, %10, %11, %12, %13, %14, %15, %16, %17, %18, %19, %20, %21, %22, %23, %24, %25, %26, %27, %28, %29, %30, %31, %32, %33, %34, %35, %36, %37, %38, %39, %40, %41, %42, %43, %44, %45, %46, %47, %48, %49, %50, %51, %52, %53, %54, %55, %56, %57, %58, %59, %60, %61, %62, %63, %64, %65, %66, %67, %68, %69, %70, %71, %72, %73, %74, %75, %76, %77, %78, %79, %80, %81, %82, %83, %84, %85, %86, %87, %88, %89, %90, %91, %92, %93, %94, %95, %96, %97, %98, %99, %100, %101, %102, %103, %104, %105, %106, %107, %108, %109, %110, %111, %112, %113, %114, %115, %116, %117, %118, %119, %120, %121, %122, %123, %124, %125, %126, %127}, "
    "a, b, p, 1, 1, 0, 1;\n}\n"
    : "+f"(d[0]), "+f"(d[1]), "+f"(d[2]), "+f"(d[3]), "+f"(d[4]), "+f"(d[5]), "+f"(d[6]), "+f"(d[7]), "+f"(d[8]), "+f"(d[9]), "+f"(d[10]), "+f"(d[11]), "+f"(d[12]), "+f"(d[13]), "+f"(d[14]), "+f"(d[15]), "+f"(d[16]), "+f"(d[17]), "+f"(d[18]), "+f"(d[19]), "+f"(d[20]), "+f"(d[21]), "+f"(d[22]), "+f"(d[23]), "+f"(d[24]), "+f"(d[25]), "+f"(d[26]), "+f"(d[27]), "+f"(d[28]), "+f"(d[29]), "+f"(d[30]), "+f"(d[31]), "+f"(d[32]), "+f"(d[33]), "+f"(d[34]), "+f"(d[35]), "+f"(d[36]), "+f"(d[37]), "+f"(d[38]), "+f"(d[39]), "+f"(d[40]), "+f"(d[41]), "+f"(d[42]), "+f"(d[43]), "+f"(d[44]), "+f"(d[45]), "+f"(d[46]), "+f"(d[47]), "+f"(d[48]), "+f"(d[49]), "+f"(d[50]), "+f"(d[51]), "+f"(d[52]), "+f"(d[53]), "+f"(d[54]), "+f"(d[55]), "+f"(d[56]), "+f"(d[57]), "+f"(d[58]), "+f"(d[59]), "+f"(d[60]), "+f"(d[61]), "+f"(d[62]), "+f"(d[63]), "+f"(d[64]), "+f"(d[65]), "+f"(d[66]), "+f"(d[67]), "+f"(d[68]), "+f"(d[69]), "+f"(d[70]), "+f"(d[71]), "+f"(d[72]), "+f"(d[73]), "+f"(d[74]), "+f"(d[75]), "+f"(d[76]), "+f"(d[77]), "+f"(d[78]), "+f"(d[79]), "+f"(d[80]), "+f"(d[81]), "+f"(d[82]), "+f"(d[83]), "+f"(d[84]), "+f"(d[85]), "+f"(d[86]), "+f"(d[87]), "+f"(d[88]), "+f"(d[89]), "+f"(d[90]), "+f"(d[91]), "+f"(d[92]), "+f"(d[93]), "+f"(d[94]), "+f"(d[95]), "+f"(d[96]), "+f"(d[97]), "+f"(d[98]), "+f"(d[99]), "+f"(d[100]), "+f"(d[101]), "+f"(d[102]), "+f"(d[103]), "+f"(d[104]), "+f"(d[105]), "+f"(d[106]), "+f"(d[107]), "+f"(d[108]), "+f"(d[109]), "+f"(d[110]), "+f"(d[111]), "+f"(d[112]), "+f"(d[113]), "+f"(d[114]), "+f"(d[115]), "+f"(d[116]), "+f"(d[117]), "+f"(d[118]), "+f"(d[119]), "+f"(d[120]), "+f"(d[121]), "+f"(d[122]), "+f"(d[123]), "+f"(d[124]), "+f"(d[125]), "+f"(d[126]), "+f"(d[127])
    : "l"(da), "l"(db), "r"(scale_d), "n"(OA), "n"(OB));
}
template <int OA, int OB> __device__ __forceinline__ void wgmma_qk(float (&d)[64], uint64_t da, uint64_t db, int scale_d) {
  asm volatile("{\n.reg .pred p;\n.reg .b64 a, b;\nsetp.ne.b32 p, %66, 0;\nadd.s64 a, %64, %67;\nadd.s64 b, %65, %68;\n"
    "wgmma.mma_async.sync.aligned.m64n128k16.f32.bf16.bf16 "
    "{%0, %1, %2, %3, %4, %5, %6, %7, %8, %9, %10, %11, %12, %13, %14, %15, %16, %17, %18, %19, %20, %21, %22, %23, %24, %25, %26, %27, %28, %29, %30, %31, %32, %33, %34, %35, %36, %37, %38, %39, %40, %41, %42, %43, %44, %45, %46, %47, %48, %49, %50, %51, %52, %53, %54, %55, %56, %57, %58, %59, %60, %61, %62, %63}, "
    "a, b, p, 1, 1, 0, 0;\n}\n"
    : "+f"(d[0]), "+f"(d[1]), "+f"(d[2]), "+f"(d[3]), "+f"(d[4]), "+f"(d[5]), "+f"(d[6]), "+f"(d[7]), "+f"(d[8]), "+f"(d[9]), "+f"(d[10]), "+f"(d[11]), "+f"(d[12]), "+f"(d[13]), "+f"(d[14]), "+f"(d[15]), "+f"(d[16]), "+f"(d[17]), "+f"(d[18]), "+f"(d[19]), "+f"(d[20]), "+f"(d[21]), "+f"(d[22]), "+f"(d[23]), "+f"(d[24]), "+f"(d[25]), "+f"(d[26]), "+f"(d[27]), "+f"(d[28]), "+f"(d[29]), "+f"(d[30]), "+f"(d[31]), "+f"(d[32]), "+f"(d[33]), "+f"(d[34]), "+f"(d[35]), "+f"(d[36]), "+f"(d[37]), "+f"(d[38]), "+f"(d[39]), "+f"(d[40]), "+f"(d[41]), "+f"(d[42]), "+f"(d[43]), "+f"(d[44]), "+f"(d[45]), "+f"(d[46]), "+f"(d[47]), "+f"(d[48]), "+f"(d[49]), "+f"(d[50]), "+f"(d[51]), "+f"(d[52]), "+f"(d[53]), "+f"(d[54]), "+f"(d[55]), "+f"(d[56]), "+f"(d[57]), "+f"(d[58]), "+f"(d[59]), "+f"(d[60]), "+f"(d[61]), "+f"(d[62]), "+f"(d[63])
    : "l"(da), "l"(db), "r"(scale_d), "n"(OA), "n"(OB));
}
template <int OA, int OB> __device__ __forceinline__ void wgmma_qk(float (&d)[56], uint64_t da, uint64_t db, int scale_d) {
  asm volatile("{\n.reg .pred p;\n.reg .b64 a, b;\nsetp.ne.b32 p, %58, 0;\nadd.s64 a, %56, %59;\nadd.s64 b, %57, %60;\n"
    "wgmma.mma_async.sync.aligned.m64n112k16.f32.bf16.bf16 "
    "{%0, %1, %2, %3, %4, %5, %6, %7, %8, %9, %10, %11, %12, %13, %14, %15, %16, %17, %18, %19, %20, %21, %22, %23, %24, %25, %26, %27, %28, %29, %30, %31, %32, %33, %34, %35, %36, %37, %38, %39, %40, %41, %42, %43, %44, %45, %46, %47, %48, %49, %50, %51, %52, %53, %54, %55}, "
    "a, b, p, 1, 1, 0, 0;\n}\n"
    : "+f"(d[0]), "+f"(d[1]), "+f"(d[2]), "+f"(d[3]), "+f"(d[4]), "+f"(d[5]), "+f"(d[6]), "+f"(d[7]), "+f"(d[8]), "+f"(d[9]), "+f"(d[10]), "+f"(d[11]), "+f"(d[12]), "+f"(d[13]), "+f"(d[14]), "+f"(d[15]), "+f"(d[16]), "+f"(d[17]), "+f"(d[18]), "+f"(d[19]), "+f"(d[20]), "+f"(d[21]), "+f"(d[22]), "+f"(d[23]), "+f"(d[24]), "+f"(d[25]), "+f"(d[26]), "+f"(d[27]), "+f"(d[28]), "+f"(d[29]), "+f"(d[30]), "+f"(d[31]), "+f"(d[32]), "+f"(d[33]), "+f"(d[34]), "+f"(d[35]), "+f"(d[36]), "+f"(d[37]), "+f"(d[38]), "+f"(d[39]), "+f"(d[40]), "+f"(d[41]), "+f"(d[42]), "+f"(d[43]), "+f"(d[44]), "+f"(d[45]), "+f"(d[46]), "+f"(d[47]), "+f"(d[48]), "+f"(d[49]), "+f"(d[50]), "+f"(d[51]), "+f"(d[52]), "+f"(d[53]), "+f"(d[54]), "+f"(d[55])
    : "l"(da), "l"(db), "r"(scale_d), "n"(OA), "n"(OB));
}
template <int OB> __device__ __forceinline__ void wgmma_rs_n256_tb(float (&d)[128], uint32_t a0, uint32_t a1, uint32_t a2, uint32_t a3, uint64_t db, int scale_d) {
  asm volatile("{\n.reg .pred p;\n.reg .b64 b;\nsetp.ne.b32 p, %133, 0;\nadd.s64 b, %132, %134;\n"
    "wgmma.mma_async.sync.aligned.m64n256k16.f32.bf16.bf16 "
    "{%0, %1, %2, %3, %4, %5, %6, %7, %8, %9, %10, %11, %12, %13, %14, %15, %16, %17, %18, %19, %20, %21, %22, %23, %24, %25, %26, %27, %28, %29, %30, %31, %32, %33, %34, %35, %36, %37, %38, %39, %40, %41, %42, %43, %44, %45, %46, %47, %48, %49, %50, %51, %52, %53, %54, %55, %56, %57, %58, %59, %60, %61, %62, %63, %64, %65, %66, %67, %68, %69, %70, %71, %72, %73, %74, %75, %76, %77, %78, %79, %80, %81, %82, %83, %84, %85, %86, %87, %88, %89, %90, %91, %92, %93, %94, %95, %96, %97, %98, %99, %100, %101, %102, %103, %104, %105, %106, %107, %108, %109, %110, %111, %112, %113, %114, %115, %116, %117, %118, %119, %120, %121, %122, %123, %124, %125, %126, %127}, "
    "{%128, %129, %130, %131}, b, p, 1, 1, 1;\n}\n"
    : "+f"(d[0]), "+f"(d[1]), "+f"(d[2]), "+f"(d[3]), "+f"(d[4]), "+f"(d[5]), "+f"(d[6]), "+f"(d[7]), "+f"(d[8]), "+f"(d[9]), "+f"(d[10]), "+f"(d[11]), "+f"(d[12]), "+f"(d[13]), "+f"(d[14]), "+f"(d[15]), "+f"(d[16]), "+f"(d[17]), "+f"(d[18]), "+f"(d[19]), "+f"(d[20]), "+f"(d[21]), "+f"(d[22]), "+f"(d[23]), "+f"(d[24]), "+f"(d[25]), "+f"(d[26]), "+f"(d[27]), "+f"(d[28]), "+f"(d[29]), "+f"(d[30]), "+f"(d[31]), "+f"(d[32]), "+f"(d[33]), "+f"(d[34]), "+f"(d[35]), "+f"(d[36]), "+f"(d[37]), "+f"(d[38]), "+f"(d[39]), "+f"(d[40]), "+f"(d[41]), "+f"(d[42]), "+f"(d[43]), "+f"(d[44]), "+f"(d[45]), "+f"(d[46]), "+f"(d[47]), "+f"(d[48]), "+f"(d[49]), "+f"(d[50]), "+f"(d[51]), "+f"(d[52]), "+f"(d[53]), "+f"(d[54]), "+f"(d[55]), "+f"(d[56]), "+f"(d[57]), "+f"(d[58]), "+f"(d[59]), "+f"(d[60]), "+f"(d[61]), "+f"(d[62]), "+f"(d[63]), "+f"(d[64]), "+f"(d[65]), "+f"(d[66]), "+f"(d[67]), "+f"(d[68]), "+f"(d[69]), "+f"(d[70]), "+f"(d[71]), "+f"(d[72]), "+f"(d[73]), "+f"(d[74]), "+f"(d[75]), "+f"(d[76]), "+f"(d[77]), "+f"(d[78]), "+f"(d[79]), "+f"(d[80]), "+f"(d[81]), "+f"(d[82]), "+f"(d[83]), "+f"(d[84]), "+f"(d[85]), "+f"(d[86]), "+f"(d[87]), "+f"(d[88]), "+f"(d[89]), "+f"(d[90]), "+f"(d[91]), "+f"(d[92]), "+f"(d[93]), "+f"(d[94]), "+f"(d[95]), "+f"(d[96]), "+f"(d[97]), "+f"(d[98]), "+f"(d[99]), "+f"(d[100]), "+f"(d[101]), "+f"(d[102]), "+f"(d[103]), "+f"(d[104]), "+f"(d[105]), "+f"(d[106]), "+f"(d[107]), "+f"(d[108]), "+f"(d[109]), "+f"(d[110]), "+f"(d[111]), "+f"(d[112]), "+f"(d[113]), "+f"(d[114]), "+f"(d[115]), "+f"(d[116]), "+f"(d[117]), "+f"(d[118]), "+f"(d[119]), "+f"(d[120]), "+f"(d[121]), "+f"(d[122]), "+f"(d[123]), "+f"(d[124]), "+f"(d[125]), "+f"(d[126]), "+f"(d[127])
    : "r"(a0), "r"(a1), "r"(a2), "r"(a3), "l"(db), "r"(scale_d), "n"(OB));
}
template <int OB> __device__ __forceinline__ void wgmma_rs_n256_tb_first(float (&d)[128], uint32_t a0, uint32_t a1, uint32_t a2, uint32_t a3, uint64_t db) {
  asm volatile("{\n.reg .pred p;\n.reg .b64 b;\nsetp.ne.b32 p, 0, 0;\nadd.s64 b, %132, %133;\n"
    "wgmma.mma_async.sync.aligned.m64n256k16.f32.bf16.bf16 "
    "{%0, %1, %2, %3, %4, %5, %6, %7, %8, %9, %10, %11, %12, %13, %14, %15, %16, %17, %18, %19, %20, %21, %22, %23, %24, %25, %26, %27, %28, %29, %30, %31, %32, %33, %34, %35, %36, %37, %38, %39, %40, %41, %42, %43, %44, %45, %46, %47, %48, %49, %50, %51, %52, %53, %54, %55, %56, %57, %58, %59, %60, %61, %62, %63, %64, %65, %66, %67, %68, %69, %70, %71, %72, %73, %74, %75, %76, %77, %78, %79, %80, %81, %82, %83, %84, %85, %86, %87, %88, %89, %90, %91, %92, %93, %94, %95, %96, %97, %98, %99, %100, %101, %102, %103, %104, %105, %106, %107, %108, %109, %110, %111, %112, %113, %114, %115, %116, %117, %118, %119, %120, %121, %122, %123, %124, %125, %126, %127}, "
    "{%128, %129, %130, %131}, b, p, 1, 1, 1;\n}\n"
    : "=f"(d[0]), "=f"(d[1]), "=f"(d[2]), "=f"(d[3]), "=f"(d[4]), "=f"(d[5]), "=f"(d[6]), "=f"(d[7]), "=f"(d[8]), "=f"(d[9]), "=f"(d[10]), "=f"(d[11]), "=f"(d[12]), "=f"(d[13]), "=f"(d[14]), "=f"(d[15]), "=f"(d[16]), "=f"(d[17]), "=f"(d[18]), "=f"(d[19]), "=f"(d[20]), "=f"(d[21]), "=f"(d[22]), "=f"(d[23]), "=f"(d[24]), "=f"(d[25]), "=f"(d[26]), "=f"(d[27]), "=f"(d[28]), "=f"(d[29]), "=f"(d[30]), "=f"(d[31]), "=f"(d[32]), "=f"(d[33]), "=f"(d[34]), "=f"(d[35]), "=f"(d[36]), "=f"(d[37]), "=f"(d[38]), "=f"(d[39]), "=f"(d[40]), "=f"(d[41]), "=f"(d[42]), "=f"(d[43]), "=f"(d[44]), "=f"(d[45]), "=f"(d[46]), "=f"(d[47]), "=f"(d[48]), "=f"(d[49]), "=f"(d[50]), "=f"(d[51]), "=f"(d[52]), "=f"(d[53]), "=f"(d[54]), "=f"(d[55]), "=f"(d[56]), "=f"(d[57]), "=f"(d[58]), "=f"(d[59]), "=f"(d[60]), "=f"(d[61]), "=f"(d[62]), "=f"(d[63]), "=f"(d[64]), "=f"(d[65]), "=f"(d[66]), "=f"(d[67]), "=f"(d[68]), "=f"(d[69]), "=f"(d[70]), "=f"(d[71]), "=f"(d[72]), "=f"(d[73]), "=f"(d[74]), "=f"(d[75]), "=f"(d[76]), "=f"(d[77]), "=f"(d[78]), "=f"(d[79]), "=f"(d[80]), "=f"(d[81]), "=f"(d[82]), "=f"(d[83]), "=f"(d[84]), "=f"(d[85]), "=f"(d[86]), "=f"(d[87]), "=f"(d[88]), "=f"(d[89]), "=f"(d[90]), "=f"(d[91]), "=f"(d[92]), "=f"(d[93]), "=f"(d[94]), "=f"(d[95]), "=f"(d[96]), "=f"(d[97]), "=f"(d[98]), "=f"(d[99]), "=f"(d[100]), "=f"(d[101]), "=f"(d[102]), "=f"(d[103]), "=f"(d[104]), "=f"(d[105]), "=f"(d[106]), "=f"(d[107]), "=f"(d[108]), "=f"(d[109]), "=f"(d[110]), "=f"(d[111]), "=f"(d[112]), "=f"(d[113]), "=f"(d[114]), "=f"(d[115]), "=f"(d[116]), "=f"(d[117]), "=f"(d[118]), "=f"(d[119]), "=f"(d[120]), "=f"(d[121]), "=f"(d[122]), "=f"(d[123]), "=f"(d[124]), "=f"(d[125]), "=f"(d[126]), "=f"(d[127])
    : "r"(a0), "r"(a1), "r"(a2), "r"(a3), "l"(db), "n"(OB));
}
template <int OB> __device__ __forceinline__ void wgmma_rs_n128_tb(float (&d)[64], uint32_t a0, uint32_t a1, uint32_t a2, uint32_t a3, uint64_t db, int scale_d) {
  asm volatile("{\n.reg .pred p;\n.reg .b64 b;\nsetp.ne.b32 p, %69, 0;\nadd.s64 b, %68, %70;\n"
    "wgmma.mma_async.sync.aligned.m64n128k16.f32.bf16.bf16 "
    "{%0, %1, %2, %3, %4, %5, %6, %7, %8, %9, %10, %11, %12, %13, %14, %15, %16, %17, %18, %19, %20, %21, %22, %23, %24, %25, %26, %27, %28, %29, %30, %31, %32, %33, %34, %35, %36, %37, %38, %39, %40, %41, %42, %43, %44, %45, %46, %47, %48, %49, %50, %51, %52, %53, %54, %55, %56, %57, %58, %59, %60, %61, %62, %63}, "
    "{%64, %65, %66, %67}, b, p, 1, 1, 1;\n}\n"
    : "+f"(d[0]), "+f"(d[1]), "+f"(d[2]), "+f"(d[3]), "+f"(d[4]), "+f"(d[5]), "+f"(d[6]), "+f"(d[7]), "+f"(d[8]), "+f"(d[9]), "+f"(d[10]), "+f"(d[11]), "+f"(d[12]), "+f"(d[13]), "+f"(d[14]), "+f"(d[15]), "+f"(d[16]), "+f"(d[17]), "+f"(d[18]), "+f"(d[19]), "+f"(d[20]), "+f"(d[21]), "+f"(d[22]), "+f"(d[23]), "+f"(d[24]), "+f"(d[25]), "+f"(d[26]), "+f"(d[27]), "+f"(d[28]), "+f"(d[29]), "+f"(d[30]), "+f"(d[31]), "+f"(d[32]), "+f"(d[33]), "+f"(d[34]), "+f"(d[35]), "+f"(d[36]), "+f"(d[37]), "+f"(d[38]), "+f"(d[39]), "+f"(d[40]), "+f"(d[41]), "+f"(d[42]), "+f"(d[43]), "+f"(d[44]), "+f"(d[45]), "+f"(d[46]), "+f"(d[47]), "+f"(d[48]), "+f"(d[49]), "+f"(d[50]), "+f"(d[51]), "+f"(d[52]), "+f"(d[53]), "+f"(d[54]), "+f"(d[55]), "+f"(d[56]), "+f"(d[57]), "+f"(d[58]), "+f"(d[59]), "+f"(d[60]), "+f"(d[61]), "+f"(d[62]), "+f"(d[63])
    : "r"(a0), "r"(a1), "r"(a2), "r"(a3), "l"(db), "r"(scale_d), "n"(OB));
}
template <int V> using IC = std::integral_constant<int, V>;
template <int I, int N, class F> __device__ __forceinline__ void static_for(F&& f) {
  if constexpr (I < N) { f(std::integral_constant<int, I>{}); static_for<I + 1, N>(f); }
}

constexpr uint32_t SM_Q = 0, SM_BAR = 7 * 32768;
constexpr uint32_t B_FULL = SM_BAR, B_EMPTY = B_FULL + 24, B_WF = B_EMPTY + 24, B_QFULL = B_WF + 32, B_QEMPTY = B_QFULL + 16,
                   B_EVH = B_QEMPTY + 16, B_EVQ = B_EVH + 8, B_EVP0 = B_EVQ + 8, B_BG = B_EVP0 + 16, B_M0 = B_BG + 8, B_HALF = B_M0 + 8,
                   B_HRD = B_HALF + 8, SM_UNSAFE = B_HRD + 8, SM_TS = SM_UNSAFE + 8, SM_ML = (SM_TS + 192 + 15) / 16 * 16, SM_EPOCH = SM_ML + 1024, SM_END = SM_EPOCH + 16;
constexpr uint32_t POS_M = 0x5462;
constexpr int SMEM_BYTES = SM_END;

#define ROW0(u) make_uint4(pack_bf16(o[16 * u], o[16 * u + 1]), pack_bf16(o[16 * u + 4], o[16 * u + 5]), \
                           pack_bf16(o[16 * u + 8], o[16 * u + 9]), pack_bf16(o[16 * u + 12], o[16 * u + 13]))
#define ROW1(u) make_uint4(pack_bf16(o[16 * u + 2], o[16 * u + 3]), pack_bf16(o[16 * u + 6], o[16 * u + 7]), \
                           pack_bf16(o[16 * u + 10], o[16 * u + 11]), pack_bf16(o[16 * u + 14], o[16 * u + 15]))

__global__ void __launch_bounds__(384, 1) gps_kernel(const __grid_constant__ Params P) {
  extern __shared__ __align__(1024) uint8_t smem_raw[];
  constexpr uint32_t sb = 1024;
  if (smem_u32(smem_raw) != sb) return;
  const int cta = blockIdx.x;
  const int wg = __shfl_sync(0xffffffffu, (int)threadIdx.x >> 7, 0);
  const int warp = __shfl_sync(0xffffffffu, ((int)threadIdx.x >> 5) & 3, 0);
  const int lane = threadIdx.x & 31;
#define ROLE                                                                                       \
  const Work& W = P.w[cta_id()];                                                                   \
  [[maybe_unused]] const int n0 = W.nb0 + W.na0, n1 = W.nb1 + W.na1, total = n0 + n1;              \
  [[maybe_unused]] const bool fin = W.role & R_FIN, tail = W.role & R_TAIL;                        \
  [[maybe_unused]] const uint32_t posw = total == 0 || tail ? POS_M : ((total & 1) ? 0x2546 : 0x4326)
  const int g = lane >> 2, t = lane & 3;
  if (wg < 2) {
    const int tid = threadIdx.x & 127;
    ROLE;
    const uint32_t sQ = sb + SM_Q + wg * 32768;
#define st0 tid_is(wg * 128)
    STAMP(st0, wg, 0);
    const int rr = lane >> 3, j = lane & 7;
    const uint4* px[4];
#pragma unroll
    for (int i = 0; i < 4; i++) px[i] = (const uint4*)(P.x + (size_t)min(W.q0 * 128 + wg * 64 + warp * 16 + i * 4 + rr, NN - 1) * 256) + j;
    auto x_load = [&](int c) {
      if (c < 4) {
#pragma unroll
        for (int i = 0; i < 4; i++)
          cp_async16(sQ + warp * 8192 + (i >> 1) * 4096 + c * 1024 + ((i & 1) * 4 + rr) * 128 + ((j ^ ((i & 1) * 4 + rr)) << 4), px[i] + c * 8);
      }
      cp_commit();
    };
    if (total > 0) {
#pragma unroll
      for (int c = 0; c < XD; c++) x_load(c);
    }
    bar_sync(4, 384);
    if (wg == 1) bar_arrive(5, 256);

    const uint32_t sF = sQ + warp * 8192 + ((lane >> 3) & 1) * 4096 + (lane & 7) * 128;
    auto frag = [&](int k) { return sF + (k >> 2) * 1024 + ((((k & 3) * 2 + (lane >> 4)) ^ (lane & 7)) << 4); };
    uint32_t hq[64];
    const bool own = (W.own >> wg) & 1;
    if (total > 0) {
      float c1[4] = {0.f, 0.f, 0.f, 0.f}, ca[4] = {0.f, 0.f, 0.f, 0.f}, cb[4] = {0.f, 0.f, 0.f, 0.f};
#pragma unroll
      for (int k = 0; k < 16; k++) {
        if ((k & 3) == 0) {
          asm volatile("cp.async.wait_group %0;" :: "n"(XD - 1) : "memory");
          __syncwarp();
          x_load(k / 4 + XD);
        }
        ldsm4(frag(k), hq[4 * k], hq[4 * k + 1], hq[4 * k + 2], hq[4 * k + 3]);
        mma16816(c1, hq[4 * k], hq[4 * k + 1], hq[4 * k + 2], hq[4 * k + 3], 0x3f803f80u, 0x3f803f80u);
        mma16816(ca, hq[4 * k], hq[4 * k + 1], hq[4 * k + 2], hq[4 * k + 3], hq[4 * k], hq[4 * k + 2]);
        mma16816(cb, hq[4 * k], hq[4 * k + 1], hq[4 * k + 2], hq[4 * k + 3], hq[4 * k + 1], hq[4 * k + 3]);
      }
      const float mu0 = c1[0] * (1.0f / 256.0f), mu1 = c1[2] * (1.0f / 256.0f);
      const float v0 = fmaf(__shfl_sync(0xffffffffu, g & 1 ? ca[1] : ca[0], g * 4 + (g >> 1)), 1.0f / 256.0f, 1e-5f - mu0 * mu0);
      const float v1 = fmaf(__shfl_sync(0xffffffffu, g & 1 ? cb[3] : cb[2], g * 4 + (g >> 1)), 1.0f / 256.0f, 1e-5f - mu1 * mu1);
      float rs0, rs1;
      asm("rsqrt.approx.ftz.f32 %0, %1;" : "=f"(rs0) : "f"(v0)); asm("rsqrt.approx.ftz.f32 %0, %1;" : "=f"(rs1) : "f"(v1));
      if (W.q0 * 128 + wg * 64 + warp * 16 >= NN) rs0 = rs1 = 0.f;
      float nb0 = -mu0 * rs0, nb1 = -mu1 * rs1;
      const uint32_t sS = sb + SM_ML + (wg * 64 + warp * 16) * 8;
      if (t == 0) {
        asm volatile("st.shared.v2.f32 [%0], {%1,%2};" :: "r"(sS + g * 8), "f"(rs0), "f"(nb0) : "memory");
        asm volatile("st.shared.v2.f32 [%0], {%1,%2};" :: "r"(sS + g * 8 + 64), "f"(rs1), "f"(nb1) : "memory");
      }
      if (__any_sync(0xffffffffu, !(4.f * mu0 * mu0 <= v0) || !(4.f * mu1 * mu1 <= v1))) {
#pragma unroll 1
        for (int r = 0; r < 16; r++) {
          const uint32_t ad = sQ + warp * 8192 + (r >> 3) * 4096 + rr * 1024 + (r & 7) * 128 + ((j ^ (r & 7)) << 4);
          const uint4 v = lds128(ad);
          float f[8] = {bf_lo(v.x), bf_hi(v.x), bf_lo(v.y), bf_hi(v.y), bf_lo(v.z), bf_hi(v.z), bf_lo(v.w), bf_hi(v.w)};
          float sum = 0.f, ss = 0.f, rs;
#pragma unroll
          for (int i = 0; i < 8; i++) sum += f[i];
#pragma unroll 1
          for (int k = 1; k < 32; k *= 2) sum += __shfl_xor_sync(0xffffffffu, sum, k);
          sum *= 1.0f / 256.0f;
#pragma unroll
          for (int i = 0; i < 8; i++) { f[i] -= sum; ss += f[i] * f[i]; }
#pragma unroll 1
          for (int k = 1; k < 32; k *= 2) ss += __shfl_xor_sync(0xffffffffu, ss, k);
          asm("rsqrt.approx.ftz.f32 %0, %1;" : "=f"(rs) : "f"(fmaf(ss, 1.0f / 256.0f, 1e-5f)));
          if (W.q0 * 128 + wg * 64 + warp * 16 >= NN) rs = 0.f;
          sts128(ad, make_uint4(pack_bf16(f[0] * rs, f[1] * rs), pack_bf16(f[2] * rs, f[3] * rs), pack_bf16(f[4] * rs, f[5] * rs), pack_bf16(f[6] * rs, f[7] * rs)));
          if (lane == 0) asm volatile("st.shared.v2.f32 [%0], {%1,%2};" :: "r"(sS + r * 8), "f"(rs), "f"(-sum * rs) : "memory");
        }
        __syncwarp();
#pragma unroll
        for (int k = 0; k < 16; k++) ldsm4(frag(k), hq[4 * k], hq[4 * k + 1], hq[4 * k + 2], hq[4 * k + 3]);
        rs0 = rs1 = 1.f; nb0 = nb1 = 0.f;
      }
      asm volatile("setmaxnreg.inc.sync.aligned.u32 %0;" :: "n"(CREG));
      const uint32_t ah0 = pack_bf16(rs0, rs0), ah1 = pack_bf16(rs1, rs1), n0_ = pack_bf16(nb0, nb0), n1_ = pack_bf16(nb1, nb1);
      const uint32_t al0 = pack_bf16(rs0 - bf_lo(ah0), rs0 - bf_lo(ah0)), al1 = pack_bf16(rs1 - bf_lo(ah1), rs1 - bf_lo(ah1));
#pragma unroll
      for (int i = 0; i < 32; i++) {
        hq[2 * i] = hfma2(hq[2 * i], ah0, hfma2(hq[2 * i], al0, n0_));
        hq[2 * i + 1] = hfma2(hq[2 * i + 1], ah1, hfma2(hq[2 * i + 1], al1, n1_));
      }
      if (own) {
        const float e0 = fmaf(bf_hi(__shfl_sync(0xffffffffu, hq[62], lane | 3)), -0.5f * KS, KC), e1 = fmaf(bf_hi(__shfl_sync(0xffffffffu, hq[63], lane | 3)), -0.5f * KS, KC);
#pragma unroll
        for (int k = 0; k < 16; k++)
          stsm4(frag(k), hfma2(hq[4 * k], KS2, KC2), hfma2(hq[4 * k + 1], KS2, KC2),
                k < 15 ? hfma2(hq[4 * k + 2], KS2, KC2) : pack_bf16(fmaf(bf_lo(hq[62]), KS, e0), t == 3 ? KC : fmaf(bf_hi(hq[62]), KS, e0)),
                k < 15 ? hfma2(hq[4 * k + 3], KS2, KC2) : pack_bf16(fmaf(bf_lo(hq[63]), KS, e1), t == 3 ? KC : fmaf(bf_hi(hq[63]), KS, e1)));
      }
      __syncwarp();
      if (lane == 0) mbar_arrive(sb + B_EVH);
    } else {
      asm volatile("setmaxnreg.inc.sync.aligned.u32 %0;" :: "n"(CREG));
    }
    STAMP(st0, wg, 1);

    float o[128];
    int qph = 0, st = tail ? wg : 0, ph = 0;
    auto release = [&](int stg) { if (lane == 0) mbar_arrive(sb + B_EMPTY + 8 * stg); };
    int resume = total > 0 ? -1 : 0;
    auto fill = [&]() __attribute__((always_inline)) {
#pragma unroll
      for (int i = 0; i < 32; i++)
        asm volatile("ld.volatile.shared.v4.f32 {%0,%1,%2,%3}, [%4];" : "=f"(o[4 * i]), "=f"(o[4 * i + 1]), "=f"(o[4 * i + 2]), "=f"(o[4 * i + 3]) : "r"(sb) : "memory");
    };
    auto finish = [&]() __attribute__((always_inline)) {
      STAMP(st0, wg, 11);
      DUMP(st0, wg, 0, 16);
      if (!P.zero) { asm volatile("exit;"); __builtin_unreachable(); }
      fill();
    };
    auto run = [&](auto hot_) __attribute__((always_inline)) {
    constexpr bool HOT = hot_.value;
    const int nloc = P.w[cta_id()].nloc;
    if (!HOT && resume == 0) {
#pragma unroll 1
      for (int i = 0; i < 32; i++) {
        const int r = i * 8 + wg * 4 + warp;
        cp_async16(sb + ((POS_M >> (r >> 6) * 4) & 15) * 32768 + sw_byte(r & 63, lane * 8), (const uint4*)P.wout + r * 32 + lane);
      }
    }
    bool wide = false;
    if (HOT) {
      reg_fence(hq);
      auto qstep = [&](auto k_) {
        constexpr int k = k_.value;
        if (k < 2 || k % 4 == 0) { mbar_wait(k == 0 ? sb + B_M0 : sb + B_WF + 2 * (k & ~3), 0); if (k == 0 || k == 4) bar_sync(5 + wg, 256); wg_fence(); }
        if constexpr (k == 0) wgmma_rs_n256_tb_first<0>(o, hq[0], hq[1], hq[2], hq[3], desc_m(sb, (POS_M & 15) * 2048));
        else wgmma_rs_n256_tb<(k & 3) * 512>(o, hq[4 * k], hq[4 * k + 1], hq[4 * k + 2], hq[4 * k + 3], desc_m(sb, ((POS_M >> (k & ~3)) & 15) * 2048), 1);
      };
      static_for<0, 4>(qstep);
      wg_commit();
      bar_arrive(6 - wg, 256);
      wg_wait<0>();
      if (!tail) release(0);
      static_for<4, 16>(qstep);
      wg_commit();
      bar_arrive(6 - wg, 256);
      wg_wait<0>();
      reg_fence(o); reg_fence(hq);
      if (!tail) release(1);
      STAMP(st0, wg, 2);
      float c0 = (o[124] + (t == 3 ? 2.f : 1.f) * o[125]) * (-0.5f / 4.5f), c1 = (o[126] + (t == 3 ? 2.f : 1.f) * o[127]) * (-0.5f / 4.5f);
      c0 += __shfl_xor_sync(0xffffffffu, c0, 1); c1 += __shfl_xor_sync(0xffffffffu, c1, 1);
      c0 += __shfl_xor_sync(0xffffffffu, c0, 2); c1 += __shfl_xor_sync(0xffffffffu, c1, 2);
      float r0 = t == 3 ? 0.f : o[125], r1 = t == 3 ? 0.f : o[127], r2 = o[124], r3 = o[126];
#pragma unroll
      for (int i = 0; i < 31; i++) { r2 += o[4 * i]; r0 += o[4 * i + 1]; r3 += o[4 * i + 2]; r1 += o[4 * i + 3]; }
      r0 += r2; r1 += r3;
      r0 += __shfl_xor_sync(0xffffffffu, r0, 1); r1 += __shfl_xor_sync(0xffffffffu, r1, 1);
      r0 += __shfl_xor_sync(0xffffffffu, r0, 2); r1 += __shfl_xor_sync(0xffffffffu, r1, 2);
      r0 = fmaf(c0, -255.f, PSH / KC - r0); r1 = fmaf(c1, -255.f, PSH / KC - r1);
      wide = !(fabsf(c0) <= SAFE_C / KS) || !(fabsf(c1) <= SAFE_C / KS);
      if (own) mbar_wait(sb + B_HRD, 0);
#pragma unroll
      for (int k = 0; k < 16; k++)
        stsm4(frag(k),
              pack_bf16(o[8 * k] + c0, o[8 * k + 1] + c0), pack_bf16(o[8 * k + 2] + c1, o[8 * k + 3] + c1),
              pack_bf16(o[8 * k + 4] + c0, k == 15 && t == 3 ? r0 : o[8 * k + 5] + c0), pack_bf16(o[8 * k + 6] + c1, k == 15 && t == 3 ? r1 : o[8 * k + 7] + c1));
      fence_async_smem();
      __syncwarp();
      STAMP(st0, wg, 3);
      if (tail) { bar_sync(7, 256); if (wg == 0) { release(0); release(1); release(2); } }
      }

    if (HOT || (resume && resume < 4)) {
      ROLE;
      float m0, m1;
      const int qh = tail ? 0 : wg, tl = tail;
      uint32_t qo = qh * 2048;
      const uint32_t ko = (2 - tl) * 2048, stop = 1 + tl + (uint32_t)P.zero;
      float l0, l1;
      auto row_sums = [&]() { l0 = __shfl_sync(0xffffffffu, o[125] + 0.f, lane | 3); l1 = __shfl_sync(0xffffffffu, o[127] + 0.f, lane | 3); };
#define PART(u) make_uint4(pack_bf16(o[8 * u] - l0, o[8 * u + 1] - l0), pack_bf16(o[8 * u + 2] - l1, o[8 * u + 3] - l1), \
                           pack_bf16(o[8 * u + 4] - l0, o[8 * u + 5] - l0), pack_bf16(o[8 * u + 6] - l1, o[8 * u + 7] - l1))
      bool unsafe = !HOT;
      m0 = m1 = 0.f;
#pragma unroll 1
      for (int seg = HOT ? 0 : resume - 1; seg < 2; seg++) {
        ROLE;
        const bool last = __any_sync(0xffffffffu, seg || n1 == 0);
        m0 = m1 = !HOT && unsafe ? -INFINITY : 0.f;
        int first = 1;
        auto tile = [&](auto n_, bool endseg) __attribute__((always_inline)) -> bool {
          constexpr int N = n_.value;
          float s[N / 2]; uint32_t p[N / 4];
          if (!mbar_try_wait(sb + B_FULL + 8 * st, ph)) mbar_wait(sb + B_FULL + 8 * st, ph);
          const bool again = !HOT && N == 112 && first && !seg;
          if (HOT || N == 128) bar_sync(5 + wg, 256);
          else asm volatile("{\n.reg .pred p;\nsetp.eq.u32 p, %1, 0;\n@p bar.sync %0, 256;\n}\n" :: "r"(5 + wg), "r"((uint32_t)again) : "memory");
          wg_fence();
          const uint64_t dQ = desc_k(sb + SM_Q, qo), dK = desc_k(sb, ko + st * 4096);
          qo += (uint32_t)P.zero;
          static_for<0, 16>([&](auto k) { constexpr int kk = (k.value + KROT) & 15, off = (kk >> 2) * 64 + (kk & 3) * 2; wgmma_qk<off, off>(s, dQ, dK, k.value > 0); });
          wg_commit();
          if (HOT || N == 128) bar_arrive(6 - wg, 256);
          else asm volatile("{\n.reg .pred p;\nsetp.eq.u32 p, %1, 0;\n@p bar.arrive %0, 256;\n}\n" :: "r"(6 - wg), "r"((uint32_t)again) : "memory");
          if (HOT && N == 112 && first && !seg) {
            float a0 = 0.f, a1 = 0.f, a2 = 0.f, a3 = 0.f;
#pragma unroll
            for (int i = 0; i < 32; i++) { a0 += o[4 * i] * o[4 * i]; a2 += o[4 * i + 1] * o[4 * i + 1]; a1 += o[4 * i + 2] * o[4 * i + 2]; a3 += o[4 * i + 3] * o[4 * i + 3]; }
            a0 += a2; a1 += a3;
            a0 += __shfl_xor_sync(0xffffffffu, a0, 1); a1 += __shfl_xor_sync(0xffffffffu, a1, 1);
            a0 += __shfl_xor_sync(0xffffffffu, a0, 2); a1 += __shfl_xor_sync(0xffffffffu, a1, 2);
            unsafe = __any_sync(0xffffffffu, bar_red_or(tail ? 7 : 1 + wg, tail ? 256 : 128, wide || !(a0 <= SAFE_N2 / (KS * KS)) || !(a1 <= SAFE_N2 / (KS * KS))));
            if (lane == 0) { asm volatile("st.shared.u8 [%0], %1;" :: "r"(sb + SM_UNSAFE + wg), "r"((uint32_t)unsafe) : "memory"); mbar_arrive(sb + B_EVQ); }
          }
          STAMP(N == 112 && first && !seg && st0, wg, 0);
          wg_wait<0>();
          reg_fence(s);
          if (HOT && N == 112 && unsafe) return true;
          if (endseg) { if (lane == 0) mbar_arrive(sb + B_QEMPTY + 8 * wg); }
          if (!HOT && unsafe) {
            float a0 = fmaxf(s[0], s[1]), a1 = fmaxf(s[2], s[3]);
#pragma unroll
            for (int i = 1; i < N / 8; i++) { a0 = fmaxf(a0, fmaxf(s[4 * i], s[4 * i + 1])); a1 = fmaxf(a1, fmaxf(s[4 * i + 2], s[4 * i + 3])); }
            if (__any_sync(0xffffffffu, (a0 > m0 + TAU) || (a1 > m1 + TAU))) {
              a0 = fmaxf(a0, __shfl_xor_sync(0xffffffffu, a0, 1)); a1 = fmaxf(a1, __shfl_xor_sync(0xffffffffu, a1, 1));
              a0 = fmaxf(a0, __shfl_xor_sync(0xffffffffu, a0, 2)); a1 = fmaxf(a1, __shfl_xor_sync(0xffffffffu, a1, 2));
              const float x0 = ceilf(fmaxf(m0, a0)), x1 = ceilf(fmaxf(m1, a1)), sc0 = ex2(m0 - x0), sc1 = ex2(m1 - x1);
              m0 = x0; m1 = x1;
#pragma unroll
              for (int i = 0; i < 32; i++) { o[4 * i] *= sc0; o[4 * i + 1] *= sc0; o[4 * i + 2] *= sc1; o[4 * i + 3] *= sc1; }
            }
#pragma unroll
            for (int i = 0; i < N / 8; i++) { s[4 * i] -= m0; s[4 * i + 1] -= m0; s[4 * i + 2] -= m1; s[4 * i + 3] -= m1; }
          }
          auto pv = [&](auto k) { wgmma_rs_n256_tb<k.value * 512 + (63 << 16)>(o, p[4 * k.value], p[4 * k.value + 1], p[4 * k.value + 2], p[4 * k.value + 3], dK, k.value > 0 || N == 128 ? 1 : !first); };
#pragma unroll
          for (int i = 0; i < 16; i++) { p[i] = pack_bf16(ex2(s[2 * i]), ex2(s[2 * i + 1])); asm volatile("" : "+r"(p[i]) :: "memory"); }
          reg_fence(o);
          do bar_sync(5 + wg, 256); while (P.zero);
          wg_fence();
          static_for<0, 4>(pv);
          wg_commit();
#pragma unroll
          for (int i = 16; i < N / 4; i++) { p[i] = pack_bf16(ex2(s[2 * i]), ex2(s[2 * i + 1])); asm volatile("" : "+r"(p[i]) :: "memory"); }
          wg_fence();
          static_for<4, N / 16>(pv);
          wg_commit();
          bar_arrive(6 - wg, 256);
          if (N == 128) { wg_wait<1>(); if (endseg && last) { if (lane == 0) mbar_arrive(sb + B_HALF); } }
          wg_wait<0>();
          reg_fence(o); reg_fence(p);
          release(st);
          if (st) { st--; ph ^= 1; } else st = stop;
          return false;
        };
#pragma unroll 1
        for (int left = tail ? 8 - wg : (seg ? W.nb1 : W.nb0); left > 0; left--) { if (tile(IC<112>{}, false)) { resume = 1; return; } STAMP(first && !seg && st0, wg, 4); first = 0; }
#pragma unroll 1
        for (int left = tail ? 32 + wg : (seg ? W.na1 : W.na0); left > 0; left--) tile(IC<128>{}, left == 1);
        STAMP(st0 && last, wg, 6);
        {
        ROLE;
        if (last && fin && !(tail && wg == 1)) break;
        row_sums();
        if (last) mbar_wait(sb + (tail ? B_QEMPTY : B_HALF), 0);
        const uint32_t sp = sb + (tail ? 0 : (last ? (posw >> 12) + wg : (wg ? 4 - 2 * st : 6))) * 32768, sm = sb + SM_ML + (tail ? 0 : wg) * 512;
#pragma unroll
        for (int u = 0; u < 16; u++) sts128(sp + (u * 128 + tid) * 16, PART(u));
        if (t == 0) {
          asm volatile("st.shared.v2.f32 [%0], {%1,%2};" :: "r"(sm + (warp * 16 + g) * 8), "f"(m0), "f"(l0) : "memory");
          asm volatile("st.shared.v2.f32 [%0], {%1,%2};" :: "r"(sm + (warp * 16 + g) * 8 + 64), "f"(m1), "f"(l1) : "memory");
        }
        __syncwarp();
        if (lane == 0) mbar_arrive(sb + B_EVP0 + 8 * wg);
        STAMP(st0 && last, wg, 7);
        if (last) break;
        mbar_wait(sb + B_QFULL + 8 * wg, qph); qph ^= 1;
        uint32_t u; asm volatile("ld.shared.u8 %0, [%1];" : "=r"(u) : "r"(sb + SM_UNSAFE + wg) : "memory");
        unsafe = __any_sync(0xffffffffu, u != 0);
        if (HOT && unsafe) { resume = 2; return; }
        }
      }

      if (P.w[cta_id()].role & R_FIN) {
        ROLE;
        if (!(tail && wg == 1)) {
        row_sums();
        const int rl = wg * 64 + warp * 16 + g;
        uint32_t a[64];
#pragma unroll
        for (int i = 0; i < 64; i++) a[i] = pack_bf16(o[2 * i] - (i & 1 ? l1 : l0), o[2 * i + 1] - (i & 1 ? l1 : l0));
        reg_fence(a);
        {
          float2 e0, e1;
          mbar_wait(sb + B_QFULL + 8 * wg, qph);
          asm volatile("ld.shared.v2.f32 {%0,%1}, [%2];" : "=f"(e0.x), "=f"(e0.y) : "r"(sb + SM_ML + rl * 8) : "memory");
          asm volatile("ld.shared.v2.f32 {%0,%1}, [%2];" : "=f"(e1.x), "=f"(e1.y) : "r"(sb + SM_ML + rl * 8 + 64) : "memory");
          STAMP(st0, wg, 7);
          uint32_t fb0 = 0x3f803f80u, fb1 = 0x3f803f80u;
          const float s0 = l0 + e0.y, s1 = l1 + e1.y;
          const bool odd = __any_sync(0xffffffffu, m0 != e0.x || m1 != e1.x || !(fmaxf(s0, s1) < 0x1p40f) || !(fminf(s0, s1) > 0x1p-40f));
          if (HOT && odd) { resume = 3; return; }
          uint4 v[16];
#pragma unroll
          for (int u = 0; u < 16; u++) v[u] = lds128(sQ + (u * 128 + tid) * 16);
          if (!HOT && odd) {
            const float x0 = fmaxf(m0, e0.x), x1 = fmaxf(m1, e1.x);
            const float d0 = fmaxf(m0 - x0, -1000.f), d1 = fmaxf(m1 - x1, -1000.f), f0 = fmaxf(e0.x - x0, -1000.f), f1 = fmaxf(e1.x - x1, -1000.f);
            l0 = l0 * ex2(d0) + e0.y * ex2(f0); l1 = l1 * ex2(d1) + e1.y * ex2(f1);
            const int E0 = fexp(l0), E1 = fexp(l1);
            const uint32_t fa0 = pow2_bf2((int)d0 - E0), fa1 = pow2_bf2((int)d1 - E1);
            fb0 = pow2_bf2((int)f0 - E0); fb1 = pow2_bf2((int)f1 - E1);
            l0 = __uint_as_float(__float_as_uint(l0) - (E0 << 23)); l1 = __uint_as_float(__float_as_uint(l1) - (E1 << 23));
#pragma unroll
            for (int i = 0; i < 32; i++) { a[2 * i] = hmul2(a[2 * i], fa0); a[2 * i + 1] = hmul2(a[2 * i + 1], fa1); }
          } else { l0 = s0; l1 = s1; }
#pragma unroll
          for (int u = 0; u < 16; u++) {
            a[4 * u] = hfma2(v[u].x, fb0, a[4 * u]); a[4 * u + 1] = hfma2(v[u].y, fb1, a[4 * u + 1]);
            a[4 * u + 2] = hfma2(v[u].z, fb0, a[4 * u + 2]); a[4 * u + 3] = hfma2(v[u].w, fb1, a[4 * u + 3]);
          }
        }
        float fs0, fs1;
        asm("rcp.approx.ftz.f32 %0, %1;" : "=f"(fs0) : "f"(l0 * (KS / KC))); asm("rcp.approx.ftz.f32 %0, %1;" : "=f"(fs1) : "f"(l1 * (KS / KC)));
        STAMP(st0, wg, 8);
        reg_fence(a);
        bar_sync(5 + wg, 256);
        uint64_t dW[4];
        float y0[64], y1[64];
        auto half0 = [&](auto u_) {
          constexpr int u = u_.value;
          if (u % 4 == 0) { mbar_wait(sb + B_WF + 2 * u, 1); wg_fence(); dW[u / 4] = desc_mn(sb, ((posw >> u) & 15) * 2048); }
          wgmma_rs_n128_tb<(u & 3) * 512>(y0, a[4 * u], a[4 * u + 1], a[4 * u + 2], a[4 * u + 3], dW[u / 4], u != 0);
        };
        auto half1 = [&](auto u_) {
          constexpr int u = u_.value;
          wgmma_rs_n128_tb<(u & 3) * 512 + 128>(y1, a[4 * u], a[4 * u + 1], a[4 * u + 2], a[4 * u + 3], dW[u / 4], u != 0);
        };
        const bool wr = W.q0 * 128 + wg * 64 + warp * 16 < NN;
        uint4* po = (uint4*)(P.out + (size_t)(W.q0 * 128 + rl) * 256) + t;
        auto emit = [&](const float* y, uint4* dst) {
          if (wr) {
            red_bf16x8(dst, make_uint4(pack_bf16(y[0] * fs0, y[1] * fs0), pack_bf16(y[4] * fs0, y[5] * fs0), pack_bf16(y[8] * fs0, y[9] * fs0), pack_bf16(y[12] * fs0, y[13] * fs0)));
            red_bf16x8(dst + 8 * 32, make_uint4(pack_bf16(y[2] * fs1, y[3] * fs1), pack_bf16(y[6] * fs1, y[7] * fs1), pack_bf16(y[10] * fs1, y[11] * fs1), pack_bf16(y[14] * fs1, y[15] * fs1)));
          }
          wg_fence();
        };
        static_for<0, 16>(half0);
        wg_commit();
        static_for<0, 4>(half1);
        wg_commit();
        wg_wait<1>();
        reg_fence(y0);
        emit(y0, po); static_for<4, 8>(half1);
        emit(y0 + 16, po + 4); static_for<8, 12>(half1);
        emit(y0 + 32, po + 8); static_for<12, 16>(half1);
        wg_commit();
        bar_arrive(6 - wg, 256);
        emit(y0 + 48, po + 12);
        wg_wait<0>();
        reg_fence(a); reg_fence(y1);
        STAMP(st0, wg, 9);
#pragma unroll
        for (int u = 0; u < 4; u++) emit(y1 + 16 * u, po + 16 + 4 * u);
        }
        if (!tail) { STAMP(st0, wg, 11); DUMP(st0, wg, 0, 16); asm volatile("exit;"); __builtin_unreachable(); }
        if (wg == 1) { bar_sync(6, 256); bar_arrive(5, 256); } else qph ^= 1;
        __syncwarp();
        if (lane == 0) mbar_arrive(sb + B_QEMPTY + 8 * wg);
        fill();
        resume = 4;
      }
        }
#pragma unroll 1
    for (int step = HOT || resume ? 0 : -4; step < (HOT && resume == 4 ? 0 : nloc); step++) {
      ROLE;
      const bool helper = HOT || (resume && resume < 4);
      const bool isw = !HOT && step < 0;
      if (isw) {
        const uint4* src = (const uint4*)(step < -2 ? P.wmsg : P.wv) + ((step & 1) * 128 + wg * 64 + warp) * 32 + lane;
        float cw[8] = {0.f, 0.f, 0.f, 0.f, 0.f, 0.f, 0.f, 0.f};
#pragma unroll 1
        for (int i = 0; i < 16; i++) cp_async16(sQ + sw_byte(i * 4 + warp, lane * 8), src + i * 128);
        cp_commit();
#pragma unroll
        for (int i = 0; i < 8; i++) {
          const uint4 v = __ldg((const uint4*)(step < -2 ? P.wmsg : P.wv) + (248 + i) * 32 + lane);
          const float k = step < -2 ? 0.f : (i == 7 ? -1.0f / 4.5f : -0.5f / 4.5f);
          cw[0] += bf_lo(v.x) * k; cw[1] += bf_hi(v.x) * k; cw[2] += bf_lo(v.y) * k; cw[3] += bf_hi(v.y) * k;
          cw[4] += bf_lo(v.z) * k; cw[5] += bf_hi(v.z) * k; cw[6] += bf_lo(v.w) * k; cw[7] += bf_hi(v.w) * k;
        }
        asm volatile("cp.async.wait_group 0;" ::: "memory");
#pragma unroll 1
        for (int i = 0; i < 16; i++) {
          const uint32_t ad = sQ + sw_byte(i * 4 + warp, lane * 8);
          const uint4 v = lds128(ad);
          uint4 w4 = make_uint4(pack_bf16(bf_lo(v.x) + cw[0], bf_hi(v.x) + cw[1]), pack_bf16(bf_lo(v.y) + cw[2], bf_hi(v.y) + cw[3]),
                                pack_bf16(bf_lo(v.z) + cw[4], bf_hi(v.z) + cw[5]), pack_bf16(bf_lo(v.w) + cw[6], bf_hi(v.w) + cw[7]));
          if (step == -1 && wg * 64 + i * 4 + warp == 127) w4 = make_uint4(0, 0, 0, 0);
          sts128(ad, w4);
        }
        fence_async_smem();
        bar_sync(7, 256);
      } else {
        SSTAMP(0);
        mbar_wait(sb + B_QFULL + 8 * wg, qph); qph ^= 1;
        STAMP(st0 && step == 0, wg, 8);
        SSTAMP(1);
        bar_sync(5 + wg, 256);
        SSTAMP(2);
      }
#pragma unroll 1
      for (int c = 0; c < 4; c++) {
        if (step == 0) mbar_wait(sb + B_WF + 8 * c, helper);
        const int turn2 = helper ? 3 : 4;
        if (c == turn2) bar_sync(5 + wg, 256);
        wg_fence();
        const uint64_t dA = desc_k(sb + SM_Q, wg * 2048 + c * 64), dW = desc_mn(sb, ((posw >> c * 4) & 15) * 2048);
        static_for<0, 4>([&](auto k) { wgmma_ss_n256_tb<k.value * 2, k.value * 512>(o, dA, dW, k.value > 0 ? 1 : c); });
        wg_commit();
        if ((c == 3 || c == turn2 - 1) && !isw) bar_arrive(6 - wg, 256);
        wg_wait<1>();
      }
      wg_wait<0>();
      reg_fence(o);
      {
        STAMP(st0 && step == 0, wg, 9);
        SSTAMP(3);
        if (isw) bar_sync(1 + wg, 128); else if (lane == 0) mbar_arrive(sb + B_QEMPTY + 8 * wg);
        uint8_t* dw = (uint8_t*)(step < -2 ? g_Wmo : g_Wvo) + ((step & 1) * 2 + wg) * 32768 + warp * 8192 + g * 128;
        const int row0 = (W.loc0 + step) * 128 + wg * 64 + warp * 16;
        uint4 r[16];
#pragma unroll
        for (int u = 0; u < 8; u++) { r[2 * u] = ROW0(u); r[2 * u + 1] = ROW1(u); }
        if (isw) {
#pragma unroll
          for (int u = 0; u < 16; u++) *(uint4*)(dw + (u >> 2) * 1024 + ((((u & 2) * 2 + t) ^ g) << 4) + (u & 1) * 4096) = r[u];
        } else if (row0 < NN) {
          uint4* po = (uint4*)(P.out + (size_t)(row0 + g) * 256) + t;
          uint32_t c1 = clk();
#pragma unroll
          for (int u = 0; u < 16; u++) {
            red_bf16x8(po + (u >> 1) * 4 + (u & 1) * 256, r[u]);
            if (!HOT) { c1 += PACE; while ((int)(clk() - c1) < 0) {} }
          }
        }
        if (!HOT && step == -1) { bar_sync(7, 256); if (tid_is(0)) flag_release(F_W); __syncwarp(); STAMP(st0, wg, 3); }
      }
    }
    if (HOT && resume == 4) return;
    finish();
    };
    if (resume < 0) run(std::true_type{});
    else fill();
    run(std::false_type{});
    asm volatile("setmaxnreg.dec.sync.aligned.u32 %0;" :: "n"(504 - 2 * CREG));
  } else {
    STAMP(lane == 0 && warp == 0, 2, 0);
        const int mi = cta >> 3;
    const uint32_t sW = sb + 3 * 32768;
    uint4 wa[4], wb[8];
    {
      const uint4* pq = (const uint4*)(P.wq + ((mi & 15) * 16 + g) * 256) + warp * 8 + t;
      const uint4* pk = (const uint4*)(P.wk + ((cta & 7) * 32 + g) * 256) + warp * 8 + t;
#pragma unroll
      for (int i = 0; i < 4; i++) wa[i] = __ldg(pq + (i >> 1) * 256 + (i & 1) * 4);
#pragma unroll
      for (int i = 0; i < 8; i++) wb[i] = __ldg(pk + (i >> 1) * 256 + (i & 1) * 4);
    }
    if (threadIdx.x == 352) {
      for (int i = 0; i < 3; i++) { mbar_init(sb + B_FULL + 8 * i, 1); mbar_init(sb + B_EMPTY + 8 * i, cta == 130 ? 4 : 8); }
      for (int i = 0; i < 4; i++) mbar_init(sb + B_WF + 8 * i, 1);
      for (int i = 0; i < 2; i++) { mbar_init(sb + B_QFULL + 8 * i, 1); mbar_init(sb + B_QEMPTY + 8 * i, 4); mbar_init(sb + B_EVP0 + 8 * i, 4); }
      mbar_init(sb + B_EVH, 8); mbar_init(sb + B_EVQ, 8); mbar_init(sb + B_HALF, 8); mbar_init(sb + B_BG, 1); mbar_init(sb + B_M0, 1); mbar_init(sb + B_HRD, 1);
      asm volatile("fence.mbarrier_init.release.cluster;" ::: "memory");
    }
    __syncwarp();
    do bar_sync(4, 384); while (P.zero);
    {
#pragma unroll
      for (int n = 0; n < 4; n++) {
        float c[4] = {0.f, 0.f, 0.f, 0.f};
#pragma unroll
        for (int u = 0; u < 2; u++) {
          mma16816(c, wa[u].x, wa[2 + u].x, wa[u].y, wa[2 + u].y, wb[2 * n + u].x, wb[2 * n + u].y);
          mma16816(c, wa[u].z, wa[2 + u].z, wa[u].w, wa[2 + u].w, wb[2 * n + u].z, wb[2 * n + u].w);
        }
        asm volatile("st.shared.v2.f32 [%0], {%1,%2};" :: "r"(sW + ((warp * 16 + g) * 40 + n * 8 + 2 * t) * 4), "f"(c[0]), "f"(c[1]) : "memory");
        asm volatile("st.shared.v2.f32 [%0], {%1,%2};" :: "r"(sW + ((warp * 16 + g + 8) * 40 + n * 8 + 2 * t) * 4), "f"(c[2]), "f"(c[3]) : "memory");
      }
      STAMP(lane == 0 && warp == 0, 2, 7);
      bar_sync(3, 128);
      if (warp < 2) {
        float c[8] = {0.f, 0.f, 0.f, 0.f, 0.f, 0.f, 0.f, 0.f};
#pragma unroll
        for (int k = 0; k < 4; k++) {
          const uint4 v = lds128(sW + ((k * 16 + warp * 8 + g) * 40 + t * 8) * 4), w = lds128(sW + ((k * 16 + warp * 8 + g) * 40 + t * 8 + 4) * 4);
          c[0] += __uint_as_float(v.x); c[1] += __uint_as_float(v.y); c[2] += __uint_as_float(v.z); c[3] += __uint_as_float(v.w);
          c[4] += __uint_as_float(w.x); c[5] += __uint_as_float(w.y); c[6] += __uint_as_float(w.z); c[7] += __uint_as_float(w.w);
        }
        const float ms = 1.4426950408889634f / 16.0f / KS;
        const uint4 m4 = make_uint4(pack_bf16(c[0] * ms, c[1] * ms), pack_bf16(c[2] * ms, c[3] * ms), pack_bf16(c[4] * ms, c[5] * ms), pack_bf16(c[6] * ms, c[7] * ms));
        sts128(sW + 16384 + (warp * 8 + g) * 64 + ((t ^ (g >> 1)) << 4), m4);
      }
    }
    asm volatile("setmaxnreg.dec.sync.aligned.u32 %0;" :: "n"(504 - 2 * CREG));
    STAMP(lane == 0 && warp == 0, 2, 13);
    bar_sync(3, 128);
#define ep1 (lds32(sb + SM_EPOCH) + 1)
    if (threadIdx.x == 256 && cta < 128) {
      fence_async_smem();
      bulk_s2g(g_M + cta * 64, sW + 16384, 1024);
      bulk_commit();
      bulk_wait_all();
      red_relaxed(g_flag + F_M + (cta >> 5));
    }
    __syncwarp();
    ROLE;
    if (warp == 3 && W.own) {
      mbar_wait_w(sb + B_EVH, 0);
      if (W.role < R_SIG) mbar_wait_w(sb + B_WF + 8, 0);
      if (lane == 0) {
        fence_async_smem();
        const int h0 = W.own == 2, nh = W.own == 3 ? 2 : 1;
        bulk_s2g(g_h + W.hp * 4096 + h0 * 2048, sb + SM_Q + h0 * 32768, nh * 32768);
        bulk_s2g(g_stat + W.q0 * 128 + h0 * 64, sb + SM_ML + h0 * 512, nh * 512);
        bulk_commit();
        bulk_wait_read();
        mbar_arrive(sb + B_HRD);
        bulk_wait_all();
        if (W.role >= R_SIG) red_relaxed(g_flag + F_H1 - 1 + W.role / R_SIG);
        red_relaxed(g_flag + F_H);
      }
      __syncwarp();
      STAMP(lane == 0, 2, 6);
    }
    if (warp == 0) {
      if (lane == 0) {
        STAMP(true, 2, 1);
        const uint32_t epoch = ld_relaxed(g_flag + F_EPOCH);
        if (total > 0) {
#pragma unroll
          for (int c = 0; c < 3; c++) mbar_expect_tx(sb + B_WF + 8 * c, c == 0 ? WCH_B - 8192 : WCH_B);
          mbar_expect_tx(sb + B_M0, 8192);
          int c = 0;
#pragma unroll 1
          for (uint32_t it = 0; c < 4; it++) {
            uint4 f;
            asm volatile("ld.relaxed.gpu.global.v4.u32 {%0,%1,%2,%3}, [%4];" : "=r"(f.x), "=r"(f.y), "=r"(f.z), "=r"(f.w) : "l"(g_flag + F_M) : "memory");
            uint32_t tm;
            asm volatile("mad.lo.u32 %0, %1, 32, 32;" : "=r"(tm) : "r"(epoch));
            int ok = (int)(f.x - tm) < 0 ? 0 : (int)(f.y - tm) < 0 ? 1 : (int)(f.z - tm) < 0 ? 2 : (int)(f.w - tm) < 0 ? 3 : 4;
            if (it > (1u << 23)) ok = 4;
            if (ok > c) {
              asm volatile("fence.acquire.gpu;" ::: "memory"); fence_async_gmem();
              if (c == 0) bulk_g2s(sb + (POS_M & 15) * 32768, g_M, 8192, sb + B_M0);
            }
#pragma unroll 1
            for (; c < ok; c++) {
              const uint32_t skip = c == 0 ? 8192 : 0;
              bulk_g2s(sb + ((POS_M >> c * 4) & 15) * 32768 + skip, pofs<const uint8_t>(g_M, c * WCH_B + skip), WCH_B - skip, sb + B_WF + 8 * c);
              STAMP(c == 0, 2, 2);
            }
          }
        }
        asm volatile("st.shared.u32 [%0], %1;" :: "r"(sb + SM_EPOCH), "r"(epoch) : "memory");
        if (total > 0) mbar_expect_tx(sb + B_WF + 24, WCH_B);
        int st = 0, ph = 0, qph = 0;
        const int nsl = tail ? 3 : 2;
        auto next_slot = [&]() { mbar_wait(sb + B_EMPTY + 8 * st, ph); if (++st == nsl) { st = 0; ph ^= 1; } };
        const uint4* wsrc = fin ? g_Wvo : g_Wmo;
        auto w_load = [&](int c0, int c1) {
#pragma unroll 1
          for (int c = c0; c < c1; c++) {
            mbar_expect_tx(sb + B_WF + 8 * c, WCH_B);
            bulk_g2s(sb + ((posw >> c * 4) & 15) * 32768, pofs<const uint8_t>(wsrc, c * WCH_B), WCH_B, sb + B_WF + 8 * c);
          }
        };
        auto q_load = [&](const uint4* src, bool wait_empty) {
#pragma unroll 1
          for (int h = 0; h < 2; h++) {
            if (wait_empty) mbar_wait(sb + B_QEMPTY + 8 * h, qph);
            mbar_expect_tx(sb + B_QFULL + 8 * h, 32768);
            bulk_g2s_last(sb + SM_Q + h * 32768, src + h * 2048, 32768, sb + B_QFULL + 8 * h);
          }
          if (wait_empty) qph ^= 1;
        };
        auto part_out = [&](int slot, int h, uint32_t region, int parity) {
          mbar_wait(sb + B_EVP0 + 8 * h, parity);
          fence_async_smem();
          bulk_s2g(g_part + slot * 4096 + h * 2048, sb + region * 32768, 32768);
          bulk_s2g(g_ml + slot * 128 + h * 64, sb + SM_ML + h * 512, 512);
          bulk_commit();
        };
        auto announce = [&](int f) {
          red_relaxed(g_flag + f);
        };
        if (total > 0) {
          STAMP(true, 2, 3);
          const int q1 = W.q0 + 2 * W.own - 3;
          if (!tail) { flag_wait(F_H1 + (fin ? 0 : W.own), (epoch + 1) * (fin ? NH1_0 : (W.own == 1 ? NH1_1 : NH1_2))); fence_async_gmem(); }
          STAMP(true, 2, 4);
          uint32_t ko = W.k0 * 8192;
#pragma unroll 1
          for (int j = 0; j < total; j++) {
            if (j == (tail ? 0 : 1)) { flag_wait(F_H, (epoch + 1) * NHSIG); fence_async_gmem(); }
            if (j == n0) {
              flag_wait(F_QP + q1 * LN_, (epoch + 1)); fence_async_gmem();
              const uint32_t u = __ldcg(g_unsafe + q1);
              asm volatile("st.shared.u32 [%0], %1;" :: "r"(sb + SM_UNSAFE), "r"(u) : "memory");
              ko = W.k1 * 8192;
            }
            if (j == n0 + 1) q_load(g_qp + q1 * 4096, true);
            if (j == total - 1) { flag_wait(F_W, (epoch + 1)); fence_async_gmem(); if (!tail) w_load(0, 1); }
            const uint32_t bytes = (j < n0 ? j < W.nb0 : j - n0 < W.nb1) ? 112 * 512 : 128 * 512, s0 = st;
            const uint32_t region = (tail ? 1 : 2) + 2 * s0, skip = j == n0 + 1 ? 32768 : 0;
            if (skip) part_out(W.slotA, 0, 6, 0);
            next_slot();
            mbar_expect_tx(sb + B_FULL + 8 * s0, bytes);
            bulk_g2s(sb + region * 32768 + skip, pofs<const uint8_t>(g_h, ko + skip), bytes - skip, sb + B_FULL + 8 * s0);
            if (skip) {
              part_out(W.slotA, 1, region, 0);
              bulk_wait_read();
              bulk_g2s(sb + region * 32768, pofs<const uint8_t>(g_h, ko), skip, sb + B_FULL + 8 * s0);
              bulk_wait_all();
              announce(F_PART + W.slotA * LN_);
            }
            ko += bytes;
          }
          next_slot();
          if (tail) { next_slot(); next_slot(); }
        } else { flag_wait(F_W, (epoch + 1)); fence_async_gmem(); }
        STAMP(true, 2, 5);
        const bool staged = total > 0 && !tail;
        w_load(staged, staged ? (fin ? 2 : 3) : 4);
        if (tail) {
          mbar_wait(sb + B_BG, 0); mbar_wait(sb + B_EVP0 + 8, 0); mbar_arrive(sb + B_QFULL);
          qph = 1; wsrc = g_Wmo;
          mbar_wait(sb + B_QEMPTY, 1);
          w_load(0, 4);
        }
#pragma unroll 1
        for (int i = 0; i < W.nloc; i++) {
          const int tl = W.loc0 + i, last = tl * 128 + 127 < NN ? tl * 128 + 127 : NN - 1;
          flag_wait(F_AGG + ((last >= NGW) + (last >= 4 * NGW) + (last >= 9 * NGW)) * LN_, (epoch + 1) * NGW); fence_async_gmem();
          if (total == 0) g_flag[F_EPOCH] = epoch + 1;
          q_load(g_agg + tl * 4096, total > 0 || i > 0);
        }
        if (fin && !tail) {
          int h = 0, c = 2, have = W.slotB >= 0 ? 2 : 0;
          mbar_wait(sb + B_BG, 0);
#pragma unroll 1
          for (uint32_t it = 0; (h < 2 || c < 4) && it < (1u << 23); it++) {
            if (have < 2) {
              uint2 f;
              asm volatile("ld.relaxed.gpu.global.v2.u32 {%0,%1}, [%2];" : "=r"(f.x), "=r"(f.y) : "l"(g_flag + F_PART + W.slotA * LN_) : "memory");
              have = (int)(f.x - (epoch + 1)) < 0 ? 0 : ((int)(f.y - (epoch + 1)) < 0 ? 1 : 2);
            }
            if (h < have && mbar_try_wait_nb(sb + B_QEMPTY + 8 * h, 0)) {
              asm volatile("fence.acquire.gpu;" ::: "memory"); fence_async_gmem();
              STAMP(true, 2, 14 + h);
              mbar_expect_tx(sb + B_QFULL + 8 * h, 32768 + 512);
              bulk_g2s(sb + SM_ML + h * 512, g_ml + W.slotA * 128 + h * 64, 512, sb + B_QFULL + 8 * h);
              bulk_g2s(sb + SM_Q + h * 32768, g_part + W.slotA * 4096 + h * 2048, 32768, sb + B_QFULL + 8 * h);
              h++;
            }
            const bool half = mbar_try_wait_nb(sb + B_HALF, 0);
            const int c1 = half ? 4 : (h > 0 ? 3 : 2);
            if (c < c1) { w_load(c, c1); c = c1; }
          }
        } else if (!fin && total > 0) {
#pragma unroll 1
          for (int h = 0; h < 2; h++) part_out(W.slotB, h, (posw >> 12) + h, 1);
          asm volatile("cp.async.bulk.wait_group.read 1;" ::: "memory");
          w_load(3, 4);
          asm volatile("cp.async.bulk.wait_group 1;" ::: "memory");
          announce(F_PART + W.slotB * LN_);
          STAMP(true, 2, 14);
          bulk_wait_all();
          announce(F_PART + W.slotB * LN_ + 1);
          STAMP(true, 2, 15);
        }
        DUMP(true, 2, 14, 16);
        DUMP(true, 2, 0, 8);
      }
      return;
    }
  }
    {
      const int gw = cta * 3 + warp - 1;
      ROLE;
      if (total > 0) {
        mbar_wait_w(sb + B_EVQ, 0);
        const uint32_t c0 = clk();
        if (warp == 1 && (W.role & R_PUB)) {
          g_unsafe[W.q0] = lds32(sb + SM_UNSAFE);
#pragma unroll 1
          for (int k = 0; k < 4; k++) {
            __nanosleep(2000);
            if (lane == 0) bulk_s2g(pofs<uint4>(g_qp, W.q0 * 65536 + k * 16384), sb + SM_Q + k * 16384, 16384);
            bulk_commit();
          }
          bulk_wait_all();
          flag_release_w(F_QP + W.q0 * LN_);
        }
        while (__any_sync(0xffffffffu, clk() - c0 < GSTART)) __nanosleep(500);
        STAMP(lane == 0 && warp == 1, 2, 8);
#define ovf_cnt pofs<uint32_t>(g_flag, (F_OVF + (ep1 & 1) * LN_) * 4)
        if (gw == 0) g_flag[F_OVF + ((ep1 + 1) & 1) * LN_] = 0;
#pragma unroll 1
        for (int e0 = gw * 32; e0 < NE; e0 += NGW * 32 * 7) {
          int d[7], s[7], pos[7];
          const int* pd = pofs<const int>(P.dst, (e0 + lane) * 4);
          const int* ps = pofs<const int>(P.src, (e0 + lane) * 4);
#pragma unroll
          for (int k = 0; k < 7; k++) { const bool ok = e0 + k * NGW * 32 < NE; d[k] = ok ? __ldcs(pd + k * NGW * 32) : -1; s[k] = ok ? __ldcs(ps + k * NGW * 32) : 0; }
          uint32_t ov = 0;
#pragma unroll
          for (int k = 0; k < 7; k++) {
            pos[k] = 0;
            if (d[k] >= 0) asm volatile("atom.relaxed.gpu.global.add.u32 %0, [%1], 1;" : "=r"(pos[k]) : "l"(pofs<int>(g_cnt, d[k] << 2)) : "memory");
            s[k] = (uint32_t)(uintptr_t)g_u + s[k] * 512;
            if (d[k] >= 0 && pos[k] < CAP) asm volatile("st.volatile.global.u32 [%0], %1;" :: "l"(pofs<int>(g_bin, (d[k] * CAPS + pos[k]) << 2)), "r"(s[k]) : "memory");
            ov |= (pos[k] >= CAP) << k;
          }
          if (__any_sync(0xffffffffu, ov != 0)) {
            uint32_t at;
            asm volatile("atom.relaxed.gpu.global.add.u32 %0, [%1], %2;" : "=r"(at) : "l"(ovf_cnt), "r"(__popc(ov)) : "memory");
#pragma unroll
            for (int k = 0; k < 7; k++) if ((ov >> k) & 1) g_ovf[at++] = make_int2(d[k], s[k]);
          }
        }
        flag_wait_w(F_H, ep1 * NHSIG);
#pragma unroll 1
        for (int n0 = gw; n0 < NN; n0 += 4 * NGW) {
          uint4 xv[4]; float2 st[4];
#pragma unroll
          for (int k = 0; k < 4; k++) {
            const int n = n0 + k * NGW < NN ? n0 + k * NGW : n0;
            xv[k] = ldcs_v(pofs<const uint4>(P.x, n * 512 + lane * 16));
            st[k] = __ldcg(pofs<const float2>(g_stat, n * 8));
          }
#pragma unroll
          for (int k = 3; k >= 0; k--) {
            const int n = n0 + k * NGW;
            const float a = st[k].x * US, c = fmaf(st[k].y, US, UB + 8388608.0f);
#define FIX(w) __byte_perm(__float_as_uint(fmaf(bf_lo(w), a, c)), __float_as_uint(fmaf(bf_hi(w), a, c)), 0x5410)
            if (n < NN) {
              *pofs<uint4>(P.out, n * 512 + lane * 16) = xv[k];
              *pofs<uint4>(g_u, n * 512 + lane * 16) = make_uint4(FIX(xv[k].x), FIX(xv[k].y), FIX(xv[k].z), FIX(xv[k].w));
            }
          }
        }
        flag_release_w(F_BIN);
        STAMP(lane == 0 && warp == 1, 2, 9);
        flag_wait_w(F_BIN, ep1 * NGW);
        STAMP(lane == 0 && warp == 1, 2, 10);
        const int myn = gw + lane * NGW < NN ? gw + lane * NGW : gw;
        int cnts = __ldcg(g_cnt + myn);
        cnts = gw + lane * NGW < NN ? (cnts > CAP ? CAP + 1 : cnts) | ((int)__ldg((const unsigned short*)P.dinv + myn) << 16) : 0;
        __syncwarp();
        g_cnt[myn] = 0;
        const uint32_t uhi = (uintptr_t)g_u >> 32, lx = lane * 16;
        uint32_t obin = gw * CAPS * 4;
        uint32_t ent = __ldcg(pofs<const uint32_t>(g_bin, obin + lane * 4)), entn = __ldcg(pofs<const uint32_t>(g_bin, obin + NGW * CAPS * 4 + lane * 4));
        int cd = __shfl_sync(0xffffffffu, cnts, 0), cb = min(cd & 0xffff, CAP), e = 0;
        uint32_t sa[4] = {0, 0, 0, 0}, sh[4] = {0, 0, 0, 0};
        auto add = [&](uint32_t x, uint32_t y, uint32_t z, uint32_t w) {
          sa[0] += x; sa[1] += y; sa[2] += z; sa[3] += w;
          sh[0] += x >> 16; sh[1] += y >> 16; sh[2] += z >> 16; sh[3] += w >> 16;
        };
        int rnd = -1, rows = -1, cdo = 0;
#pragma unroll 1
        for (;;) {
          const bool hold = rows >= 0 && rnd == 8;
          const int m = hold ? 0 : cb - e;
          uint4 v[8];
          if (m >= 8) {
#pragma unroll
            for (int k = 0; k < 8; k++) v[k] = ldcg_v(addr64(__shfl_sync(0xffffffffu, ent, k) + lx, uhi));
          } else {
#pragma unroll
            for (int k = 0; k < 8; k++) {
              v[k] = make_uint4(0, 0, 0, 0);
              if (k < 7) ldcg_if(v[k], addr64(__shfl_sync(0xffffffffu, ent, k) + lx, uhi), k < m);
            }
          }
          if (rows >= 0) {
            const int n = gw + rnd * NGW;
            if (n < NN) {
              const float di = __uint_as_float(cdo & 0xffff0000u) * (1.0f / US), nl = -di * UB * (float)rows;
#define AGG(k) pack_bf16(fmaf((float)(sa[k] - (sh[k] << 16)), di, nl), fmaf((float)sh[k], di, nl))
              *pofs<uint4>(g_agg, ((n >> 3) * 4096 + (n & 7) * 144) ^ ((lx & 0x70) | ((lx & 0x180) << 3))) = make_uint4(AGG(0), AGG(1), AGG(2), AGG(3));
            }
#pragma unroll
            for (int k = 0; k < 4; k++) sa[k] = sh[k] = 0;
            rows = -1;
            if (rnd == 0 || rnd == 3 || rnd == 8 || rnd == NRND - 1) flag_release_w(F_AGG + ((rnd > 0) + (rnd > 3) + (rnd > 8)) * LN_);
            if (rnd == NRND - 1) break;
            if (hold) {
              if (fin && W.slotB >= 0) {
        #pragma unroll 1
                for (int k = 0; k < 2; k++) flag_wait_w(F_PART + (k ? W.slotB : W.slotA) * LN_, ep1);
        #pragma unroll 1
                for (int b = warp - 1; b < 8; b += 3) {
                  float2* ma = g_ml + W.slotA * 128 + b * 16 + g;
                  const float2* mb = g_ml + W.slotB * 128 + b * 16 + g;
                  const float2 a0 = __ldcg(ma), a1 = __ldcg(ma + 8), b0 = __ldcg(mb), b1 = __ldcg(mb + 8);
                  const float x0 = fmaxf(a0.x, b0.x), x1 = fmaxf(a1.x, b1.x);
                  const float fa0 = ex2(a0.x - x0), fa1 = ex2(a1.x - x1), fb0 = ex2(b0.x - x0), fb1 = ex2(b1.x - x1);
                  __syncwarp();
                  if (t == 0) { ma[0] = make_float2(x0, a0.y * fa0 + b0.y * fb0); ma[8] = make_float2(x1, a1.y * fa1 + b1.y * fb1); }
                  const uint32_t ofs = ((b >> 2) * 2048 + (b & 3) * 32 + lane) * 16;
        #pragma unroll 1
                  for (int u = 0; u < 16; u += 4) {
                    uint4* pa = pofs<uint4>(g_part, W.slotA * 65536 + ofs + u * 2048);
                    const uint4* pb = pofs<const uint4>(g_part, W.slotB * 65536 + ofs + u * 2048);
                    uint4 va[4], vb[4];
        #pragma unroll
                    for (int k = 0; k < 4; k++) { va[k] = ldcg_v(pa + k * 128); vb[k] = ldcs_v(pb + k * 128); }
        #define FOLD(w, fa, fb) pack_bf16(bf_lo(va[k].w) * fa + bf_lo(vb[k].w) * fb, bf_hi(va[k].w) * fa + bf_hi(vb[k].w) * fb)
        #pragma unroll
                    for (int k = 3; k >= 0; k--) pa[k * 128] = make_uint4(FOLD(x, fa0, fb0), FOLD(y, fa1, fb1), FOLD(z, fa0, fb0), FOLD(w, fa1, fb1));
                  }
                }
                bar_sync(3, 96);
                if (warp == 1) asm volatile("fence.acq_rel.gpu;" ::: "memory");
              }
              if (fin && warp == 1 && lane == 0) mbar_arrive(sb + B_BG);
              while (__any_sync(0xffffffffu, clk() - c0 < GPAUSE)) __nanosleep(500);
              continue;
            }
          }
#define SUM8(f) (v[7].f + v[6].f + v[5].f + v[4].f + v[3].f + v[2].f + v[1].f + v[0].f)
          add(SUM8(x), SUM8(y), SUM8(z), SUM8(w));
          e += 8;
          if (e < cb) {
            ent = __shfl_down_sync(0xffffffffu, ent, 8);
            if (e == 32) ent = __ldcg(pofs<const uint32_t>(g_bin, obin + 128 + lx / 4));
            continue;
          }
          rnd++; rows = cb; cdo = cd;
          if ((cd & 0xffff) > CAP) {
            const int no = __shfl_sync(0xffffffffu, (int)ld_relaxed(ovf_cnt), 0);
#pragma unroll 1
            for (int i0 = 0; i0 < no; i0 += 32) {
              int2 en = __ldcg(g_ovf + min(i0 + lane, no - 1));
              uint32_t mk = __ballot_sync(0xffffffffu, en.x == gw + rnd * NGW && i0 + lane < no);
              rows += __popc(mk);
#pragma unroll 1
              while (mk) {
                const int bit = __ffs(mk) - 1; mk &= mk - 1;
                const uint4 r = ldcg_v(addr64((uint32_t)__shfl_sync(0xffffffffu, en.y, bit) + lx, uhi));
                add(r.x, r.y, r.z, r.w);
              }
            }
          }
          obin += NGW * CAPS * 4;
          ent = entn; entn = __ldcg(pofs<const uint32_t>(g_bin, obin + NGW * CAPS * 4 + lx / 4));
          cd = __shfl_sync(0xffffffffu, cnts, rnd + 1); cb = min(cd & 0xffff, CAP); e = 0;
        }
      }
      STAMP(lane == 0 && warp == 1, 2, 11);
      if (warp == 2 && fin && lane == 0) {
        prefetch_l2(pofs<uint8_t>(P.out, W.q0 * 65536), tail ? 8192 : 65536);
        if (W.slotB >= 0) prefetch_l2(pofs<uint8_t>(g_part, W.slotA * 65536), 65536);
        prefetch_l2(pofs<uint8_t>(g_Wvo, (cta & 63) * 4096), 4096);
      }
      DUMP(warp == 1 && lane == 0, 2, 8, 14);
    }
}

}

extern "C" void kernel_launch(void* const* d_in, const int* in_sizes, int n_in, void* d_out, int out_size) {
  Params P;
  P.x = (const __nv_bfloat16*)d_in[0];
  P.src = (const int*)d_in[1];
  P.dst = (const int*)d_in[2];
  P.dinv = (const __nv_bfloat16*)d_in[3];
  P.wmsg = (const __nv_bfloat16*)d_in[4];
  P.wq = (const __nv_bfloat16*)d_in[5];
  P.wk = (const __nv_bfloat16*)d_in[6];
  P.wv = (const __nv_bfloat16*)d_in[7];
  P.wout = (const __nv_bfloat16*)d_in[8];
  P.out = (__nv_bfloat16*)d_out;
  P.zero = 0;
  for (int c = 0; c < NCTA; c++) P.w[c] = make_work(c);
  static void* scr = nullptr;
  if (!scr) {
    cudaFuncSetAttribute(gps_kernel, cudaFuncAttributeMaxDynamicSharedMemorySize, SMEM_BYTES);
    cudaGetSymbolAddress(&scr, g_scr);
  }
  P.s = (Scratch*)((((uintptr_t)scr + SCR_ALIGN - 1) & ~(uintptr_t)(SCR_ALIGN - 1)) + SCR_OFS);
  P.u = (uint4*)(((uintptr_t)P.s->u + 511) & ~(uintptr_t)511);
  if (((uintptr_t)P.u >> 32) != (((uintptr_t)(P.u + NN * 32) - 1) >> 32)) P.u += NN * 32;
  gps_kernel<<<NCTA, 384, SMEM_BYTES>>>(P);
}
```

```cpp
#include <cuda_runtime.h>
#include <cuda_bf16.h>
#include <stdint.h>
#include <stddef.h>
#include <type_traits>
#define FB 5
#define MB 5
#define GSTART 40000
#define XD 3
#define NTAIL 5
#define PACE 64
#define GPAUSE 112000
#define CREG 224
#define BACKOFF 1000

namespace {

constexpr int NN = 10000;
constexpr int NE = 160000;
constexpr int NQT = 79;
constexpr int NCTA = 132;
constexpr int CAP = 64;
constexpr int CAPS = 64;
constexpr int NHSIG = 105;
constexpr uint32_t WCH_B = 32768;
constexpr int NGW = (NCTA - 1) * 3;
constexpr float TAU = 16.0f;
constexpr float SAFE_N2 = 36.0f, SAFE_C = 0.6f;
#define KOFF 3
#define PSH -8.0f
#define KROT 15
constexpr float US = 256.0f, UB = 4095.0f;
constexpr float KS = 0.25f, KC = KOFF * KS;
constexpr uint32_t KS2 = 0x3e803e80u, KC2 = KOFF == 2 ? 0x3f003f00u : (KOFF == 1 ? 0x3e803e80u : 0x3f403f40u);

constexpr int NAGG = 4;
constexpr int NRND = (NN + NGW - 1) / NGW;
constexpr int NSLOT = 105;
constexpr int F_EPOCH = 0, F_H = 1, F_M = 4  , F_H1 = 8  , LN_ = 32;
constexpr int F_BIN = LN_, F_W = 2 * LN_, F_OVF = 3 * LN_  , F_QP = 5 * LN_, F_AGG = F_QP + NQT * LN_,
              F_PART = F_AGG + NAGG * LN_, F_END = F_PART + NSLOT * LN_;

struct Scratch {
  uint32_t flag[F_END];
  alignas(4096) uint4 M[8192];
  uint4 Wvo[8192], Wmo[8192];
  float2 ml[NSLOT * 128];
  uint32_t unsafe[96];
  int cnt[NN + 32];
  float2 stat[NQT * 128];
  alignas(4096) uint4 h[NQT * 4096];
  uint4 u[2 * NN * 32 + 32];
  uint4 qp[NQT * 4096];
  uint4 agg[NQT * 4096];
  uint4 part[NSLOT * 4096];
  int bin[NN * CAPS];
  int2 ovf[NE];
};
static_assert(offsetof(Scratch, h) % 128 == 0, "alignment");
#define SCR_ALIGN (2u << 20)
#define SCR_OFS 0
__device__ uint4 g_scr[(sizeof(Scratch) + SCR_ALIGN + SCR_OFS) / 16];
struct alignas(16) Work { short k0, k1; signed char q0, hp, nb0, na0, nb1, na1, slotA, slotB, loc0, nloc, own, role; };
constexpr int R_FIN = 1, R_PUB = 2, R_TAIL = 4, R_SIG = 8  ;
struct Params {
  const __nv_bfloat16 *x, *wq, *wk;
  Scratch* s;
  uint4* u;
  __nv_bfloat16* out;
  const __nv_bfloat16 *wout, *wmsg, *wv, *dinv;
  const int *src, *dst;
  long long zero;
  Work w[NCTA];
};
constexpr int first_cnt(int k) { return 2 * ((k + 6) / 8 - k / 8 + 1); }
constexpr int NH1_0 = 2, NH1_1 = first_cnt(48 * 8 - MB), NH1_2 = first_cnt(48 * 8 - MB + 16 * 8 - (15 - MB) / 2);
constexpr int NSERV = NQT - 52;
inline Work make_work(int c) {
  Work w;
  const int gi = c / 5, r = c % 5, q = gi * 3;
  const bool helper = r & 1, mid = r == 2;
  w.q0 = helper ? q + 1 : q + (r >> 1);
  const int hb1 = (15 - MB) / 2, hb3 = 15 - MB - hb1;
  w.nb0 = helper ? (r == 1 ? hb1 : hb3) : (mid ? MB : FB);
  w.na0 = (helper ? 16 : 48) - w.nb0;
  w.k0 = helper ? (48 * 8 - MB) + (r >> 1) * (16 * 8 - hb1) : 0;
  w.k1 = 48 * 8 - FB;
  w.nb1 = helper ? (FB < 7 ? 7 : 15) - FB : 0;
  w.na1 = helper ? (FB < 7 ? 31 : 32) - w.nb1 : 0;
  w.slotA = 4 * gi + (helper ? r - 1 : (mid ? 0 : (r >> 1) + 1));
  w.slotB = helper ? 4 * gi + r : (mid ? 4 * gi + 2 : -1);
  w.loc0 = NSERV + gi * 2 + (r >> 1);
  w.nloc = helper;
  w.own = helper ? (r + 1) >> 1 : (mid ? 0 : 3);
  w.role = helper ? 0 : (mid ? R_FIN : R_FIN | R_PUB);
  const int k1st[3] = {0, 48 * 8 - MB, 48 * 8 - MB + 16 * 8 - hb1};
  int pos[NQT], sig[NQT];
  for (int i = 0; i < NQT; i++) { pos[i] = i; sig[i] = 0; }
  for (int i = 0; i < 3; i++)
    for (int p = k1st[i] / 8; p <= (k1st[i] + 6) / 8; p++) {
      int m = 1, at = 0;
      while (sig[m]) m += 3;
      while (pos[at] != p) at++;
      pos[at] = pos[m]; pos[m] = p; sig[m] = 1 + i;
    }
  w.hp = c < 131 ? pos[w.q0] : 0;
  if (helper && c < 130) w.role |= sig[w.q0] * R_SIG;
  if (c == 130) { w.nb0 = 15; w.na0 = 65; w.slotA = NSLOT - 1; w.own = 1; w.role = R_FIN | R_TAIL; w.loc0 = NSERV - NTAIL; w.nloc = NTAIL; }
  if (c == 131) { w.nb0 = w.na0 = w.nb1 = w.na1 = 0; w.loc0 = 0; w.nloc = NSERV - NTAIL; w.own = 0; }
  return w;
}
#define g_flag P.s->flag
#define g_M P.s->M
#define g_Wvo P.s->Wvo
#define g_Wmo P.s->Wmo
#define g_ml P.s->ml
#define g_unsafe P.s->unsafe
#define g_cnt P.s->cnt
#define g_h P.s->h
#define g_u P.u
#define g_stat P.s->stat
#define g_qp P.s->qp
#define g_agg P.s->agg
#define g_part P.s->part
#define g_bin P.s->bin
#define g_ovf P.s->ovf

__device__ __forceinline__ uint32_t smem_u32(const void* p) { return (uint32_t)__cvta_generic_to_shared(p); }
__device__ __forceinline__ void mbar_init(uint32_t bar, uint32_t cnt) { asm volatile("mbarrier.init.shared::cta.b64 [%0], %1;" :: "r"(bar), "r"(cnt) : "memory"); }
__device__ __forceinline__ void mbar_arrive(uint32_t bar) { asm volatile("mbarrier.arrive.shared::cta.b64 _, [%0];" :: "r"(bar) : "memory"); }
__device__ __forceinline__ void mbar_expect_tx(uint32_t bar, uint32_t bytes) { asm volatile("mbarrier.arrive.expect_tx.shared::cta.b64 _, [%0], %1;" :: "r"(bar), "r"(bytes) : "memory"); }
__device__ __forceinline__ bool mbar_try_wait(uint32_t bar, uint32_t parity) {
  uint32_t ok;
  asm volatile("{\n.reg .pred p;\nmbarrier.try_wait.parity.shared::cta.b64 p, [%1], %2;\nselp.b32 %0, 1, 0, p;\n}\n" : "=r"(ok) : "r"(bar), "r"(parity) : "memory");
  return ok;
}
__device__ __forceinline__ bool mbar_try_wait_nb(uint32_t bar, uint32_t parity) {
  uint32_t ok;
  asm volatile("{\n.reg .pred p;\nmbarrier.test_wait.parity.shared::cta.b64 p, [%1], %2;\nselp.b32 %0, 1, 0, p;\n}\n" : "=r"(ok) : "r"(bar), "r"(parity) : "memory");
  return ok;
}
__device__ __forceinline__ void mbar_wait(uint32_t bar, uint32_t parity) {
#pragma unroll 1
  for (uint32_t it = 0; it < (1u << 25); it++) if (mbar_try_wait(bar, parity)) break;
}
__device__ __forceinline__ void bulk_s2g(void* dst, uint32_t src, uint32_t bytes) {
  asm volatile("cp.async.bulk.global.shared::cta.bulk_group [%0], [%1], %2;" :: "l"(dst), "r"(src), "r"(bytes) : "memory");
}
__device__ __forceinline__ void bulk_commit() { asm volatile("cp.async.bulk.commit_group;" ::: "memory"); }
__device__ __forceinline__ void bulk_wait_read() { asm volatile("cp.async.bulk.wait_group.read 0;" ::: "memory"); }
__device__ __forceinline__ void bulk_wait_all() { asm volatile("cp.async.bulk.wait_group 0;" ::: "memory"); }
__device__ __forceinline__ bool bar_red_or(int id, int cnt, bool c) {
  uint32_t r;
  asm volatile("{\n.reg .pred p, q;\nsetp.ne.b32 q, %3, 0;\nbar.red.or.pred p, %1, %2, q;\nselp.b32 %0, 1, 0, p;\n}\n"
               : "=r"(r) : "r"(id), "r"(cnt), "r"((uint32_t)c) : "memory");
  return r != 0;
}
template <class T> __device__ __forceinline__ T* pofs(const void* base, uint32_t off) {
  asm volatile("" : "+r"(off));
  return (T*)((uint8_t*)base + off);
}
__device__ __forceinline__ const void* addr64(uint32_t lo, uint32_t hi) { uint64_t a; asm("mov.b64 %0, {%1, %2};" : "=l"(a) : "r"(lo), "r"(hi)); return (const void*)a; }
__device__ __forceinline__ uint4 ldcg_v(const void* a) {
  uint4 v;
  asm volatile("ld.volatile.global.v4.u32 {%0,%1,%2,%3}, [%4];" : "=r"(v.x), "=r"(v.y), "=r"(v.z), "=r"(v.w) : "l"(a) : "memory");
  return v;
}
__device__ __forceinline__ uint4 ldcs_v(const void* a) {
  uint4 v;
  asm volatile("ld.global.cs.v4.u32 {%0,%1,%2,%3}, [%4];" : "=r"(v.x), "=r"(v.y), "=r"(v.z), "=r"(v.w) : "l"(a) : "memory");
  return v;
}
__device__ __forceinline__ void prefetch_l2(const void* a, uint32_t bytes) { asm volatile("cp.async.bulk.prefetch.L2.global [%0], %1;" :: "l"(a), "r"(bytes) : "memory"); }
__device__ __forceinline__ void ldcg_if(uint4& v, const void* a, bool c) {
  asm volatile("{\n.reg .pred p;\nsetp.ne.b32 p, %5, 0;\n@p ld.volatile.global.v4.u32 {%0,%1,%2,%3}, [%4];\n}\n"
               : "+r"(v.x), "+r"(v.y), "+r"(v.z), "+r"(v.w) : "l"(a), "r"((uint32_t)c) : "memory");
}
__device__ __forceinline__ void cp_async16(uint32_t dst, const void* src) {
  asm volatile("cp.async.cg.shared.global [%0], [%1], 16;" :: "r"(dst), "l"(src) : "memory");
}
__device__ __forceinline__ void red_bf16x8(void* a, uint4 v) {
  asm volatile("red.global.add.noftz.v4.bf16x2 [%0], {%1,%2,%3,%4};" :: "l"(a), "r"(v.x), "r"(v.y), "r"(v.z), "r"(v.w) : "memory");
}
__device__ __forceinline__ uint32_t clk() { uint32_t c; asm volatile("mov.u32 %0, %%clock;" : "=r"(c) :: "memory"); return c; }
__device__ __forceinline__ void stsm4(uint32_t a, uint32_t r0, uint32_t r1, uint32_t r2, uint32_t r3) {
  asm volatile("stmatrix.sync.aligned.m8n8.x4.shared.b16 [%0], {%1,%2,%3,%4};" :: "r"(a), "r"(r0), "r"(r1), "r"(r2), "r"(r3) : "memory");
}
__device__ __forceinline__ void ldsm4(uint32_t a, uint32_t& r0, uint32_t& r1, uint32_t& r2, uint32_t& r3) {
  asm volatile("ldmatrix.sync.aligned.m8n8.x4.shared.b16 {%0,%1,%2,%3}, [%4];" : "=r"(r0), "=r"(r1), "=r"(r2), "=r"(r3) : "r"(a) : "memory");
}
__device__ __forceinline__ void red_relaxed(uint32_t* p) { asm volatile("red.relaxed.gpu.global.add.u32 [%0], 1;" :: "l"(p) : "memory"); }
__device__ __forceinline__ uint32_t lds32(uint32_t a) { uint32_t v; asm volatile("ld.shared.u32 %0, [%1];" : "=r"(v) : "r"(a) : "memory"); return v; }
__device__ __forceinline__ void cp_commit() { asm volatile("cp.async.commit_group;" ::: "memory"); }
__device__ __forceinline__ uint32_t hmul2(uint32_t a, uint32_t b) { uint32_t d; asm("mul.rn.bf16x2 %0, %1, %2;" : "=r"(d) : "r"(a), "r"(b)); return d; }
__device__ __forceinline__ uint32_t hfma2(uint32_t a, uint32_t b, uint32_t c) { uint32_t d; asm("fma.rn.bf16x2 %0, %1, %2, %3;" : "=r"(d) : "r"(a), "r"(b), "r"(c)); return d; }
__device__ __forceinline__ uint32_t pow2_bf2(int n) { return (uint32_t)max(n + 127, 0) * 0x00800080u; }
__device__ __forceinline__ int fexp(float x) { return (int)(__float_as_uint(x) >> 23) - 127; }
__device__ __forceinline__ void bulk_g2s(uint32_t dst, const void* src, uint32_t bytes, uint32_t bar) {
  asm volatile("cp.async.bulk.shared::cta.global.mbarrier::complete_tx::bytes [%0], [%1], %2, [%3];"
    :: "r"(dst), "l"(src), "r"(bytes), "r"(bar) : "memory");
}
__device__ __forceinline__ void bulk_g2s_last(uint32_t dst, const void* src, uint32_t bytes, uint32_t bar) {
  asm volatile("{\n.reg .b64 p;\ncreatepolicy.fractional.L2::evict_first.b64 p;\n"
    "cp.async.bulk.shared::cta.global.mbarrier::complete_tx::bytes.L2::cache_hint [%0], [%1], %2, [%3], p;\n}\n"
    :: "r"(dst), "l"(src), "r"(bytes), "r"(bar) : "memory");
}
__device__ __forceinline__ void wg_fence() { asm volatile("wgmma.fence.sync.aligned;" ::: "memory"); }
__device__ __forceinline__ void wg_commit() { asm volatile("wgmma.commit_group.sync.aligned;" ::: "memory"); }
template<int N> __device__ __forceinline__ void wg_wait() { asm volatile("wgmma.wait_group.sync.aligned %0;" :: "n"(N) : "memory"); }
__device__ __forceinline__ void bar_sync(int id, int cnt) { asm volatile("bar.sync %0, %1;" :: "r"(id), "r"(cnt) : "memory"); }
__device__ __forceinline__ void fence_async_smem() { asm volatile("fence.proxy.async.shared::cta;" ::: "memory"); }
__device__ __forceinline__ void fence_async_gmem() { asm volatile("fence.proxy.async.global;" ::: "memory"); }
__device__ __forceinline__ void bar_arrive(int id, int cnt) { asm volatile("bar.arrive %0, %1;" :: "r"(id), "r"(cnt) : "memory"); }
__device__ __forceinline__ void red_release(uint32_t* p) { asm volatile("red.release.gpu.global.add.u32 [%0], 1;" :: "l"(p) : "memory"); }
__device__ __forceinline__ void red_release_w(uint32_t* p) {
  __syncwarp();
  asm volatile("{\n.reg .pred q;\n.reg .b32 l;\nmov.u32 l, %%laneid;\nsetp.eq.u32 q, l, 0;\n@q fence.release.gpu;\n@q red.relaxed.gpu.global.add.u32 [%0], 1;\n}\n" :: "l"(p) : "memory");
}
__device__ __forceinline__ void mbar_wait_w(uint32_t bar, uint32_t parity) {
#pragma unroll 1
  for (uint32_t it = 0; it < (1u << 25); it++) if (__all_sync(0xffffffffu, mbar_try_wait(bar, parity))) break;
}
#define flag_release_w(f) red_release_w(g_flag + (f))
#define flag_wait_w(f, target) poll_acquire_w(g_flag + (f), target)
#define flag_release(f) red_release(g_flag + (f))
__device__ __forceinline__ uint32_t ld_relaxed(const uint32_t* p) {
  uint32_t v; asm volatile("ld.relaxed.gpu.global.u32 %0, [%1];" : "=r"(v) : "l"(p) : "memory"); return v;
}
#define flag_wait(f, target) poll_acquire(g_flag + (f), target)
__device__ __forceinline__ void poll_acquire(const uint32_t* p, uint32_t target) {
#pragma unroll 1
  for (uint32_t it = 0; it < (1u << 23); it++) if ((int)(ld_relaxed(p) - target) >= 0) break;
  asm volatile("fence.acquire.gpu;" ::: "memory");
}
__device__ __forceinline__ void poll_acquire_w(const uint32_t* p, uint32_t target) {
#pragma unroll 1
  for (uint32_t it = 0; it < (1u << 23); it++) {
    if (__all_sync(0xffffffffu, (int)(ld_relaxed(p) - target) >= 0)) break;
    if (BACKOFF) __nanosleep(BACKOFF);
  }
  asm volatile("fence.acquire.gpu;" ::: "memory");
}
template<int N> __device__ __forceinline__ void reg_fence(float (&d)[N]) {
#pragma unroll
  for (int i = 0; i < N; i++) asm volatile("" : "+f"(d[i]) :: "memory");
}
template<int N> __device__ __forceinline__ void reg_fence(uint32_t (&d)[N]) {
#pragma unroll
  for (int i = 0; i < N; i++) asm volatile("" : "+r"(d[i]) :: "memory");
}
__device__ __forceinline__ float ex2(float x) { float y; asm("ex2.approx.ftz.f32 %0, %1;" : "=f"(y) : "f"(x)); return y; }
__device__ __forceinline__ uint32_t pack_bf16(float lo, float hi) { uint32_t r; asm("cvt.rn.bf16x2.f32 %0, %1, %2;" : "=r"(r) : "f"(hi), "f"(lo)); return r; }
__device__ __forceinline__ float bf_lo(uint32_t w) { return __uint_as_float(w << 16); }
__device__ __forceinline__ float bf_hi(uint32_t w) { return __uint_as_float(w & 0xffff0000u); }
__device__ __forceinline__ uint64_t desc_k(uint32_t addr, uint32_t add) { return (uint64_t)((((addr & 0x3FFFF) >> 4) | (1u << 16)) + add) | (0x40000100ull << 32); }
__device__ __forceinline__ uint64_t desc_mn(uint32_t addr, uint32_t add) { return (uint64_t)((((addr & 0x3FFFF) >> 4) | ((1024u >> 4) << 16)) + add) | (0x40000100ull << 32); }
__device__ __forceinline__ uint64_t desc_m(uint32_t addr, uint32_t add) { return (uint64_t)((((addr & 0x3FFFF) >> 4) | ((1024u >> 4) << 16)) + add) | (0x80000020ull << 32); }
__device__ __forceinline__ void sts128(uint32_t a, uint4 v) { asm volatile("st.shared.v4.u32 [%0], {%1,%2,%3,%4};" :: "r"(a), "r"(v.x), "r"(v.y), "r"(v.z), "r"(v.w) : "memory"); }
__device__ __forceinline__ uint4 lds128(uint32_t a) { uint4 v; asm volatile("ld.shared.v4.u32 {%0,%1,%2,%3}, [%4];" : "=r"(v.x), "=r"(v.y), "=r"(v.z), "=r"(v.w) : "r"(a) : "memory"); return v; }
__device__ __forceinline__ void mma16816(float (&c)[4], uint32_t a0, uint32_t a1, uint32_t a2, uint32_t a3, uint32_t b0, uint32_t b1) {
  asm volatile("mma.sync.aligned.m16n8k16.row.col.f32.bf16.bf16.f32 {%0,%1,%2,%3}, {%4,%5,%6,%7}, {%8,%9}, {%0,%1,%2,%3};"
    : "+f"(c[0]), "+f"(c[1]), "+f"(c[2]), "+f"(c[3]) : "r"(a0), "r"(a1), "r"(a2), "r"(a3), "r"(b0), "r"(b1));
}
__device__ __forceinline__ uint32_t sw_byte(int r, int c) {
  return (uint32_t)((r >> 3) * 4096 + (c >> 6) * 1024 + (r & 7) * 128 + ((((c >> 3) & 7) ^ (r & 7)) << 4) + (c & 7) * 2);
}
__device__ __forceinline__ int cta_id() { int c; asm volatile("mov.u32 %0, %%ctaid.x;" : "=r"(c)); return c; }
__device__ __forceinline__ bool tid_is(int v) { int t; asm volatile("mov.u32 %0, %%tid.x;" : "=r"(t)); return t == v; }
#define STAMP(cond, who, i)
#define CSTAMP(cond, who, i)
#define DUMP(cond, who, i0, i1)
#define XSTAMP(cond, i)
#define SSTAMP(i)

template <int OA, int OB> __device__ __forceinline__ void wgmma_ss_n256_tb(float (&d)[128], uint64_t da, uint64_t db, int scale_d) {
  asm volatile("{\n.reg .pred p;\n.reg .b64 a, b;\nsetp.ne.b32 p, %130, 0;\nadd.s64 a, %128, %131;\nadd.s64 b, %129, %132;\n"
    "wgmma.mma_async.sync.aligned.m64n256k16.f32.bf16.bf16 "
    "{%0, %1, %2, %3, %4, %5, %6, %7, %8, %9, %10, %11, %12, %13, %14, %15, %16, %17, %18, %19, %20, %21, %22, %23, %24, %25, %26, %27, %28, %29, %30, %31, %32, %33, %34, %35, %36, %37, %38, %39, %40, %41, %42, %43, %44, %45, %46, %47, %48, %49, %50, %51, %52, %53, %54, %55, %56, %57, %58, %59, %60, %61, %62, %63, %64, %65, %66, %67, %68, %69, %70, %71, %72, %73, %74, %75, %76, %77, %78, %79, %80, %81, %82, %83, %84, %85, %86, %87, %88, %89, %90, %91, %92, %93, %94, %95, %96, %97, %98, %99, %100, %101, %102, %103, %104, %105, %106, %107, %108, %109, %110, %111, %112, %113, %114, %115, %116, %117, %118, %119, %120, %121, %122, %123, %124, %125, %126, %127}, "
    "a, b, p, 1, 1, 0, 1;\n}\n"
    : "+f"(d[0]), "+f"(d[1]), "+f"(d[2]), "+f"(d[3]), "+f"(d[4]), "+f"(d[5]), "+f"(d[6]), "+f"(d[7]), "+f"(d[8]), "+f"(d[9]), "+f"(d[10]), "+f"(d[11]), "+f"(d[12]), "+f"(d[13]), "+f"(d[14]), "+f"(d[15]), "+f"(d[16]), "+f"(d[17]), "+f"(d[18]), "+f"(d[19]), "+f"(d[20]), "+f"(d[21]), "+f"(d[22]), "+f"(d[23]), "+f"(d[24]), "+f"(d[25]), "+f"(d[26]), "+f"(d[27]), "+f"(d[28]), "+f"(d[29]), "+f"(d[30]), "+f"(d[31]), "+f"(d[32]), "+f"(d[33]), "+f"(d[34]), "+f"(d[35]), "+f"(d[36]), "+f"(d[37]), "+f"(d[38]), "+f"(d[39]), "+f"(d[40]), "+f"(d[41]), "+f"(d[42]), "+f"(d[43]), "+f"(d[44]), "+f"(d[45]), "+f"(d[46]), "+f"(d[47]), "+f"(d[48]), "+f"(d[49]), "+f"(d[50]), "+f"(d[51]), "+f"(d[52]), "+f"(d[53]), "+f"(d[54]), "+f"(d[55]), "+f"(d[56]), "+f"(d[57]), "+f"(d[58]), "+f"(d[59]), "+f"(d[60]), "+f"(d[61]), "+f"(d[62]), "+f"(d[63]), "+f"(d[64]), "+f"(d[65]), "+f"(d[66]), "+f"(d[67]), "+f"(d[68]), "+f"(d[69]), "+f"(d[70]), "+f"(d[71]), "+f"(d[72]), "+f"(d[73]), "+f"(d[74]), "+f"(d[75]), "+f"(d[76]), "+f"(d[77]), "+f"(d[78]), "+f"(d[79]), "+f"(d[80]), "+f"(d[81]), "+f"(d[82]), "+f"(d[83]), "+f"(d[84]), "+f"(d[85]), "+f"(d[86]), "+f"(d[87]), "+f"(d[88]), "+f"(d[89]), "+f"(d[90]), "+f"(d[91]), "+f"(d[92]), "+f"(d[93]), "+f"(d[94]), "+f"(d[95]), "+f"(d[96]), "+f"(d[97]), "+f"(d[98]), "+f"(d[99]), "+f"(d[100]), "+f"(d[101]), "+f"(d[102]), "+f"(d[103]), "+f"(d[104]), "+f"(d[105]), "+f"(d[106]), "+f"(d[107]), "+f"(d[108]), "+f"(d[109]), "+f"(d[110]), "+f"(d[111]), "+f"(d[112]), "+f"(d[113]), "+f"(d[114]), "+f"(d[115]), "+f"(d[116]), "+f"(d[117]), "+f"(d[118]), "+f"(d[119]), "+f"(d[120]), "+f"(d[121]), "+f"(d[122]), "+f"(d[123]), "+f"(d[124]), "+f"(d[125]), "+f"(d[126]), "+f"(d[127])
    : "l"(da), "l"(db), "r"(scale_d), "n"(OA), "n"(OB));
}
template <int OA, int OB> __device__ __forceinline__ void wgmma_qk(float (&d)[64], uint64_t da, uint64_t db, int scale_d) {
  asm volatile("{\n.reg .pred p;\n.reg .b64 a, b;\nsetp.ne.b32 p, %66, 0;\nadd.s64 a, %64, %67;\nadd.s64 b, %65, %68;\n"
    "wgmma.mma_async.sync.aligned.m64n128k16.f32.bf16.bf16 "
    "{%0, %1, %2, %3, %4, %5, %6, %7, %8, %9, %10, %11, %12, %13, %14, %15, %16, %17, %18, %19, %20, %21, %22, %23, %24, %25, %26, %27, %28, %29, %30, %31, %32, %33, %34, %35, %36, %37, %38, %39, %40, %41, %42, %43, %44, %45, %46, %47, %48, %49, %50, %51, %52, %53, %54, %55, %56, %57, %58, %59, %60, %61, %62, %63}, "
    "a, b, p, 1, 1, 0, 0;\n}\n"
    : "+f"(d[0]), "+f"(d[1]), "+f"(d[2]), "+f"(d[3]), "+f"(d[4]), "+f"(d[5]), "+f"(d[6]), "+f"(d[7]), "+f"(d[8]), "+f"(d[9]), "+f"(d[10]), "+f"(d[11]), "+f"(d[12]), "+f"(d[13]), "+f"(d[14]), "+f"(d[15]), "+f"(d[16]), "+f"(d[17]), "+f"(d[18]), "+f"(d[19]), "+f"(d[20]), "+f"(d[21]), "+f"(d[22]), "+f"(d[23]), "+f"(d[24]), "+f"(d[25]), "+f"(d[26]), "+f"(d[27]), "+f"(d[28]), "+f"(d[29]), "+f"(d[30]), "+f"(d[31]), "+f"(d[32]), "+f"(d[33]), "+f"(d[34]), "+f"(d[35]), "+f"(d[36]), "+f"(d[37]), "+f"(d[38]), "+f"(d[39]), "+f"(d[40]), "+f"(d[41]), "+f"(d[42]), "+f"(d[43]), "+f"(d[44]), "+f"(d[45]), "+f"(d[46]), "+f"(d[47]), "+f"(d[48]), "+f"(d[49]), "+f"(d[50]), "+f"(d[51]), "+f"(d[52]), "+f"(d[53]), "+f"(d[54]), "+f"(d[55]), "+f"(d[56]), "+f"(d[57]), "+f"(d[58]), "+f"(d[59]), "+f"(d[60]), "+f"(d[61]), "+f"(d[62]), "+f"(d[63])
    : "l"(da), "l"(db), "r"(scale_d), "n"(OA), "n"(OB));
}
template <int OA, int OB> __device__ __forceinline__ void wgmma_qk(float (&d)[56], uint64_t da, uint64_t db, int scale_d) {
  asm volatile("{\n.reg .pred p;\n.reg .b64 a, b;\nsetp.ne.b32 p, %58, 0;\nadd.s64 a, %56, %59;\nadd.s64 b, %57, %60;\n"
    "wgmma.mma_async.sync.aligned.m64n112k16.f32.bf16.bf16 "
    "{%0, %1, %2, %3, %4, %5, %6, %7, %8, %9, %10, %11, %12, %13, %14, %15, %16, %17, %18, %19, %20, %21, %22, %23, %24, %25, %26, %27, %28, %29, %30, %31, %32, %33, %34, %35, %36, %37, %38, %39, %40, %41, %42, %43, %44, %45, %46, %47, %48, %49, %50, %51, %52, %53, %54, %55}, "
    "a, b, p, 1, 1, 0, 0;\n}\n"
    : "+f"(d[0]), "+f"(d[1]), "+f"(d[2]), "+f"(d[3]), "+f"(d[4]), "+f"(d[5]), "+f"(d[6]), "+f"(d[7]), "+f"(d[8]), "+f"(d[9]), "+f"(d[10]), "+f"(d[11]), "+f"(d[12]), "+f"(d[13]), "+f"(d[14]), "+f"(d[15]), "+f"(d[16]), "+f"(d[17]), "+f"(d[18]), "+f"(d[19]), "+f"(d[20]), "+f"(d[21]), "+f"(d[22]), "+f"(d[23]), "+f"(d[24]), "+f"(d[25]), "+f"(d[26]), "+f"(d[27]), "+f"(d[28]), "+f"(d[29]), "+f"(d[30]), "+f"(d[31]), "+f"(d[32]), "+f"(d[33]), "+f"(d[34]), "+f"(d[35]), "+f"(d[36]), "+f"(d[37]), "+f"(d[38]), "+f"(d[39]), "+f"(d[40]), "+f"(d[41]), "+f"(d[42]), "+f"(d[43]), "+f"(d[44]), "+f"(d[45]), "+f"(d[46]), "+f"(d[47]), "+f"(d[48]), "+f"(d[49]), "+f"(d[50]), "+f"(d[51]), "+f"(d[52]), "+f"(d[53]), "+f"(d[54]), "+f"(d[55])
    : "l"(da), "l"(db), "r"(scale_d), "n"(OA), "n"(OB));
}
template <int OB> __device__ __forceinline__ void wgmma_rs_n256_tb(float (&d)[128], uint32_t a0, uint32_t a1, uint32_t a2, uint32_t a3, uint64_t db, int scale_d) {
  asm volatile("{\n.reg .pred p;\n.reg .b64 b;\nsetp.ne.b32 p, %133, 0;\nadd.s64 b, %132, %134;\n"
    "wgmma.mma_async.sync.aligned.m64n256k16.f32.bf16.bf16 "
    "{%0, %1, %2, %3, %4, %5, %6, %7, %8, %9, %10, %11, %12, %13, %14, %15, %16, %17, %18, %19, %20, %21, %22, %23, %24, %25, %26, %27, %28, %29, %30, %31, %32, %33, %34, %35, %36, %37, %38, %39, %40, %41, %42, %43, %44, %45, %46, %47, %48, %49, %50, %51, %52, %53, %54, %55, %56, %57, %58, %59, %60, %61, %62, %63, %64, %65, %66, %67, %68, %69, %70, %71, %72, %73, %74, %75, %76, %77, %78, %79, %80, %81, %82, %83, %84, %85, %86, %87, %88, %89, %90, %91, %92, %93, %94, %95, %96, %97, %98, %99, %100, %101, %102, %103, %104, %105, %106, %107, %108, %109, %110, %111, %112, %113, %114, %115, %116, %117, %118, %119, %120, %121, %122, %123, %124, %125, %126, %127}, "
    "{%128, %129, %130, %131}, b, p, 1, 1, 1;\n}\n"
    : "+f"(d[0]), "+f"(d[1]), "+f"(d[2]), "+f"(d[3]), "+f"(d[4]), "+f"(d[5]), "+f"(d[6]), "+f"(d[7]), "+f"(d[8]), "+f"(d[9]), "+f"(d[10]), "+f"(d[11]), "+f"(d[12]), "+f"(d[13]), "+f"(d[14]), "+f"(d[15]), "+f"(d[16]), "+f"(d[17]), "+f"(d[18]), "+f"(d[19]), "+f"(d[20]), "+f"(d[21]), "+f"(d[22]), "+f"(d[23]), "+f"(d[24]), "+f"(d[25]), "+f"(d[26]), "+f"(d[27]), "+f"(d[28]), "+f"(d[29]), "+f"(d[30]), "+f"(d[31]), "+f"(d[32]), "+f"(d[33]), "+f"(d[34]), "+f"(d[35]), "+f"(d[36]), "+f"(d[37]), "+f"(d[38]), "+f"(d[39]), "+f"(d[40]), "+f"(d[41]), "+f"(d[42]), "+f"(d[43]), "+f"(d[44]), "+f"(d[45]), "+f"(d[46]), "+f"(d[47]), "+f"(d[48]), "+f"(d[49]), "+f"(d[50]), "+f"(d[51]), "+f"(d[52]), "+f"(d[53]), "+f"(d[54]), "+f"(d[55]), "+f"(d[56]), "+f"(d[57]), "+f"(d[58]), "+f"(d[59]), "+f"(d[60]), "+f"(d[61]), "+f"(d[62]), "+f"(d[63]), "+f"(d[64]), "+f"(d[65]), "+f"(d[66]), "+f"(d[67]), "+f"(d[68]), "+f"(d[69]), "+f"(d[70]), "+f"(d[71]), "+f"(d[72]), "+f"(d[73]), "+f"(d[74]), "+f"(d[75]), "+f"(d[76]), "+f"(d[77]), "+f"(d[78]), "+f"(d[79]), "+f"(d[80]), "+f"(d[81]), "+f"(d[82]), "+f"(d[83]), "+f"(d[84]), "+f"(d[85]), "+f"(d[86]), "+f"(d[87]), "+f"(d[88]), "+f"(d[89]), "+f"(d[90]), "+f"(d[91]), "+f"(d[92]), "+f"(d[93]), "+f"(d[94]), "+f"(d[95]), "+f"(d[96]), "+f"(d[97]), "+f"(d[98]), "+f"(d[99]), "+f"(d[100]), "+f"(d[101]), "+f"(d[102]), "+f"(d[103]), "+f"(d[104]), "+f"(d[105]), "+f"(d[106]), "+f"(d[107]), "+f"(d[108]), "+f"(d[109]), "+f"(d[110]), "+f"(d[111]), "+f"(d[112]), "+f"(d[113]), "+f"(d[114]), "+f"(d[115]), "+f"(d[116]), "+f"(d[117]), "+f"(d[118]), "+f"(d[119]), "+f"(d[120]), "+f"(d[121]), "+f"(d[122]), "+f"(d[123]), "+f"(d[124]), "+f"(d[125]), "+f"(d[126]), "+f"(d[127])
    : "r"(a0), "r"(a1), "r"(a2), "r"(a3), "l"(db), "r"(scale_d), "n"(OB));
}
template <int OB> __device__ __forceinline__ void wgmma_rs_n256_tb_first(float (&d)[128], uint32_t a0, uint32_t a1, uint32_t a2, uint32_t a3, uint64_t db) {
  asm volatile("{\n.reg .pred p;\n.reg .b64 b;\nsetp.ne.b32 p, 0, 0;\nadd.s64 b, %132, %133;\n"
    "wgmma.mma_async.sync.aligned.m64n256k16.f32.bf16.bf16 "
    "{%0, %1, %2, %3, %4, %5, %6, %7, %8, %9, %10, %11, %12, %13, %14, %15, %16, %17, %18, %19, %20, %21, %22, %23, %24, %25, %26, %27, %28, %29, %30, %31, %32, %33, %34, %35, %36, %37, %38, %39, %40, %41, %42, %43, %44, %45, %46, %47, %48, %49, %50, %51, %52, %53, %54, %55, %56, %57, %58, %59, %60, %61, %62, %63, %64, %65, %66, %67, %68, %69, %70, %71, %72, %73, %74, %75, %76, %77, %78, %79, %80, %81, %82, %83, %84, %85, %86, %87, %88, %89, %90, %91, %92, %93, %94, %95, %96, %97, %98, %99, %100, %101, %102, %103, %104, %105, %106, %107, %108, %109, %110, %111, %112, %113, %114, %115, %116, %117, %118, %119, %120, %121, %122, %123, %124, %125, %126, %127}, "
    "{%128, %129, %130, %131}, b, p, 1, 1, 1;\n}\n"
    : "=f"(d[0]), "=f"(d[1]), "=f"(d[2]), "=f"(d[3]), "=f"(d[4]), "=f"(d[5]), "=f"(d[6]), "=f"(d[7]), "=f"(d[8]), "=f"(d[9]), "=f"(d[10]), "=f"(d[11]), "=f"(d[12]), "=f"(d[13]), "=f"(d[14]), "=f"(d[15]), "=f"(d[16]), "=f"(d[17]), "=f"(d[18]), "=f"(d[19]), "=f"(d[20]), "=f"(d[21]), "=f"(d[22]), "=f"(d[23]), "=f"(d[24]), "=f"(d[25]), "=f"(d[26]), "=f"(d[27]), "=f"(d[28]), "=f"(d[29]), "=f"(d[30]), "=f"(d[31]), "=f"(d[32]), "=f"(d[33]), "=f"(d[34]), "=f"(d[35]), "=f"(d[36]), "=f"(d[37]), "=f"(d[38]), "=f"(d[39]), "=f"(d[40]), "=f"(d[41]), "=f"(d[42]), "=f"(d[43]), "=f"(d[44]), "=f"(d[45]), "=f"(d[46]), "=f"(d[47]), "=f"(d[48]), "=f"(d[49]), "=f"(d[50]), "=f"(d[51]), "=f"(d[52]), "=f"(d[53]), "=f"(d[54]), "=f"(d[55]), "=f"(d[56]), "=f"(d[57]), "=f"(d[58]), "=f"(d[59]), "=f"(d[60]), "=f"(d[61]), "=f"(d[62]), "=f"(d[63]), "=f"(d[64]), "=f"(d[65]), "=f"(d[66]), "=f"(d[67]), "=f"(d[68]), "=f"(d[69]), "=f"(d[70]), "=f"(d[71]), "=f"(d[72]), "=f"(d[73]), "=f"(d[74]), "=f"(d[75]), "=f"(d[76]), "=f"(d[77]), "=f"(d[78]), "=f"(d[79]), "=f"(d[80]), "=f"(d[81]), "=f"(d[82]), "=f"(d[83]), "=f"(d[84]), "=f"(d[85]), "=f"(d[86]), "=f"(d[87]), "=f"(d[88]), "=f"(d[89]), "=f"(d[90]), "=f"(d[91]), "=f"(d[92]), "=f"(d[93]), "=f"(d[94]), "=f"(d[95]), "=f"(d[96]), "=f"(d[97]), "=f"(d[98]), "=f"(d[99]), "=f"(d[100]), "=f"(d[101]), "=f"(d[102]), "=f"(d[103]), "=f"(d[104]), "=f"(d[105]), "=f"(d[106]), "=f"(d[107]), "=f"(d[108]), "=f"(d[109]), "=f"(d[110]), "=f"(d[111]), "=f"(d[112]), "=f"(d[113]), "=f"(d[114]), "=f"(d[115]), "=f"(d[116]), "=f"(d[117]), "=f"(d[118]), "=f"(d[119]), "=f"(d[120]), "=f"(d[121]), "=f"(d[122]), "=f"(d[123]), "=f"(d[124]), "=f"(d[125]), "=f"(d[126]), "=f"(d[127])
    : "r"(a0), "r"(a1), "r"(a2), "r"(a3), "l"(db), "n"(OB));
}
template <int OB> __device__ __forceinline__ void wgmma_rs_n128_tb(float (&d)[64], uint32_t a0, uint32_t a1, uint32_t a2, uint32_t a3, uint64_t db, int scale_d) {
  asm volatile("{\n.reg .pred p;\n.reg .b64 b;\nsetp.ne.b32 p, %69, 0;\nadd.s64 b, %68, %70;\n"
    "wgmma.mma_async.sync.aligned.m64n128k16.f32.bf16.bf16 "
    "{%0, %1, %2, %3, %4, %5, %6, %7, %8, %9, %10, %11, %12, %13, %14, %15, %16, %17, %18, %19, %20, %21, %22, %23, %24, %25, %26, %27, %28, %29, %30, %31, %32, %33, %34, %35, %36, %37, %38, %39, %40, %41, %42, %43, %44, %45, %46, %47, %48, %49, %50, %51, %52, %53, %54, %55, %56, %57, %58, %59, %60, %61, %62, %63}, "
    "{%64, %65, %66, %67}, b, p, 1, 1, 1;\n}\n"
    : "+f"(d[0]), "+f"(d[1]), "+f"(d[2]), "+f"(d[3]), "+f"(d[4]), "+f"(d[5]), "+f"(d[6]), "+f"(d[7]), "+f"(d[8]), "+f"(d[9]), "+f"(d[10]), "+f"(d[11]), "+f"(d[12]), "+f"(d[13]), "+f"(d[14]), "+f"(d[15]), "+f"(d[16]), "+f"(d[17]), "+f"(d[18]), "+f"(d[19]), "+f"(d[20]), "+f"(d[21]), "+f"(d[22]), "+f"(d[23]), "+f"(d[24]), "+f"(d[25]), "+f"(d[26]), "+f"(d[27]), "+f"(d[28]), "+f"(d[29]), "+f"(d[30]), "+f"(d[31]), "+f"(d[32]), "+f"(d[33]), "+f"(d[34]), "+f"(d[35]), "+f"(d[36]), "+f"(d[37]), "+f"(d[38]), "+f"(d[39]), "+f"(d[40]), "+f"(d[41]), "+f"(d[42]), "+f"(d[43]), "+f"(d[44]), "+f"(d[45]), "+f"(d[46]), "+f"(d[47]), "+f"(d[48]), "+f"(d[49]), "+f"(d[50]), "+f"(d[51]), "+f"(d[52]), "+f"(d[53]), "+f"(d[54]), "+f"(d[55]), "+f"(d[56]), "+f"(d[57]), "+f"(d[58]), "+f"(d[59]), "+f"(d[60]), "+f"(d[61]), "+f"(d[62]), "+f"(d[63])
    : "r"(a0), "r"(a1), "r"(a2), "r"(a3), "l"(db), "r"(scale_d), "n"(OB));
}
template <int V> using IC = std::integral_constant<int, V>;
template <int I, int N, class F> __device__ __forceinline__ void static_for(F&& f) {
  if constexpr (I < N) { f(std::integral_constant<int, I>{}); static_for<I + 1, N>(f); }
}

constexpr uint32_t SM_Q = 0, SM_BAR = 7 * 32768;
constexpr uint32_t B_FULL = SM_BAR, B_EMPTY = B_FULL + 24, B_WF = B_EMPTY + 24, B_QFULL = B_WF + 32, B_QEMPTY = B_QFULL + 16,
                   B_EVH = B_QEMPTY + 16, B_EVQ = B_EVH + 8, B_EVP0 = B_EVQ + 8, B_BG = B_EVP0 + 16, B_M0 = B_BG + 8, B_HALF = B_M0 + 8,
                   B_HRD = B_HALF + 8, SM_UNSAFE = B_HRD + 8, SM_TS = SM_UNSAFE + 8, SM_ML = (SM_TS + 192 + 15) / 16 * 16, SM_EPOCH = SM_ML + 1024, SM_END = SM_EPOCH + 16;
constexpr uint32_t POS_M = 0x5462;
constexpr int SMEM_BYTES = SM_END;

#define ROW0(u) make_uint4(pack_bf16(o[16 * u], o[16 * u + 1]), pack_bf16(o[16 * u + 4], o[16 * u + 5]), \
                           pack_bf16(o[16 * u + 8], o[16 * u + 9]), pack_bf16(o[16 * u + 12], o[16 * u + 13]))
#define ROW1(u) make_uint4(pack_bf16(o[16 * u + 2], o[16 * u + 3]), pack_bf16(o[16 * u + 6], o[16 * u + 7]), \
                           pack_bf16(o[16 * u + 10], o[16 * u + 11]), pack_bf16(o[16 * u + 14], o[16 * u + 15]))

__global__ void __launch_bounds__(384, 1) gps_kernel(const __grid_constant__ Params P) {
  extern __shared__ __align__(1024) uint8_t smem_raw[];
  constexpr uint32_t sb = 1024;
  if (smem_u32(smem_raw) != sb) return;
  const int cta = blockIdx.x;
  const int wg = __shfl_sync(0xffffffffu, (int)threadIdx.x >> 7, 0);
  const int warp = __shfl_sync(0xffffffffu, ((int)threadIdx.x >> 5) & 3, 0);
  const int lane = threadIdx.x & 31;
#define ROLE                                                                                       \
  const Work& W = P.w[cta_id()];                                                                   \
  [[maybe_unused]] const int n0 = W.nb0 + W.na0, n1 = W.nb1 + W.na1, total = n0 + n1;              \
  [[maybe_unused]] const bool fin = W.role & R_FIN, tail = W.role & R_TAIL;                        \
  [[maybe_unused]] const uint32_t posw = total == 0 || tail ? POS_M : ((total & 1) ? 0x2546 : 0x4326)
  const int g = lane >> 2, t = lane & 3;
  if (wg < 2) {
    const int tid = threadIdx.x & 127;
    ROLE;
    const uint32_t sQ = sb + SM_Q + wg * 32768;
#define st0 tid_is(wg * 128)
    STAMP(st0, wg, 0);
    const int rr = lane >> 3, j = lane & 7;
    const uint4* px[4];
#pragma unroll
    for (int i = 0; i < 4; i++) px[i] = (const uint4*)(P.x + (size_t)min(W.q0 * 128 + wg * 64 + warp * 16 + i * 4 + rr, NN - 1) * 256) + j;
    auto x_load = [&](int c) {
      if (c < 4) {
#pragma unroll
        for (int i = 0; i < 4; i++)
          cp_async16(sQ + warp * 8192 + (i >> 1) * 4096 + c * 1024 + ((i & 1) * 4 + rr) * 128 + ((j ^ ((i & 1) * 4 + rr)) << 4), px[i] + c * 8);
      }
      cp_commit();
    };
    if (total > 0) {
#pragma unroll
      for (int c = 0; c < XD; c++) x_load(c);
    }
    bar_sync(4, 384);
    if (wg == 1) bar_arrive(5, 256);

    const uint32_t sF = sQ + warp * 8192 + ((lane >> 3) & 1) * 4096 + (lane & 7) * 128;
    auto frag = [&](int k) { return sF + (k >> 2) * 1024 + ((((k & 3) * 2 + (lane >> 4)) ^ (lane & 7)) << 4); };
    uint32_t hq[64];
    const bool own = (W.own >> wg) & 1;
    if (total > 0) {
      float c1[4] = {0.f, 0.f, 0.f, 0.f}, ca[4] = {0.f, 0.f, 0.f, 0.f}, cb[4] = {0.f, 0.f, 0.f, 0.f};
#pragma unroll
      for (int k = 0; k < 16; k++) {
        if ((k & 3) == 0) {
          asm volatile("cp.async.wait_group %0;" :: "n"(XD - 1) : "memory");
          __syncwarp();
          x_load(k / 4 + XD);
        }
        ldsm4(frag(k), hq[4 * k], hq[4 * k + 1], hq[4 * k + 2], hq[4 * k + 3]);
        mma16816(c1, hq[4 * k], hq[4 * k + 1], hq[4 * k + 2], hq[4 * k + 3], 0x3f803f80u, 0x3f803f80u);
        mma16816(ca, hq[4 * k], hq[4 * k + 1], hq[4 * k + 2], hq[4 * k + 3], hq[4 * k], hq[4 * k + 2]);
        mma16816(cb, hq[4 * k], hq[4 * k + 1], hq[4 * k + 2], hq[4 * k + 3], hq[4 * k + 1], hq[4 * k + 3]);
      }
      const float mu0 = c1[0] * (1.0f / 256.0f), mu1 = c1[2] * (1.0f / 256.0f);
      const float v0 = fmaf(__shfl_sync(0xffffffffu, g & 1 ? ca[1] : ca[0], g * 4 + (g >> 1)), 1.0f / 256.0f, 1e-5f - mu0 * mu0);
      const float v1 = fmaf(__shfl_sync(0xffffffffu, g & 1 ? cb[3] : cb[2], g * 4 + (g >> 1)), 1.0f / 256.0f, 1e-5f - mu1 * mu1);
      float rs0, rs1;
      asm("rsqrt.approx.ftz.f32 %0, %1;" : "=f"(rs0) : "f"(v0)); asm("rsqrt.approx.ftz.f32 %0, %1;" : "=f"(rs1) : "f"(v1));
      if (W.q0 * 128 + wg * 64 + warp * 16 >= NN) rs0 = rs1 = 0.f;
      float nb0 = -mu0 * rs0, nb1 = -mu1 * rs1;
      const uint32_t sS = sb + SM_ML + (wg * 64 + warp * 16) * 8;
      if (t == 0) {
        asm volatile("st.shared.v2.f32 [%0], {%1,%2};" :: "r"(sS + g * 8), "f"(rs0), "f"(nb0) : "memory");
        asm volatile("st.shared.v2.f32 [%0], {%1,%2};" :: "r"(sS + g * 8 + 64), "f"(rs1), "f"(nb1) : "memory");
      }
      if (__any_sync(0xffffffffu, !(4.f * mu0 * mu0 <= v0) || !(4.f * mu1 * mu1 <= v1))) {
#pragma unroll 1
        for (int r = 0; r < 16; r++) {
          const uint32_t ad = sQ + warp * 8192 + (r >> 3) * 4096 + rr * 1024 + (r & 7) * 128 + ((j ^ (r & 7)) << 4);
          const uint4 v = lds128(ad);
          float f[8] = {bf_lo(v.x), bf_hi(v.x), bf_lo(v.y), bf_hi(v.y), bf_lo(v.z), bf_hi(v.z), bf_lo(v.w), bf_hi(v.w)};
          float sum = 0.f, ss = 0.f, rs;
#pragma unroll
          for (int i = 0; i < 8; i++) sum += f[i];
#pragma unroll 1
          for (int k = 1; k < 32; k *= 2) sum += __shfl_xor_sync(0xffffffffu, sum, k);
          sum *= 1.0f / 256.0f;
#pragma unroll
          for (int i = 0; i < 8; i++) { f[i] -= sum; ss += f[i] * f[i]; }
#pragma unroll 1
          for (int k = 1; k < 32; k *= 2) ss += __shfl_xor_sync(0xffffffffu, ss, k);
          asm("rsqrt.approx.ftz.f32 %0, %1;" : "=f"(rs) : "f"(fmaf(ss, 1.0f / 256.0f, 1e-5f)));
          if (W.q0 * 128 + wg * 64 + warp * 16 >= NN) rs = 0.f;
          sts128(ad, make_uint4(pack_bf16(f[0] * rs, f[1] * rs), pack_bf16(f[2] * rs, f[3] * rs), pack_bf16(f[4] * rs, f[5] * rs), pack_bf16(f[6] * rs, f[7] * rs)));
          if (lane == 0) asm volatile("st.shared.v2.f32 [%0], {%1,%2};" :: "r"(sS + r * 8), "f"(rs), "f"(-sum * rs) : "memory");
        }
        __syncwarp();
#pragma unroll
        for (int k = 0; k < 16; k++) ldsm4(frag(k), hq[4 * k], hq[4 * k + 1], hq[4 * k + 2], hq[4 * k + 3]);
        rs0 = rs1 = 1.f; nb0 = nb1 = 0.f;
      }
      asm volatile("setmaxnreg.inc.sync.aligned.u32 %0;" :: "n"(CREG));
      const uint32_t ah0 = pack_bf16(rs0, rs0), ah1 = pack_bf16(rs1, rs1), n0_ = pack_bf16(nb0, nb0), n1_ = pack_bf16(nb1, nb1);
      const uint32_t al0 = pack_bf16(rs0 - bf_lo(ah0), rs0 - bf_lo(ah0)), al1 = pack_bf16(rs1 - bf_lo(ah1), rs1 - bf_lo(ah1));
#pragma unroll
      for (int i = 0; i < 32; i++) {
        hq[2 * i] = hfma2(hq[2 * i], ah0, hfma2(hq[2 * i], al0, n0_));
        hq[2 * i + 1] = hfma2(hq[2 * i + 1], ah1, hfma2(hq[2 * i + 1], al1, n1_));
      }
      if (own) {
        const float e0 = fmaf(bf_hi(__shfl_sync(0xffffffffu, hq[62], lane | 3)), -0.5f * KS, KC), e1 = fmaf(bf_hi(__shfl_sync(0xffffffffu, hq[63], lane | 3)), -0.5f * KS, KC);
#pragma unroll
        for (int k = 0; k < 16; k++)
          stsm4(frag(k), hfma2(hq[4 * k], KS2, KC2), hfma2(hq[4 * k + 1], KS2, KC2),
                k < 15 ? hfma2(hq[4 * k + 2], KS2, KC2) : pack_bf16(fmaf(bf_lo(hq[62]), KS, e0), t == 3 ? KC : fmaf(bf_hi(hq[62]), KS, e0)),
                k < 15 ? hfma2(hq[4 * k + 3], KS2, KC2) : pack_bf16(fmaf(bf_lo(hq[63]), KS, e1), t == 3 ? KC : fmaf(bf_hi(hq[63]), KS, e1)));
      }
      __syncwarp();
      if (lane == 0) mbar_arrive(sb + B_EVH);
    } else {
      asm volatile("setmaxnreg.inc.sync.aligned.u32 %0;" :: "n"(CREG));
    }
    STAMP(st0, wg, 1);

    float o[128];
    int qph = 0, st = tail ? wg : 0, ph = 0;
    auto release = [&](int stg) { if (lane == 0) mbar_arrive(sb + B_EMPTY + 8 * stg); };
    int resume = total > 0 ? -1 : 0;
    auto fill = [&]() __attribute__((always_inline)) {
#pragma unroll
      for (int i = 0; i < 32; i++)
        asm volatile("ld.volatile.shared.v4.f32 {%0,%1,%2,%3}, [%4];" : "=f"(o[4 * i]), "=f"(o[4 * i + 1]), "=f"(o[4 * i + 2]), "=f"(o[4 * i + 3]) : "r"(sb) : "memory");
    };
    auto finish = [&]() __attribute__((always_inline)) {
      STAMP(st0, wg, 11);
      DUMP(st0, wg, 0, 16);
      if (!P.zero) { asm volatile("exit;"); __builtin_unreachable(); }
      fill();
    };
    auto run = [&](auto hot_) __attribute__((always_inline)) {
    constexpr bool HOT = hot_.value;
    const int nloc = P.w[cta_id()].nloc;
    if (!HOT && resume == 0) {
#pragma unroll 1
      for (int i = 0; i < 32; i++) {
        const int r = i * 8 + wg * 4 + warp;
        cp_async16(sb + ((POS_M >> (r >> 6) * 4) & 15) * 32768 + sw_byte(r & 63, lane * 8), (const uint4*)P.wout + r * 32 + lane);
      }
    }
    bool wide = false;
    if (HOT) {
      reg_fence(hq);
      auto qstep = [&](auto k_) {
        constexpr int k = k_.value;
        if (k < 2 || k % 4 == 0) { mbar_wait(k == 0 ? sb + B_M0 : sb + B_WF + 2 * (k & ~3), 0); if (k == 0 || k == 4) bar_sync(5 + wg, 256); wg_fence(); }
        if constexpr (k == 0) wgmma_rs_n256_tb_first<0>(o, hq[0], hq[1], hq[2], hq[3], desc_m(sb, (POS_M & 15) * 2048));
        else wgmma_rs_n256_tb<(k & 3) * 512>(o, hq[4 * k], hq[4 * k + 1], hq[4 * k + 2], hq[4 * k + 3], desc_m(sb, ((POS_M >> (k & ~3)) & 15) * 2048), 1);
      };
      static_for<0, 4>(qstep);
      wg_commit();
      bar_arrive(6 - wg, 256);
      wg_wait<0>();
      if (!tail) release(0);
      static_for<4, 16>(qstep);
      wg_commit();
      bar_arrive(6 - wg, 256);
      wg_wait<0>();
      reg_fence(o); reg_fence(hq);
      if (!tail) release(1);
      STAMP(st0, wg, 2);
      float c0 = (o[124] + (t == 3 ? 2.f : 1.f) * o[125]) * (-0.5f / 4.5f), c1 = (o[126] + (t == 3 ? 2.f : 1.f) * o[127]) * (-0.5f / 4.5f);
      c0 += __shfl_xor_sync(0xffffffffu, c0, 1); c1 += __shfl_xor_sync(0xffffffffu, c1, 1);
      c0 += __shfl_xor_sync(0xffffffffu, c0, 2); c1 += __shfl_xor_sync(0xffffffffu, c1, 2);
      float r0 = t == 3 ? 0.f : o[125], r1 = t == 3 ? 0.f : o[127], r2 = o[124], r3 = o[126];
#pragma unroll
      for (int i = 0; i < 31; i++) { r2 += o[4 * i]; r0 += o[4 * i + 1]; r3 += o[4 * i + 2]; r1 += o[4 * i + 3]; }
      r0 += r2; r1 += r3;
      r0 += __shfl_xor_sync(0xffffffffu, r0, 1); r1 += __shfl_xor_sync(0xffffffffu, r1, 1);
      r0 += __shfl_xor_sync(0xffffffffu, r0, 2); r1 += __shfl_xor_sync(0xffffffffu, r1, 2);
      r0 = fmaf(c0, -255.f, PSH / KC - r0); r1 = fmaf(c1, -255.f, PSH / KC - r1);
      wide = !(fabsf(c0) <= SAFE_C / KS) || !(fabsf(c1) <= SAFE_C / KS);
      if (own) mbar_wait(sb + B_HRD, 0);
#pragma unroll
      for (int k = 0; k < 16; k++)
        stsm4(frag(k),
              pack_bf16(o[8 * k] + c0, o[8 * k + 1] + c0), pack_bf16(o[8 * k + 2] + c1, o[8 * k + 3] + c1),
              pack_bf16(o[8 * k + 4] + c0, k == 15 && t == 3 ? r0 : o[8 * k + 5] + c0), pack_bf16(o[8 * k + 6] + c1, k == 15 && t == 3 ? r1 : o[8 * k + 7] + c1));
      fence_async_smem();
      __syncwarp();
      STAMP(st0, wg, 3);
      if (tail) { bar_sync(7, 256); if (wg == 0) { release(0); release(1); release(2); } }
      }

    if (HOT || (resume && resume < 4)) {
      ROLE;
      float m0, m1;
      const int qh = tail ? 0 : wg, tl = tail;
      uint32_t qo = qh * 2048;
      const uint32_t ko = (2 - tl) * 2048, stop = 1 + tl + (uint32_t)P.zero;
      float l0, l1;
      auto row_sums = [&]() { l0 = __shfl_sync(0xffffffffu, o[125] + 0.f, lane | 3); l1 = __shfl_sync(0xffffffffu, o[127] + 0.f, lane | 3); };
#define PART(u) make_uint4(pack_bf16(o[8 * u] - l0, o[8 * u + 1] - l0), pack_bf16(o[8 * u + 2] - l1, o[8 * u + 3] - l1), \
                           pack_bf16(o[8 * u + 4] - l0, o[8 * u + 5] - l0), pack_bf16(o[8 * u + 6] - l1, o[8 * u + 7] - l1))
      bool unsafe = !HOT;
      m0 = m1 = 0.f;
#pragma unroll 1
      for (int seg = HOT ? 0 : resume - 1; seg < 2; seg++) {
        ROLE;
        const bool last = __any_sync(0xffffffffu, seg || n1 == 0);
        m0 = m1 = !HOT && unsafe ? -INFINITY : 0.f;
        int first = 1;
        auto tile = [&](auto n_, bool endseg) __attribute__((always_inline)) -> bool {
          constexpr int N = n_.value;
          float s[N / 2]; uint32_t p[N / 4];
          if (!mbar_try_wait(sb + B_FULL + 8 * st, ph)) mbar_wait(sb + B_FULL + 8 * st, ph);
          const bool again = !HOT && N == 112 && first && !seg;
          if (HOT || N == 128) bar_sync(5 + wg, 256);
          else asm volatile("{\n.reg .pred p;\nsetp.eq.u32 p, %1, 0;\n@p bar.sync %0, 256;\n}\n" :: "r"(5 + wg), "r"((uint32_t)again) : "memory");
          wg_fence();
          const uint64_t dQ = desc_k(sb + SM_Q, qo), dK = desc_k(sb, ko + st * 4096);
          qo += (uint32_t)P.zero;
          static_for<0, 16>([&](auto k) { constexpr int kk = (k.value + KROT) & 15, off = (kk >> 2) * 64 + (kk & 3) * 2; wgmma_qk<off, off>(s, dQ, dK, k.value > 0); });
          wg_commit();
          if (HOT || N == 128) bar_arrive(6 - wg, 256);
          else asm volatile("{\n.reg .pred p;\nsetp.eq.u32 p, %1, 0;\n@p bar.arrive %0, 256;\n}\n" :: "r"(6 - wg), "r"((uint32_t)again) : "memory");
          if (HOT && N == 112 && first && !seg) {
            float a0 = 0.f, a1 = 0.f, a2 = 0.f, a3 = 0.f;
#pragma unroll
            for (int i = 0; i < 32; i++) { a0 += o[4 * i] * o[4 * i]; a2 += o[4 * i + 1] * o[4 * i + 1]; a1 += o[4 * i + 2] * o[4 * i + 2]; a3 += o[4 * i + 3] * o[4 * i + 3]; }
            a0 += a2; a1 += a3;
            a0 += __shfl_xor_sync(0xffffffffu, a0, 1); a1 += __shfl_xor_sync(0xffffffffu, a1, 1);
            a0 += __shfl_xor_sync(0xffffffffu, a0, 2); a1 += __shfl_xor_sync(0xffffffffu, a1, 2);
            unsafe = __any_sync(0xffffffffu, bar_red_or(tail ? 7 : 1 + wg, tail ? 256 : 128, wide || !(a0 <= SAFE_N2 / (KS * KS)) || !(a1 <= SAFE_N2 / (KS * KS))));
            if (lane == 0) { asm volatile("st.shared.u8 [%0], %1;" :: "r"(sb + SM_UNSAFE + wg), "r"((uint32_t)unsafe) : "memory"); mbar_arrive(sb + B_EVQ); }
          }
          STAMP(N == 112 && first && !seg && st0, wg, 0);
          wg_wait<0>();
          reg_fence(s);
          if (HOT && N == 112 && unsafe) return true;
          if (endseg) { if (lane == 0) mbar_arrive(sb + B_QEMPTY + 8 * wg); }
          if (!HOT && unsafe) {
            float a0 = fmaxf(s[0], s[1]), a1 = fmaxf(s[2], s[3]);
#pragma unroll
            for (int i = 1; i < N / 8; i++) { a0 = fmaxf(a0, fmaxf(s[4 * i], s[4 * i + 1])); a1 = fmaxf(a1, fmaxf(s[4 * i + 2], s[4 * i + 3])); }
            if (__any_sync(0xffffffffu, (a0 > m0 + TAU) || (a1 > m1 + TAU))) {
              a0 = fmaxf(a0, __shfl_xor_sync(0xffffffffu, a0, 1)); a1 = fmaxf(a1, __shfl_xor_sync(0xffffffffu, a1, 1));
              a0 = fmaxf(a0, __shfl_xor_sync(0xffffffffu, a0, 2)); a1 = fmaxf(a1, __shfl_xor_sync(0xffffffffu, a1, 2));
              const float x0 = ceilf(fmaxf(m0, a0)), x1 = ceilf(fmaxf(m1, a1)), sc0 = ex2(m0 - x0), sc1 = ex2(m1 - x1);
              m0 = x0; m1 = x1;
#pragma unroll
              for (int i = 0; i < 32; i++) { o[4 * i] *= sc0; o[4 * i + 1] *= sc0; o[4 * i + 2] *= sc1; o[4 * i + 3] *= sc1; }
            }
#pragma unroll
            for (int i = 0; i < N / 8; i++) { s[4 * i] -= m0; s[4 * i + 1] -= m0; s[4 * i + 2] -= m1; s[4 * i + 3] -= m1; }
          }
          auto pv = [&](auto k) { wgmma_rs_n256_tb<k.value * 512 + (63 << 16)>(o, p[4 * k.value], p[4 * k.value + 1], p[4 * k.value + 2], p[4 * k.value + 3], dK, k.value > 0 || N == 128 ? 1 : !first); };
#pragma unroll
          for (int i = 0; i < 16; i++) { p[i] = pack_bf16(ex2(s[2 * i]), ex2(s[2 * i + 1])); asm volatile("" : "+r"(p[i]) :: "memory"); }
          reg_fence(o);
          do bar_sync(5 + wg, 256); while (P.zero);
          wg_fence();
          static_for<0, 4>(pv);
          wg_commit();
#pragma unroll
          for (int i = 16; i < N / 4; i++) { p[i] = pack_bf16(ex2(s[2 * i]), ex2(s[2 * i + 1])); asm volatile("" : "+r"(p[i]) :: "memory"); }
          wg_fence();
          static_for<4, N / 16>(pv);
          wg_commit();
          bar_arrive(6 - wg, 256);
          if (N == 128) { wg_wait<1>(); if (endseg && last) { if (lane == 0) mbar_arrive(sb + B_HALF); } }
          wg_wait<0>();
          reg_fence(o); reg_fence(p);
          release(st);
          if (st) { st--; ph ^= 1; } else st = stop;
          return false;
        };
#pragma unroll 1
        for (int left = tail ? 8 - wg : (seg ? W.nb1 : W.nb0); left > 0; left--) { if (tile(IC<112>{}, false)) { resume = 1; return; } STAMP(first && !seg && st0, wg, 4); first = 0; }
#pragma unroll 1
        for (int left = tail ? 32 + wg : (seg ? W.na1 : W.na0); left > 0; left--) tile(IC<128>{}, left == 1);
        STAMP(st0 && last, wg, 6);
        {
        ROLE;
        if (last && fin && !(tail && wg == 1)) break;
        row_sums();
        if (last) mbar_wait(sb + (tail ? B_QEMPTY : B_HALF), 0);
        const uint32_t sp = sb + (tail ? 0 : (last ? (posw >> 12) + wg : (wg ? 4 - 2 * st : 6))) * 32768, sm = sb + SM_ML + (tail ? 0 : wg) * 512;
#pragma unroll
        for (int u = 0; u < 16; u++) sts128(sp + (u * 128 + tid) * 16, PART(u));
        if (t == 0) {
          asm volatile("st.shared.v2.f32 [%0], {%1,%2};" :: "r"(sm + (warp * 16 + g) * 8), "f"(m0), "f"(l0) : "memory");
          asm volatile("st.shared.v2.f32 [%0], {%1,%2};" :: "r"(sm + (warp * 16 + g) * 8 + 64), "f"(m1), "f"(l1) : "memory");
        }
        __syncwarp();
        if (lane == 0) mbar_arrive(sb + B_EVP0 + 8 * wg);
        STAMP(st0 && last, wg, 7);
        if (last) break;
        mbar_wait(sb + B_QFULL + 8 * wg, qph); qph ^= 1;
        uint32_t u; asm volatile("ld.shared.u8 %0, [%1];" : "=r"(u) : "r"(sb + SM_UNSAFE + wg) : "memory");
        unsafe = __any_sync(0xffffffffu, u != 0);
        if (HOT && unsafe) { resume = 2; return; }
        }
      }

      if (P.w[cta_id()].role & R_FIN) {
        ROLE;
        if (!(tail && wg == 1)) {
        row_sums();
        const int rl = wg * 64 + warp * 16 + g;
        uint32_t a[64];
#pragma unroll
        for (int i = 0; i < 64; i++) a[i] = pack_bf16(o[2 * i] - (i & 1 ? l1 : l0), o[2 * i + 1] - (i & 1 ? l1 : l0));
        reg_fence(a);
        {
          float2 e0, e1;
          mbar_wait(sb + B_QFULL + 8 * wg, qph);
          asm volatile("ld.shared.v2.f32 {%0,%1}, [%2];" : "=f"(e0.x), "=f"(e0.y) : "r"(sb + SM_ML + rl * 8) : "memory");
          asm volatile("ld.shared.v2.f32 {%0,%1}, [%2];" : "=f"(e1.x), "=f"(e1.y) : "r"(sb + SM_ML + rl * 8 + 64) : "memory");
          STAMP(st0, wg, 7);
          uint32_t fb0 = 0x3f803f80u, fb1 = 0x3f803f80u;
          const float s0 = l0 + e0.y, s1 = l1 + e1.y;
          const bool odd = __any_sync(0xffffffffu, m0 != e0.x || m1 != e1.x || !(fmaxf(s0, s1) < 0x1p40f) || !(fminf(s0, s1) > 0x1p-40f));
          if (HOT && odd) { resume = 3; return; }
          uint4 v[16];
#pragma unroll
          for (int u = 0; u < 16; u++) v[u] = lds128(sQ + (u * 128 + tid) * 16);
          if (!HOT && odd) {
            const float x0 = fmaxf(m0, e0.x), x1 = fmaxf(m1, e1.x);
            const float d0 = fmaxf(m0 - x0, -1000.f), d1 = fmaxf(m1 - x1, -1000.f), f0 = fmaxf(e0.x - x0, -1000.f), f1 = fmaxf(e1.x - x1, -1000.f);
            l0 = l0 * ex2(d0) + e0.y * ex2(f0); l1 = l1 * ex2(d1) + e1.y * ex2(f1);
            const int E0 = fexp(l0), E1 = fexp(l1);
            const uint32_t fa0 = pow2_bf2((int)d0 - E0), fa1 = pow2_bf2((int)d1 - E1);
            fb0 = pow2_bf2((int)f0 - E0); fb1 = pow2_bf2((int)f1 - E1);
            l0 = __uint_as_float(__float_as_uint(l0) - (E0 << 23)); l1 = __uint_as_float(__float_as_uint(l1) - (E1 << 23));
#pragma unroll
            for (int i = 0; i < 32; i++) { a[2 * i] = hmul2(a[2 * i], fa0); a[2 * i + 1] = hmul2(a[2 * i + 1], fa1); }
          } else { l0 = s0; l1 = s1; }
#pragma unroll
          for (int u = 0; u < 16; u++) {
            a[4 * u] = hfma2(v[u].x, fb0, a[4 * u]); a[4 * u + 1] = hfma2(v[u].y, fb1, a[4 * u + 1]);
            a[4 * u + 2] = hfma2(v[u].z, fb0, a[4 * u + 2]); a[4 * u + 3] = hfma2(v[u].w, fb1, a[4 * u + 3]);
          }
        }
        float fs0, fs1;
        asm("rcp.approx.ftz.f32 %0, %1;" : "=f"(fs0) : "f"(l0 * (KS / KC))); asm("rcp.approx.ftz.f32 %0, %1;" : "=f"(fs1) : "f"(l1 * (KS / KC)));
        STAMP(st0, wg, 8);
        reg_fence(a);
        bar_sync(5 + wg, 256);
        uint64_t dW[4];
        float y0[64], y1[64];
        auto half0 = [&](auto u_) {
          constexpr int u = u_.value;
          if (u % 4 == 0) { mbar_wait(sb + B_WF + 2 * u, 1); wg_fence(); dW[u / 4] = desc_mn(sb, ((posw >> u) & 15) * 2048); }
          wgmma_rs_n128_tb<(u & 3) * 512>(y0, a[4 * u], a[4 * u + 1], a[4 * u + 2], a[4 * u + 3], dW[u / 4], u != 0);
        };
        auto half1 = [&](auto u_) {
          constexpr int u = u_.value;
          wgmma_rs_n128_tb<(u & 3) * 512 + 128>(y1, a[4 * u], a[4 * u + 1], a[4 * u + 2], a[4 * u + 3], dW[u / 4], u != 0);
        };
        const bool wr = W.q0 * 128 + wg * 64 + warp * 16 < NN;
        uint4* po = (uint4*)(P.out + (size_t)(W.q0 * 128 + rl) * 256) + t;
        auto emit = [&](const float* y, uint4* dst) {
          if (wr) {
            red_bf16x8(dst, make_uint4(pack_bf16(y[0] * fs0, y[1] * fs0), pack_bf16(y[4] * fs0, y[5] * fs0), pack_bf16(y[8] * fs0, y[9] * fs0), pack_bf16(y[12] * fs0, y[13] * fs0)));
            red_bf16x8(dst + 8 * 32, make_uint4(pack_bf16(y[2] * fs1, y[3] * fs1), pack_bf16(y[6] * fs1, y[7] * fs1), pack_bf16(y[10] * fs1, y[11] * fs1), pack_bf16(y[14] * fs1, y[15] * fs1)));
          }
          wg_fence();
        };
        static_for<0, 16>(half0);
        wg_commit();
        static_for<0, 4>(half1);
        wg_commit();
        wg_wait<1>();
        reg_fence(y0);
        emit(y0, po); static_for<4, 8>(half1);
        emit(y0 + 16, po + 4); static_for<8, 12>(half1);
        emit(y0 + 32, po + 8); static_for<12, 16>(half1);
        wg_commit();
        bar_arrive(6 - wg, 256);
        emit(y0 + 48, po + 12);
        wg_wait<0>();
        reg_fence(a); reg_fence(y1);
        STAMP(st0, wg, 9);
#pragma unroll
        for (int u = 0; u < 4; u++) emit(y1 + 16 * u, po + 16 + 4 * u);
        }
        if (!tail) { STAMP(st0, wg, 11); DUMP(st0, wg, 0, 16); asm volatile("exit;"); __builtin_unreachable(); }
        if (wg == 1) { bar_sync(6, 256); bar_arrive(5, 256); } else qph ^= 1;
        __syncwarp();
        if (lane == 0) mbar_arrive(sb + B_QEMPTY + 8 * wg);
        fill();
        resume = 4;
      }
        }
#pragma unroll 1
    for (int step = HOT || resume ? 0 : -4; step < (HOT && resume == 4 ? 0 : nloc); step++) {
      ROLE;
      const bool helper = HOT || (resume && resume < 4);
      const bool isw = !HOT && step < 0;
      if (isw) {
        const uint4* src = (const uint4*)(step < -2 ? P.wmsg : P.wv) + ((step & 1) * 128 + wg * 64 + warp) * 32 + lane;
        float cw[8] = {0.f, 0.f, 0.f, 0.f, 0.f, 0.f, 0.f, 0.f};
#pragma unroll 1
        for (int i = 0; i < 16; i++) cp_async16(sQ + sw_byte(i * 4 + warp, lane * 8), src + i * 128);
        cp_commit();
#pragma unroll
        for (int i = 0; i < 8; i++) {
          const uint4 v = __ldg((const uint4*)(step < -2 ? P.wmsg : P.wv) + (248 + i) * 32 + lane);
          const float k = step < -2 ? 0.f : (i == 7 ? -1.0f / 4.5f : -0.5f / 4.5f);
          cw[0] += bf_lo(v.x) * k; cw[1] += bf_hi(v.x) * k; cw[2] += bf_lo(v.y) * k; cw[3] += bf_hi(v.y) * k;
          cw[4] += bf_lo(v.z) * k; cw[5] += bf_hi(v.z) * k; cw[6] += bf_lo(v.w) * k; cw[7] += bf_hi(v.w) * k;
        }
        asm volatile("cp.async.wait_group 0;" ::: "memory");
#pragma unroll 1
        for (int i = 0; i < 16; i++) {
          const uint32_t ad = sQ + sw_byte(i * 4 + warp, lane * 8);
          const uint4 v = lds128(ad);
          uint4 w4 = make_uint4(pack_bf16(bf_lo(v.x) + cw[0], bf_hi(v.x) + cw[1]), pack_bf16(bf_lo(v.y) + cw[2], bf_hi(v.y) + cw[3]),
                                pack_bf16(bf_lo(v.z) + cw[4], bf_hi(v.z) + cw[5]), pack_bf16(bf_lo(v.w) + cw[6], bf_hi(v.w) + cw[7]));
          if (step == -1 && wg * 64 + i * 4 + warp == 127) w4 = make_uint4(0, 0, 0, 0);
          sts128(ad, w4);
        }
        fence_async_smem();
        bar_sync(7, 256);
      } else {
        SSTAMP(0);
        mbar_wait(sb + B_QFULL + 8 * wg, qph); qph ^= 1;
        STAMP(st0 && step == 0, wg, 8);
        SSTAMP(1);
        bar_sync(5 + wg, 256);
        SSTAMP(2);
      }
#pragma unroll 1
      for (int c = 0; c < 4; c++) {
        if (step == 0) mbar_wait(sb + B_WF + 8 * c, helper);
        const int turn2 = helper ? 3 : 4;
        if (c == turn2) bar_sync(5 + wg, 256);
        wg_fence();
        const uint64_t dA = desc_k(sb + SM_Q, wg * 2048 + c * 64), dW = desc_mn(sb, ((posw >> c * 4) & 15) * 2048);
        static_for<0, 4>([&](auto k) { wgmma_ss_n256_tb<k.value * 2, k.value * 512>(o, dA, dW, k.value > 0 ? 1 : c); });
        wg_commit();
        if ((c == 3 || c == turn2 - 1) && !isw) bar_arrive(6 - wg, 256);
        wg_wait<1>();
      }
      wg_wait<0>();
      reg_fence(o);
      {
        STAMP(st0 && step == 0, wg, 9);
        SSTAMP(3);
        if (isw) bar_sync(1 + wg, 128); else if (lane == 0) mbar_arrive(sb + B_QEMPTY + 8 * wg);
        uint8_t* dw = (uint8_t*)(step < -2 ? g_Wmo : g_Wvo) + ((step & 1) * 2 + wg) * 32768 + warp * 8192 + g * 128;
        const int row0 = (W.loc0 + step) * 128 + wg * 64 + warp * 16;
        uint4 r[16];
#pragma unroll
        for (int u = 0; u < 8; u++) { r[2 * u] = ROW0(u); r[2 * u + 1] = ROW1(u); }
        if (isw) {
#pragma unroll
          for (int u = 0; u < 16; u++) *(uint4*)(dw + (u >> 2) * 1024 + ((((u & 2) * 2 + t) ^ g) << 4) + (u & 1) * 4096) = r[u];
        } else if (row0 < NN) {
          uint4* po = (uint4*)(P.out + (size_t)(row0 + g) * 256) + t;
          uint32_t c1 = clk();
#pragma unroll
          for (int u = 0; u < 16; u++) {
            red_bf16x8(po + (u >> 1) * 4 + (u & 1) * 256, r[u]);
            if (!HOT) { c1 += PACE; while ((int)(clk() - c1) < 0) {} }
          }
        }
        if (!HOT && step == -1) { bar_sync(7, 256); if (tid_is(0)) flag_release(F_W); __syncwarp(); STAMP(st0, wg, 3); }
      }
    }
    if (HOT && resume == 4) return;
    finish();
    };
    if (resume < 0) run(std::true_type{});
    else fill();
    run(std::false_type{});
    asm volatile("setmaxnreg.dec.sync.aligned.u32 %0;" :: "n"(504 - 2 * CREG));
  } else {
    STAMP(lane == 0 && warp == 0, 2, 0);
        const int mi = cta >> 3;
    const uint32_t sW = sb + 3 * 32768;
    uint4 wa[4], wb[8];
    {
      const uint4* pq = (const uint4*)(P.wq + ((mi & 15) * 16 + g) * 256) + warp * 8 + t;
      const uint4* pk = (const uint4*)(P.wk + ((cta & 7) * 32 + g) * 256) + warp * 8 + t;
#pragma unroll
      for (int i = 0; i < 4; i++) wa[i] = __ldg(pq + (i >> 1) * 256 + (i & 1) * 4);
#pragma unroll
      for (int i = 0; i < 8; i++) wb[i] = __ldg(pk + (i >> 1) * 256 + (i & 1) * 4);
    }
    if (threadIdx.x == 352) {
      for (int i = 0; i < 3; i++) { mbar_init(sb + B_FULL + 8 * i, 1); mbar_init(sb + B_EMPTY + 8 * i, cta == 130 ? 4 : 8); }
      for (int i = 0; i < 4; i++) mbar_init(sb + B_WF + 8 * i, 1);
      for (int i = 0; i < 2; i++) { mbar_init(sb + B_QFULL + 8 * i, 1); mbar_init(sb + B_QEMPTY + 8 * i, 4); mbar_init(sb + B_EVP0 + 8 * i, 4); }
      mbar_init(sb + B_EVH, 8); mbar_init(sb + B_EVQ, 8); mbar_init(sb + B_HALF, 8); mbar_init(sb + B_BG, 1); mbar_init(sb + B_M0, 1); mbar_init(sb + B_HRD, 1);
      asm volatile("fence.mbarrier_init.release.cluster;" ::: "memory");
    }
    __syncwarp();
    do bar_sync(4, 384); while (P.zero);
    {
#pragma unroll
      for (int n = 0; n < 4; n++) {
        float c[4] = {0.f, 0.f, 0.f, 0.f};
#pragma unroll
        for (int u = 0; u < 2; u++) {
          mma16816(c, wa[u].x, wa[2 + u].x, wa[u].y, wa[2 + u].y, wb[2 * n + u].x, wb[2 * n + u].y);
          mma16816(c, wa[u].z, wa[2 + u].z, wa[u].w, wa[2 + u].w, wb[2 * n + u].z, wb[2 * n + u].w);
        }
        asm volatile("st.shared.v2.f32 [%0], {%1,%2};" :: "r"(sW + ((warp * 16 + g) * 40 + n * 8 + 2 * t) * 4), "f"(c[0]), "f"(c[1]) : "memory");
        asm volatile("st.shared.v2.f32 [%0], {%1,%2};" :: "r"(sW + ((warp * 16 + g + 8) * 40 + n * 8 + 2 * t) * 4), "f"(c[2]), "f"(c[3]) : "memory");
      }
      STAMP(lane == 0 && warp == 0, 2, 7);
      bar_sync(3, 128);
      if (warp < 2) {
        float c[8] = {0.f, 0.f, 0.f, 0.f, 0.f, 0.f, 0.f, 0.f};
#pragma unroll
        for (int k = 0; k < 4; k++) {
          const uint4 v = lds128(sW + ((k * 16 + warp * 8 + g) * 40 + t * 8) * 4), w = lds128(sW + ((k * 16 + warp * 8 + g) * 40 + t * 8 + 4) * 4);
          c[0] += __uint_as_float(v.x); c[1] += __uint_as_float(v.y); c[2] += __uint_as_float(v.z); c[3] += __uint_as_float(v.w);
          c[4] += __uint_as_float(w.x); c[5] += __uint_as_float(w.y); c[6] += __uint_as_float(w.z); c[7] += __uint_as_float(w.w);
        }
        const float ms = 1.4426950408889634f / 16.0f / KS;
        const uint4 m4 = make_uint4(pack_bf16(c[0] * ms, c[1] * ms), pack_bf16(c[2] * ms, c[3] * ms), pack_bf16(c[4] * ms, c[5] * ms), pack_bf16(c[6] * ms, c[7] * ms));
        sts128(sW + 16384 + (warp * 8 + g) * 64 + ((t ^ (g >> 1)) << 4), m4);
      }
    }
    asm volatile("setmaxnreg.dec.sync.aligned.u32 %0;" :: "n"(504 - 2 * CREG));
    STAMP(lane == 0 && warp == 0, 2, 13);
    bar_sync(3, 128);
#define ep1 (lds32(sb + SM_EPOCH) + 1)
    if (threadIdx.x == 256 && cta < 128) {
      fence_async_smem();
      bulk_s2g(g_M + cta * 64, sW + 16384, 1024);
      bulk_commit();
      bulk_wait_all();
      red_relaxed(g_flag + F_M + (cta >> 5));
    }
    __syncwarp();
    ROLE;
    if (warp == 3 && W.own) {
      mbar_wait_w(sb + B_EVH, 0);
      if (W.role < R_SIG) mbar_wait_w(sb + B_WF + 8, 0);
      if (lane == 0) {
        fence_async_smem();
        const int h0 = W.own == 2, nh = W.own == 3 ? 2 : 1;
        bulk_s2g(g_h + W.hp * 4096 + h0 * 2048, sb + SM_Q + h0 * 32768, nh * 32768);
        bulk_s2g(g_stat + W.q0 * 128 + h0 * 64, sb + SM_ML + h0 * 512, nh * 512);
        bulk_commit();
        bulk_wait_read();
        mbar_arrive(sb + B_HRD);
        bulk_wait_all();
        if (W.role >= R_SIG) red_relaxed(g_flag + F_H1 - 1 + W.role / R_SIG);
        red_relaxed(g_flag + F_H);
      }
      __syncwarp();
      STAMP(lane == 0, 2, 6);
    }
    if (warp == 0) {
      if (lane == 0) {
        STAMP(true, 2, 1);
        const uint32_t epoch = ld_relaxed(g_flag + F_EPOCH);
        if (total > 0) {
#pragma unroll
          for (int c = 0; c < 3; c++) mbar_expect_tx(sb + B_WF + 8 * c, c == 0 ? WCH_B - 8192 : WCH_B);
          mbar_expect_tx(sb + B_M0, 8192);
          int c = 0;
#pragma unroll 1
          for (uint32_t it = 0; c < 4; it++) {
            uint4 f;
            asm volatile("ld.relaxed.gpu.global.v4.u32 {%0,%1,%2,%3}, [%4];" : "=r"(f.x), "=r"(f.y), "=r"(f.z), "=r"(f.w) : "l"(g_flag + F_M) : "memory");
            uint32_t tm;
            asm volatile("mad.lo.u32 %0, %1, 32, 32;" : "=r"(tm) : "r"(epoch));
            int ok = (int)(f.x - tm) < 0 ? 0 : (int)(f.y - tm) < 0 ? 1 : (int)(f.z - tm) < 0 ? 2 : (int)(f.w - tm) < 0 ? 3 : 4;
            if (it > (1u << 23)) ok = 4;
            if (ok > c) {
              asm volatile("fence.acquire.gpu;" ::: "memory"); fence_async_gmem();
              if (c == 0) bulk_g2s(sb + (POS_M & 15) * 32768, g_M, 8192, sb + B_M0);
            }
#pragma unroll 1
            for (; c < ok; c++) {
              const uint32_t skip = c == 0 ? 8192 : 0;
              bulk_g2s(sb + ((POS_M >> c * 4) & 15) * 32768 + skip, pofs<const uint8_t>(g_M, c * WCH_B + skip), WCH_B - skip, sb + B_WF + 8 * c);
              STAMP(c == 0, 2, 2);
            }
          }
        }
        asm volatile("st.shared.u32 [%0], %1;" :: "r"(sb + SM_EPOCH), "r"(epoch) : "memory");
        if (total > 0) mbar_expect_tx(sb + B_WF + 24, WCH_B);
        int st = 0, ph = 0, qph = 0;
        const int nsl = tail ? 3 : 2;
        auto next_slot = [&]() { mbar_wait(sb + B_EMPTY + 8 * st, ph); if (++st == nsl) { st = 0; ph ^= 1; } };
        const uint4* wsrc = fin ? g_Wvo : g_Wmo;
        auto w_load = [&](int c0, int c1) {
#pragma unroll 1
          for (int c = c0; c < c1; c++) {
            mbar_expect_tx(sb + B_WF + 8 * c, WCH_B);
            bulk_g2s(sb + ((posw >> c * 4) & 15) * 32768, pofs<const uint8_t>(wsrc, c * WCH_B), WCH_B, sb + B_WF + 8 * c);
          }
        };
        auto q_load = [&](const uint4* src, bool wait_empty) {
#pragma unroll 1
          for (int h = 0; h < 2; h++) {
            if (wait_empty) mbar_wait(sb + B_QEMPTY + 8 * h, qph);
            mbar_expect_tx(sb + B_QFULL + 8 * h, 32768);
            bulk_g2s_last(sb + SM_Q + h * 32768, src + h * 2048, 32768, sb + B_QFULL + 8 * h);
          }
          if (wait_empty) qph ^= 1;
        };
        auto part_out = [&](int slot, int h, uint32_t region, int parity) {
          mbar_wait(sb + B_EVP0 + 8 * h, parity);
          fence_async_smem();
          bulk_s2g(g_part + slot * 4096 + h * 2048, sb + region * 32768, 32768);
          bulk_s2g(g_ml + slot * 128 + h * 64, sb + SM_ML + h * 512, 512);
          bulk_commit();
        };
        auto announce = [&](int f) {
          red_relaxed(g_flag + f);
        };
        if (total > 0) {
          STAMP(true, 2, 3);
          const int q1 = W.q0 + 2 * W.own - 3;
          if (!tail) { flag_wait(F_H1 + (fin ? 0 : W.own), (epoch + 1) * (fin ? NH1_0 : (W.own == 1 ? NH1_1 : NH1_2))); fence_async_gmem(); }
          STAMP(true, 2, 4);
          uint32_t ko = W.k0 * 8192;
#pragma unroll 1
          for (int j = 0; j < total; j++) {
            if (j == (tail ? 0 : 1)) { flag_wait(F_H, (epoch + 1) * NHSIG); fence_async_gmem(); }
            if (j == n0) {
              flag_wait(F_QP + q1 * LN_, (epoch + 1)); fence_async_gmem();
              const uint32_t u = __ldcg(g_unsafe + q1);
              asm volatile("st.shared.u32 [%0], %1;" :: "r"(sb + SM_UNSAFE), "r"(u) : "memory");
              ko = W.k1 * 8192;
            }
            if (j == n0 + 1) q_load(g_qp + q1 * 4096, true);
            if (j == total - 1) { flag_wait(F_W, (epoch + 1)); fence_async_gmem(); if (!tail) w_load(0, 1); }
            const uint32_t bytes = (j < n0 ? j < W.nb0 : j - n0 < W.nb1) ? 112 * 512 : 128 * 512, s0 = st;
            const uint32_t region = (tail ? 1 : 2) + 2 * s0, skip = j == n0 + 1 ? 32768 : 0;
            if (skip) part_out(W.slotA, 0, 6, 0);
            next_slot();
            mbar_expect_tx(sb + B_FULL + 8 * s0, bytes);
            bulk_g2s(sb + region * 32768 + skip, pofs<const uint8_t>(g_h, ko + skip), bytes - skip, sb + B_FULL + 8 * s0);
            if (skip) {
              part_out(W.slotA, 1, region, 0);
              bulk_wait_read();
              bulk_g2s(sb + region * 32768, pofs<const uint8_t>(g_h, ko), skip, sb + B_FULL + 8 * s0);
              bulk_wait_all();
              announce(F_PART + W.slotA * LN_);
            }
            ko += bytes;
          }
          next_slot();
          if (tail) { next_slot(); next_slot(); }
        } else { flag_wait(F_W, (epoch + 1)); fence_async_gmem(); }
        STAMP(true, 2, 5);
        const bool staged = total > 0 && !tail;
        w_load(staged, staged ? (fin ? 2 : 3) : 4);
        if (tail) {
          mbar_wait(sb + B_BG, 0); mbar_wait(sb + B_EVP0 + 8, 0); mbar_arrive(sb + B_QFULL);
          qph = 1; wsrc = g_Wmo;
          mbar_wait(sb + B_QEMPTY, 1);
          w_load(0, 4);
        }
#pragma unroll 1
        for (int i = 0; i < W.nloc; i++) {
          const int tl = W.loc0 + i, last = tl * 128 + 127 < NN ? tl * 128 + 127 : NN - 1;
          flag_wait(F_AGG + ((last >= NGW) + (last >= 4 * NGW) + (last >= 9 * NGW)) * LN_, (epoch + 1) * NGW); fence_async_gmem();
          if (total == 0) g_flag[F_EPOCH] = epoch + 1;
          q_load(g_agg + tl * 4096, total > 0 || i > 0);
        }
        if (fin && !tail) {
          int h = 0, c = 2, have = W.slotB >= 0 ? 2 : 0;
          mbar_wait(sb + B_BG, 0);
#pragma unroll 1
          for (uint32_t it = 0; (h < 2 || c < 4) && it < (1u << 23); it++) {
            if (have < 2) {
              uint2 f;
              asm volatile("ld.relaxed.gpu.global.v2.u32 {%0,%1}, [%2];" : "=r"(f.x), "=r"(f.y) : "l"(g_flag + F_PART + W.slotA * LN_) : "memory");
              have = (int)(f.x - (epoch + 1)) < 0 ? 0 : ((int)(f.y - (epoch + 1)) < 0 ? 1 : 2);
            }
            if (h < have && mbar_try_wait_nb(sb + B_QEMPTY + 8 * h, 0)) {
              asm volatile("fence.acquire.gpu;" ::: "memory"); fence_async_gmem();
              STAMP(true, 2, 14 + h);
              mbar_expect_tx(sb + B_QFULL + 8 * h, 32768 + 512);
              bulk_g2s(sb + SM_ML + h * 512, g_ml + W.slotA * 128 + h * 64, 512, sb + B_QFULL + 8 * h);
              bulk_g2s(sb + SM_Q + h * 32768, g_part + W.slotA * 4096 + h * 2048, 32768, sb + B_QFULL + 8 * h);
              h++;
            }
            const bool half = mbar_try_wait_nb(sb + B_HALF, 0);
            const int c1 = half ? 4 : (h > 0 ? 3 : 2);
            if (c < c1) { w_load(c, c1); c = c1; }
          }
        } else if (!fin && total > 0) {
#pragma unroll 1
          for (int h = 0; h < 2; h++) part_out(W.slotB, h, (posw >> 12) + h, 1);
          asm volatile("cp.async.bulk.wait_group.read 1;" ::: "memory");
          w_load(3, 4);
          asm volatile("cp.async.bulk.wait_group 1;" ::: "memory");
          announce(F_PART + W.slotB * LN_);
          STAMP(true, 2, 14);
          bulk_wait_all();
          announce(F_PART + W.slotB * LN_ + 1);
          STAMP(true, 2, 15);
        }
        DUMP(true, 2, 14, 16);
        DUMP(true, 2, 0, 8);
      }
      return;
    }
  }
    {
      const int gw = cta * 3 + warp - 1;
      ROLE;
      if (total > 0) {
        mbar_wait_w(sb + B_EVQ, 0);
        const uint32_t c0 = clk();
        if (warp == 1 && (W.role & R_PUB)) {
          g_unsafe[W.q0] = lds32(sb + SM_UNSAFE);
#pragma unroll 1
          for (int k = 0; k < 4; k++) {
            __nanosleep(2000);
            if (lane == 0) bulk_s2g(pofs<uint4>(g_qp, W.q0 * 65536 + k * 16384), sb + SM_Q + k * 16384, 16384);
            bulk_commit();
          }
          bulk_wait_all();
          flag_release_w(F_QP + W.q0 * LN_);
        }
        while (__any_sync(0xffffffffu, clk() - c0 < GSTART)) __nanosleep(500);
        STAMP(lane == 0 && warp == 1, 2, 8);
#define ovf_cnt pofs<uint32_t>(g_flag, (F_OVF + (ep1 & 1) * LN_) * 4)
        if (gw == 0) g_flag[F_OVF + ((ep1 + 1) & 1) * LN_] = 0;
#pragma unroll 1
        for (int e0 = gw * 32; e0 < NE; e0 += NGW * 32 * 7) {
          int d[7], s[7], pos[7];
          const int* pd = pofs<const int>(P.dst, (e0 + lane) * 4);
          const int* ps = pofs<const int>(P.src, (e0 + lane) * 4);
#pragma unroll
          for (int k = 0; k < 7; k++) { const bool ok = e0 + k * NGW * 32 < NE; d[k] = ok ? __ldcs(pd + k * NGW * 32) : -1; s[k] = ok ? __ldcs(ps + k * NGW * 32) : 0; }
          uint32_t ov = 0;
#pragma unroll
          for (int k = 0; k < 7; k++) {
            pos[k] = 0;
            if (d[k] >= 0) asm volatile("atom.relaxed.gpu.global.add.u32 %0, [%1], 1;" : "=r"(pos[k]) : "l"(pofs<int>(g_cnt, d[k] << 2)) : "memory");
            s[k] = (uint32_t)(uintptr_t)g_u + s[k] * 512;
            if (d[k] >= 0 && pos[k] < CAP) asm volatile("st.volatile.global.u32 [%0], %1;" :: "l"(pofs<int>(g_bin, (d[k] * CAPS + pos[k]) << 2)), "r"(s[k]) : "memory");
            ov |= (pos[k] >= CAP) << k;
          }
          if (__any_sync(0xffffffffu, ov != 0)) {
            uint32_t at;
            asm volatile("atom.relaxed.gpu.global.add.u32 %0, [%1], %2;" : "=r"(at) : "l"(ovf_cnt), "r"(__popc(ov)) : "memory");
#pragma unroll
            for (int k = 0; k < 7; k++) if ((ov >> k) & 1) g_ovf[at++] = make_int2(d[k], s[k]);
          }
        }
        flag_wait_w(F_H, ep1 * NHSIG);
#pragma unroll 1
        for (int n0 = gw; n0 < NN; n0 += 4 * NGW) {
          uint4 xv[4]; float2 st[4];
#pragma unroll
          for (int k = 0; k < 4; k++) {
            const int n = n0 + k * NGW < NN ? n0 + k * NGW : n0;
            xv[k] = ldcs_v(pofs<const uint4>(P.x, n * 512 + lane * 16));
            st[k] = __ldcg(pofs<const float2>(g_stat, n * 8));
          }
#pragma unroll
          for (int k = 3; k >= 0; k--) {
            const int n = n0 + k * NGW;
            const float a = st[k].x * US, c = fmaf(st[k].y, US, UB + 8388608.0f);
#define FIX(w) __byte_perm(__float_as_uint(fmaf(bf_lo(w), a, c)), __float_as_uint(fmaf(bf_hi(w), a, c)), 0x5410)
            if (n < NN) {
              *pofs<uint4>(P.out, n * 512 + lane * 16) = xv[k];
              *pofs<uint4>(g_u, n * 512 + lane * 16) = make_uint4(FIX(xv[k].x), FIX(xv[k].y), FIX(xv[k].z), FIX(xv[k].w));
            }
          }
        }
        flag_release_w(F_BIN);
        STAMP(lane == 0 && warp == 1, 2, 9);
        flag_wait_w(F_BIN, ep1 * NGW);
        STAMP(lane == 0 && warp == 1, 2, 10);
        const int myn = gw + lane * NGW < NN ? gw + lane * NGW : gw;
        int cnts = __ldcg(g_cnt + myn);
        cnts = gw + lane * NGW < NN ? (cnts > CAP ? CAP + 1 : cnts) | ((int)__ldg((const unsigned short*)P.dinv + myn) << 16) : 0;
        __syncwarp();
        g_cnt[myn] = 0;
        const uint32_t uhi = (uintptr_t)g_u >> 32, lx = lane * 16;
        uint32_t obin = gw * CAPS * 4;
        auto bin = [&](uint32_t ofs, int r, int first) {
          uint32_t en;
          asm volatile("{\n.reg .pred p;\nsetp.lt.u32 p, %2, %3;\nmov.u32 %0, 0;\n@p ld.global.cg.u32 %0, [%1];\n}\n"
                       : "=&r"(en) : "l"(pofs<const uint32_t>(g_bin, ofs + first * 4 + lx / 4)), "r"(lx + first * 16), "r"((__shfl_sync(0xffffffffu, cnts, r) & 0xffff) * 16) : "memory");
          return en;
        };
        uint32_t ent = bin(obin, 0, 0), entn = bin(obin + NGW * CAPS * 4, 1, 0);
        int cd = __shfl_sync(0xffffffffu, cnts, 0), cb = min(cd & 0xffff, CAP), e = 0;
        uint32_t sa[4] = {0, 0, 0, 0}, sh[4] = {0, 0, 0, 0};
        auto add = [&](uint32_t x, uint32_t y, uint32_t z, uint32_t w) {
          sa[0] += x; sa[1] += y; sa[2] += z; sa[3] += w;
          sh[0] += x >> 16; sh[1] += y >> 16; sh[2] += z >> 16; sh[3] += w >> 16;
        };
        int rnd = -1, rows = -1, cdo = 0;
#pragma unroll 1
        for (;;) {
          const bool hold = rows >= 0 && rnd == 8;
          const int m = hold ? 0 : cb - e;
          uint4 v[8];
          if (m >= 8) {
#pragma unroll
            for (int k = 0; k < 8; k++) v[k] = ldcg_v(addr64(__shfl_sync(0xffffffffu, ent, k) + lx, uhi));
          } else {
#pragma unroll
            for (int k = 0; k < 8; k++) {
              v[k] = make_uint4(0, 0, 0, 0);
              if (k < 7) ldcg_if(v[k], addr64(__shfl_sync(0xffffffffu, ent, k) + lx, uhi), k < m);
            }
          }
          if (rows >= 0) {
            const int n = gw + rnd * NGW;
            if (n < NN) {
              const float di = __uint_as_float(cdo & 0xffff0000u) * (1.0f / US), nl = -di * UB * (float)rows;
#define AGG(k) pack_bf16(fmaf((float)(sa[k] - (sh[k] << 16)), di, nl), fmaf((float)sh[k], di, nl))
              *pofs<uint4>(g_agg, ((n >> 3) * 4096 + (n & 7) * 144) ^ ((lx & 0x70) | ((lx & 0x180) << 3))) = make_uint4(AGG(0), AGG(1), AGG(2), AGG(3));
            }
#pragma unroll
            for (int k = 0; k < 4; k++) sa[k] = sh[k] = 0;
            rows = -1;
            if (rnd == 0 || rnd == 3 || rnd == 8 || rnd == NRND - 1) flag_release_w(F_AGG + ((rnd > 0) + (rnd > 3) + (rnd > 8)) * LN_);
            if (rnd == NRND - 1) break;
            if (hold) {
              if (fin && W.slotB >= 0) {
#pragma unroll 1
                for (int k = 0; k < 2; k++) flag_wait_w(F_PART + (k ? W.slotB : W.slotA) * LN_, ep1);
#pragma unroll 1
                for (int b = warp - 1; b < 8; b += 3) {
                  float2* ma = g_ml + W.slotA * 128 + b * 16 + g;
                  const float2* mb = g_ml + W.slotB * 128 + b * 16 + g;
                  const float2 a0 = __ldcg(ma), a1 = __ldcg(ma + 8), b0 = __ldcg(mb), b1 = __ldcg(mb + 8);
                  const float x0 = fmaxf(a0.x, b0.x), x1 = fmaxf(a1.x, b1.x);
                  const float fa0 = ex2(a0.x - x0), fa1 = ex2(a1.x - x1), fb0 = ex2(b0.x - x0), fb1 = ex2(b1.x - x1);
                  __syncwarp();
                  if (t == 0) { ma[0] = make_float2(x0, a0.y * fa0 + b0.y * fb0); ma[8] = make_float2(x1, a1.y * fa1 + b1.y * fb1); }
                  const uint32_t ofs = ((b >> 2) * 2048 + (b & 3) * 32 + lane) * 16;
#pragma unroll 1
                  for (int u = 0; u < 16; u += 4) {
                    uint4* pa = pofs<uint4>(g_part, W.slotA * 65536 + ofs + u * 2048);
                    const uint4* pb = pofs<const uint4>(g_part, W.slotB * 65536 + ofs + u * 2048);
                    uint4 va[4], vb[4];
#pragma unroll
                    for (int k = 0; k < 4; k++) { va[k] = ldcg_v(pa + k * 128); vb[k] = ldcs_v(pb + k * 128); }
#define FOLD(w, fa, fb) pack_bf16(bf_lo(va[k].w) * fa + bf_lo(vb[k].w) * fb, bf_hi(va[k].w) * fa + bf_hi(vb[k].w) * fb)
#pragma unroll
                    for (int k = 3; k >= 0; k--) pa[k * 128] = make_uint4(FOLD(x, fa0, fb0), FOLD(y, fa1, fb1), FOLD(z, fa0, fb0), FOLD(w, fa1, fb1));
                  }
                }
                bar_sync(3, 96);
                if (warp == 1) asm volatile("fence.acq_rel.gpu;" ::: "memory");
              }
              if (fin && warp == 1 && lane == 0) mbar_arrive(sb + B_BG);
              while (__any_sync(0xffffffffu, clk() - c0 < GPAUSE)) __nanosleep(500);
              continue;
            }
          }
#define SUM8(f) (v[7].f + v[6].f + v[5].f + v[4].f + v[3].f + v[2].f + v[1].f + v[0].f)
          add(SUM8(x), SUM8(y), SUM8(z), SUM8(w));
          e += 8;
          if (e < cb) {
            ent = __shfl_down_sync(0xffffffffu, ent, 8);
            if (e == 32) ent = bin(obin, rnd + 1, 32);
            continue;
          }
          rnd++; rows = cb; cdo = cd;
          if ((cd & 0xffff) > CAP) {
            const int no = __shfl_sync(0xffffffffu, (int)ld_relaxed(ovf_cnt), 0);
#pragma unroll 1
            for (int i0 = 0; i0 < no; i0 += 32) {
              int2 en = __ldcg(g_ovf + min(i0 + lane, no - 1));
              uint32_t mk = __ballot_sync(0xffffffffu, en.x == gw + rnd * NGW && i0 + lane < no);
              rows += __popc(mk);
#pragma unroll 1
              while (mk) {
                const int bit = __ffs(mk) - 1; mk &= mk - 1;
                const uint4 r = ldcg_v(addr64((uint32_t)__shfl_sync(0xffffffffu, en.y, bit) + lx, uhi));
                add(r.x, r.y, r.z, r.w);
              }
            }
          }
          obin += NGW * CAPS * 4;
          ent = entn; entn = bin(obin + NGW * CAPS * 4, rnd + 2, 0);
          cd = __shfl_sync(0xffffffffu, cnts, rnd + 1); cb = min(cd & 0xffff, CAP); e = 0;
        }
      }
      STAMP(lane == 0 && warp == 1, 2, 11);
      if (warp == 2 && fin && lane == 0) {
        prefetch_l2(pofs<uint8_t>(P.out, W.q0 * 65536), tail ? 8192 : 65536);
        if (W.slotB >= 0) prefetch_l2(pofs<uint8_t>(g_part, W.slotA * 65536), 65536);
        flag_wait(F_W, ep1);
        prefetch_l2(pofs<uint8_t>(g_Wvo, (cta & 63) * 4096), 4096);
      }
      DUMP(warp == 1 && lane == 0, 2, 8, 14);
    }
}

}

extern "C" void kernel_launch(void* const* d_in, const int* in_sizes, int n_in, void* d_out, int out_size) {
  Params P;
  P.x = (const __nv_bfloat16*)d_in[0];
  P.src = (const int*)d_in[1];
  P.dst = (const int*)d_in[2];
  P.dinv = (const __nv_bfloat16*)d_in[3];
  P.wmsg = (const __nv_bfloat16*)d_in[4];
  P.wq = (const __nv_bfloat16*)d_in[5];
  P.wk = (const __nv_bfloat16*)d_in[6];
  P.wv = (const __nv_bfloat16*)d_in[7];
  P.wout = (const __nv_bfloat16*)d_in[8];
  P.out = (__nv_bfloat16*)d_out;
  P.zero = 0;
  for (int c = 0; c < NCTA; c++) P.w[c] = make_work(c);
  static void* scr = nullptr;
  if (!scr) {
    cudaFuncSetAttribute(gps_kernel, cudaFuncAttributeMaxDynamicSharedMemorySize, SMEM_BYTES);
    cudaGetSymbolAddress(&scr, g_scr);
  }
  P.s = (Scratch*)((((uintptr_t)scr + SCR_ALIGN - 1) & ~(uintptr_t)(SCR_ALIGN - 1)) + SCR_OFS);
  P.u = (uint4*)(((uintptr_t)P.s->u + 511) & ~(uintptr_t)511);
  if (((uintptr_t)P.u >> 32) != (((uintptr_t)(P.u + NN * 32) - 1) >> 32)) P.u += NN * 32;
  gps_kernel<<<NCTA, 384, SMEM_BYTES>>>(P);
}
```

```cpp
#include <cuda_runtime.h>
#include <cuda_bf16.h>
#include <stdint.h>
#include <stddef.h>
#include <type_traits>
#define FB 5
#define MB 5
#define GSTART 40000
#define XD 3
#define NTAIL 5
#define PACE 64
#define GPAUSE 112000
#define CREG 224
#define BACKOFF 1000

namespace {

constexpr int NN = 10000;
constexpr int NE = 160000;
constexpr int NQT = 79;
constexpr int NCTA = 132;
constexpr int CAP = 64;
constexpr int CAPS = 64;
constexpr int NHSIG = 105;
constexpr uint32_t WCH_B = 32768;
constexpr int NGW = (NCTA - 1) * 3;
constexpr float TAU = 16.0f;
constexpr float SAFE_N2 = 31.0f, SAFE_C = 0.6f;
#define KOFF 3
#define PSH -8.0f
#define KROT 15
constexpr float US = 256.0f, UB = 4095.0f;
constexpr float KS = 0.25f, KC = KOFF * KS;
constexpr uint32_t KC2 = KOFF == 2 ? 0x3f003f00u : (KOFF == 1 ? 0x3e803e80u : 0x3f403f40u);

constexpr int NAGG = 4;
constexpr int NRND = (NN + NGW - 1) / NGW;
constexpr int NSLOT = 105;
constexpr int F_EPOCH = 0, F_GE = 1, F_H = 2, F_M = 4  , F_H1 = 8  , F_RHO = 11, F_RC = 12, LN_ = 32;
constexpr int F_BIN = LN_, F_W = 2 * LN_, F_OVF = 3 * LN_  , F_QP = 5 * LN_, F_AGG = F_QP + NQT * LN_,
              F_PART = F_AGG + NAGG * LN_, F_END = F_PART + NSLOT * LN_;

struct Scratch {
  uint32_t flag[F_END];
  alignas(4096) uint4 M[8192];
  uint4 Wvo[8192], Wmo[8192];
  float2 ml[NSLOT * 128];
  uint32_t unsafe[96];
  int cnt[NN + 32];
  float2 stat[NQT * 128];
  alignas(4096) uint4 h[NQT * 4096];
  uint4 u[2 * NN * 32 + 32];
  uint4 qp[NQT * 4096];
  uint4 agg[NQT * 4096];
  uint4 part[NSLOT * 4096];
  int bin[NN * CAPS];
  int2 ovf[NE];
};
static_assert(offsetof(Scratch, h) % 128 == 0, "alignment");
#define SCR_ALIGN (2u << 20)
#define SCR_OFS 0
__device__ uint4 g_scr[(sizeof(Scratch) + SCR_ALIGN + SCR_OFS) / 16];
struct alignas(16) Work { short k0, k1; signed char q0, hp, nb0, na0, nb1, na1, slotA, slotB, loc0, nloc, own, role; };
constexpr int R_FIN = 1, R_PUB = 2, R_TAIL = 4, R_SIG = 8  ;
struct Params {
  const __nv_bfloat16 *x, *wq, *wk;
  Scratch* s;
  uint4* u;
  __nv_bfloat16* out;
  const __nv_bfloat16 *wout, *wmsg, *wv, *dinv;
  const int *src, *dst;
  long long zero;
  Work w[NCTA];
};
constexpr int first_cnt(int k) { return 2 * ((k + 6) / 8 - k / 8 + 1); }
constexpr int NH1_0 = 2, NH1_1 = first_cnt(48 * 8 - MB), NH1_2 = first_cnt(48 * 8 - MB + 16 * 8 - (15 - MB) / 2);
constexpr int NSERV = NQT - 52;
inline Work make_work(int c) {
  Work w;
  const int gi = c / 5, r = c % 5, q = gi * 3;
  const bool helper = r & 1, mid = r == 2;
  w.q0 = helper ? q + 1 : q + (r >> 1);
  const int hb1 = (15 - MB) / 2, hb3 = 15 - MB - hb1;
  w.nb0 = helper ? (r == 1 ? hb1 : hb3) : (mid ? MB : FB);
  w.na0 = (helper ? 16 : 48) - w.nb0;
  w.k0 = helper ? (48 * 8 - MB) + (r >> 1) * (16 * 8 - hb1) : 0;
  w.k1 = 48 * 8 - FB;
  w.nb1 = helper ? (FB < 7 ? 7 : 15) - FB : 0;
  w.na1 = helper ? (FB < 7 ? 31 : 32) - w.nb1 : 0;
  w.slotA = 4 * gi + (helper ? r - 1 : (mid ? 0 : (r >> 1) + 1));
  w.slotB = helper ? 4 * gi + r : (mid ? 4 * gi + 2 : -1);
  w.loc0 = NSERV + gi * 2 + (r >> 1);
  w.nloc = helper;
  w.own = helper ? (r + 1) >> 1 : (mid ? 0 : 3);
  w.role = helper ? 0 : (mid ? R_FIN : R_FIN | R_PUB);
  const int k1st[3] = {0, 48 * 8 - MB, 48 * 8 - MB + 16 * 8 - hb1};
  int pos[NQT], sig[NQT];
  for (int i = 0; i < NQT; i++) { pos[i] = i; sig[i] = 0; }
  for (int i = 0; i < 3; i++)
    for (int p = k1st[i] / 8; p <= (k1st[i] + 6) / 8; p++) {
      int m = 1, at = 0;
      while (sig[m]) m += 3;
      while (pos[at] != p) at++;
      pos[at] = pos[m]; pos[m] = p; sig[m] = 1 + i;
    }
  w.hp = c < 131 ? pos[w.q0] : 0;
  if (helper && c < 130) w.role |= sig[w.q0] * R_SIG;
  if (c == 130) { w.nb0 = 15; w.na0 = 65; w.slotA = NSLOT - 1; w.own = 1; w.role = R_FIN | R_TAIL; w.loc0 = NSERV - NTAIL; w.nloc = NTAIL; }
  if (c == 131) { w.nb0 = w.na0 = w.nb1 = w.na1 = 0; w.loc0 = 0; w.nloc = NSERV - NTAIL; w.own = 0; }
  return w;
}
#define g_flag P.s->flag
#define g_M P.s->M
#define g_Wvo P.s->Wvo
#define g_Wmo P.s->Wmo
#define g_ml P.s->ml
#define g_unsafe P.s->unsafe
#define g_cnt P.s->cnt
#define g_h P.s->h
#define g_u P.u
#define g_stat P.s->stat
#define g_qp P.s->qp
#define g_agg P.s->agg
#define g_part P.s->part
#define g_bin P.s->bin
#define g_ovf P.s->ovf

__device__ __forceinline__ uint32_t smem_u32(const void* p) { return (uint32_t)__cvta_generic_to_shared(p); }
__device__ __forceinline__ void mbar_init(uint32_t bar, uint32_t cnt) { asm volatile("mbarrier.init.shared::cta.b64 [%0], %1;" :: "r"(bar), "r"(cnt) : "memory"); }
__device__ __forceinline__ void mbar_arrive(uint32_t bar) { asm volatile("mbarrier.arrive.shared::cta.b64 _, [%0];" :: "r"(bar) : "memory"); }
__device__ __forceinline__ void mbar_expect_tx(uint32_t bar, uint32_t bytes) { asm volatile("mbarrier.arrive.expect_tx.shared::cta.b64 _, [%0], %1;" :: "r"(bar), "r"(bytes) : "memory"); }
__device__ __forceinline__ bool mbar_try_wait(uint32_t bar, uint32_t parity) {
  uint32_t ok;
  asm volatile("{\n.reg .pred p;\nmbarrier.try_wait.parity.shared::cta.b64 p, [%1], %2;\nselp.b32 %0, 1, 0, p;\n}\n" : "=r"(ok) : "r"(bar), "r"(parity) : "memory");
  return ok;
}
__device__ __forceinline__ bool mbar_try_wait_nb(uint32_t bar, uint32_t parity) {
  uint32_t ok;
  asm volatile("{\n.reg .pred p;\nmbarrier.test_wait.parity.shared::cta.b64 p, [%1], %2;\nselp.b32 %0, 1, 0, p;\n}\n" : "=r"(ok) : "r"(bar), "r"(parity) : "memory");
  return ok;
}
__device__ __forceinline__ void mbar_wait(uint32_t bar, uint32_t parity) {
#pragma unroll 1
  for (uint32_t it = 0; it < (1u << 25); it++) if (mbar_try_wait(bar, parity)) break;
}
__device__ __forceinline__ void bulk_s2g(void* dst, uint32_t src, uint32_t bytes) {
  asm volatile("cp.async.bulk.global.shared::cta.bulk_group [%0], [%1], %2;" :: "l"(dst), "r"(src), "r"(bytes) : "memory");
}
__device__ __forceinline__ void bulk_commit() { asm volatile("cp.async.bulk.commit_group;" ::: "memory"); }
__device__ __forceinline__ void bulk_wait_read() { asm volatile("cp.async.bulk.wait_group.read 0;" ::: "memory"); }
__device__ __forceinline__ void bulk_wait_all() { asm volatile("cp.async.bulk.wait_group 0;" ::: "memory"); }
__device__ __forceinline__ bool bar_red_or(int id, int cnt, bool c) {
  uint32_t r;
  asm volatile("{\n.reg .pred p, q;\nsetp.ne.b32 q, %3, 0;\nbar.red.or.pred p, %1, %2, q;\nselp.b32 %0, 1, 0, p;\n}\n"
               : "=r"(r) : "r"(id), "r"(cnt), "r"((uint32_t)c) : "memory");
  return r != 0;
}
template <class T> __device__ __forceinline__ T* pofs(const void* base, uint32_t off) {
  asm volatile("" : "+r"(off));
  return (T*)((uint8_t*)base + off);
}
__device__ __forceinline__ const void* addr64(uint32_t lo, uint32_t hi) { uint64_t a; asm("mov.b64 %0, {%1, %2};" : "=l"(a) : "r"(lo), "r"(hi)); return (const void*)a; }
__device__ __forceinline__ uint4 ldcg_v(const void* a) {
  uint4 v;
  asm volatile("ld.volatile.global.v4.u32 {%0,%1,%2,%3}, [%4];" : "=r"(v.x), "=r"(v.y), "=r"(v.z), "=r"(v.w) : "l"(a) : "memory");
  return v;
}
__device__ __forceinline__ uint4 ldcs_v(const void* a) {
  uint4 v;
  asm volatile("ld.global.cs.v4.u32 {%0,%1,%2,%3}, [%4];" : "=r"(v.x), "=r"(v.y), "=r"(v.z), "=r"(v.w) : "l"(a) : "memory");
  return v;
}
__device__ __forceinline__ void prefetch_l2(const void* a, uint32_t bytes) { asm volatile("cp.async.bulk.prefetch.L2.global [%0], %1;" :: "l"(a), "r"(bytes) : "memory"); }
__device__ __forceinline__ void ldcg_if(uint4& v, const void* a, bool c) {
  asm volatile("{\n.reg .pred p;\nsetp.ne.b32 p, %5, 0;\n@p ld.volatile.global.v4.u32 {%0,%1,%2,%3}, [%4];\n}\n"
               : "+r"(v.x), "+r"(v.y), "+r"(v.z), "+r"(v.w) : "l"(a), "r"((uint32_t)c) : "memory");
}
__device__ __forceinline__ void cp_async16(uint32_t dst, const void* src) {
  asm volatile("cp.async.cg.shared.global [%0], [%1], 16;" :: "r"(dst), "l"(src) : "memory");
}
__device__ __forceinline__ void red_bf16x8(void* a, uint4 v) {
  asm volatile("red.global.add.noftz.v4.bf16x2 [%0], {%1,%2,%3,%4};" :: "l"(a), "r"(v.x), "r"(v.y), "r"(v.z), "r"(v.w) : "memory");
}
__device__ __forceinline__ uint32_t clk() { uint32_t c; asm volatile("mov.u32 %0, %%clock;" : "=r"(c) :: "memory"); return c; }
__device__ __forceinline__ void stsm4(uint32_t a, uint32_t r0, uint32_t r1, uint32_t r2, uint32_t r3) {
  asm volatile("stmatrix.sync.aligned.m8n8.x4.shared.b16 [%0], {%1,%2,%3,%4};" :: "r"(a), "r"(r0), "r"(r1), "r"(r2), "r"(r3) : "memory");
}
__device__ __forceinline__ void ldsm4(uint32_t a, uint32_t& r0, uint32_t& r1, uint32_t& r2, uint32_t& r3) {
  asm volatile("ldmatrix.sync.aligned.m8n8.x4.shared.b16 {%0,%1,%2,%3}, [%4];" : "=r"(r0), "=r"(r1), "=r"(r2), "=r"(r3) : "r"(a) : "memory");
}
__device__ __forceinline__ void red_relaxed(uint32_t* p) { asm volatile("red.relaxed.gpu.global.add.u32 [%0], 1;" :: "l"(p) : "memory"); }
__device__ __forceinline__ uint32_t lds32(uint32_t a) { uint32_t v; asm volatile("ld.shared.u32 %0, [%1];" : "=r"(v) : "r"(a) : "memory"); return v; }
__device__ __forceinline__ void cp_commit() { asm volatile("cp.async.commit_group;" ::: "memory"); }
__device__ __forceinline__ uint32_t hmul2(uint32_t a, uint32_t b) { uint32_t d; asm("mul.rn.bf16x2 %0, %1, %2;" : "=r"(d) : "r"(a), "r"(b)); return d; }
__device__ __forceinline__ uint32_t hfma2(uint32_t a, uint32_t b, uint32_t c) { uint32_t d; asm("fma.rn.bf16x2 %0, %1, %2, %3;" : "=r"(d) : "r"(a), "r"(b), "r"(c)); return d; }
__device__ __forceinline__ uint32_t pow2_bf2(int n) { return (uint32_t)max(n + 127, 0) * 0x00800080u; }
__device__ __forceinline__ int fexp(float x) { return (int)(__float_as_uint(x) >> 23) - 127; }
__device__ __forceinline__ void bulk_g2s(uint32_t dst, const void* src, uint32_t bytes, uint32_t bar) {
  asm volatile("cp.async.bulk.shared::cta.global.mbarrier::complete_tx::bytes [%0], [%1], %2, [%3];"
    :: "r"(dst), "l"(src), "r"(bytes), "r"(bar) : "memory");
}
__device__ __forceinline__ void bulk_g2s_last(uint32_t dst, const void* src, uint32_t bytes, uint32_t bar) {
  asm volatile("{\n.reg .b64 p;\ncreatepolicy.fractional.L2::evict_first.b64 p;\n"
    "cp.async.bulk.shared::cta.global.mbarrier::complete_tx::bytes.L2::cache_hint [%0], [%1], %2, [%3], p;\n}\n"
    :: "r"(dst), "l"(src), "r"(bytes), "r"(bar) : "memory");
}
__device__ __forceinline__ void wg_fence() { asm volatile("wgmma.fence.sync.aligned;" ::: "memory"); }
__device__ __forceinline__ void wg_commit() { asm volatile("wgmma.commit_group.sync.aligned;" ::: "memory"); }
template<int N> __device__ __forceinline__ void wg_wait() { asm volatile("wgmma.wait_group.sync.aligned %0;" :: "n"(N) : "memory"); }
__device__ __forceinline__ void bar_sync(int id, int cnt) { asm volatile("bar.sync %0, %1;" :: "r"(id), "r"(cnt) : "memory"); }
__device__ __forceinline__ void fence_async_smem() { asm volatile("fence.proxy.async.shared::cta;" ::: "memory"); }
__device__ __forceinline__ void fence_async_gmem() { asm volatile("fence.proxy.async.global;" ::: "memory"); }
__device__ __forceinline__ void bar_arrive(int id, int cnt) { asm volatile("bar.arrive %0, %1;" :: "r"(id), "r"(cnt) : "memory"); }
__device__ __forceinline__ void red_release(uint32_t* p) { asm volatile("red.release.gpu.global.add.u32 [%0], 1;" :: "l"(p) : "memory"); }
__device__ __forceinline__ void red_release_w(uint32_t* p) {
  __syncwarp();
  asm volatile("{\n.reg .pred q;\n.reg .b32 l;\nmov.u32 l, %%laneid;\nsetp.eq.u32 q, l, 0;\n@q fence.release.gpu;\n@q red.relaxed.gpu.global.add.u32 [%0], 1;\n}\n" :: "l"(p) : "memory");
}
__device__ __forceinline__ void mbar_wait_w(uint32_t bar, uint32_t parity) {
#pragma unroll 1
  for (uint32_t it = 0; it < (1u << 25); it++) if (__all_sync(0xffffffffu, mbar_try_wait(bar, parity))) break;
}
#define flag_release_w(f) red_release_w(g_flag + (f))
#define flag_wait_w(f, target) poll_acquire_w(g_flag + (f), target)
#define flag_release(f) red_release(g_flag + (f))
__device__ __forceinline__ uint32_t ld_relaxed(const uint32_t* p) {
  uint32_t v; asm volatile("ld.relaxed.gpu.global.u32 %0, [%1];" : "=r"(v) : "l"(p) : "memory"); return v;
}
#define flag_wait(f, target) poll_acquire(g_flag + (f), target)
__device__ __forceinline__ void poll_acquire(const uint32_t* p, uint32_t target) {
#pragma unroll 1
  for (uint32_t it = 0; it < (1u << 23); it++) if ((int)(ld_relaxed(p) - target) >= 0) break;
  asm volatile("fence.acquire.gpu;" ::: "memory");
}
__device__ __forceinline__ void poll_acquire_w(const uint32_t* p, uint32_t target) {
#pragma unroll 1
  for (uint32_t it = 0; it < (1u << 23); it++) {
    if (__all_sync(0xffffffffu, (int)(ld_relaxed(p) - target) >= 0)) break;
    if (BACKOFF) __nanosleep(BACKOFF);
  }
  asm volatile("fence.acquire.gpu;" ::: "memory");
}
template<int N> __device__ __forceinline__ void reg_fence(float (&d)[N]) {
#pragma unroll
  for (int i = 0; i < N; i++) asm volatile("" : "+f"(d[i]) :: "memory");
}
template<int N> __device__ __forceinline__ void reg_fence(uint32_t (&d)[N]) {
#pragma unroll
  for (int i = 0; i < N; i++) asm volatile("" : "+r"(d[i]) :: "memory");
}
__device__ __forceinline__ float ex2(float x) { float y; asm("ex2.approx.ftz.f32 %0, %1;" : "=f"(y) : "f"(x)); return y; }
__device__ __forceinline__ uint32_t pack_bf16(float lo, float hi) { uint32_t r; asm("cvt.rn.bf16x2.f32 %0, %1, %2;" : "=r"(r) : "f"(hi), "f"(lo)); return r; }
__device__ __forceinline__ float bf_lo(uint32_t w) { return __uint_as_float(w << 16); }
__device__ __forceinline__ float bf_hi(uint32_t w) { return __uint_as_float(w & 0xffff0000u); }
__device__ __forceinline__ uint64_t desc_k(uint32_t addr, uint32_t add) { return (uint64_t)((((addr & 0x3FFFF) >> 4) | (1u << 16)) + add) | (0x40000100ull << 32); }
__device__ __forceinline__ uint64_t desc_mn(uint32_t addr, uint32_t add) { return (uint64_t)((((addr & 0x3FFFF) >> 4) | ((1024u >> 4) << 16)) + add) | (0x40000100ull << 32); }
__device__ __forceinline__ uint64_t desc_m(uint32_t addr, uint32_t add) { return (uint64_t)((((addr & 0x3FFFF) >> 4) | ((1024u >> 4) << 16)) + add) | (0x80000020ull << 32); }
__device__ __forceinline__ void sts128(uint32_t a, uint4 v) { asm volatile("st.shared.v4.u32 [%0], {%1,%2,%3,%4};" :: "r"(a), "r"(v.x), "r"(v.y), "r"(v.z), "r"(v.w) : "memory"); }
__device__ __forceinline__ uint4 lds128(uint32_t a) { uint4 v; asm volatile("ld.shared.v4.u32 {%0,%1,%2,%3}, [%4];" : "=r"(v.x), "=r"(v.y), "=r"(v.z), "=r"(v.w) : "r"(a) : "memory"); return v; }
__device__ __forceinline__ void mma16816(float (&c)[4], uint32_t a0, uint32_t a1, uint32_t a2, uint32_t a3, uint32_t b0, uint32_t b1) {
  asm volatile("mma.sync.aligned.m16n8k16.row.col.f32.bf16.bf16.f32 {%0,%1,%2,%3}, {%4,%5,%6,%7}, {%8,%9}, {%0,%1,%2,%3};"
    : "+f"(c[0]), "+f"(c[1]), "+f"(c[2]), "+f"(c[3]) : "r"(a0), "r"(a1), "r"(a2), "r"(a3), "r"(b0), "r"(b1));
}
__device__ __forceinline__ uint32_t sw_byte(int r, int c) {
  return (uint32_t)((r >> 3) * 4096 + (c >> 6) * 1024 + (r & 7) * 128 + ((((c >> 3) & 7) ^ (r & 7)) << 4) + (c & 7) * 2);
}
__device__ __forceinline__ int cta_id() { int c; asm volatile("mov.u32 %0, %%ctaid.x;" : "=r"(c)); return c; }
__device__ __forceinline__ bool tid_is(int v) { int t; asm volatile("mov.u32 %0, %%tid.x;" : "=r"(t)); return t == v; }
#define STAMP(cond, who, i)
#define CSTAMP(cond, who, i)
#define DUMP(cond, who, i0, i1)
#define XSTAMP(cond, i)
#define SSTAMP(i)

template <int OA, int OB> __device__ __forceinline__ void wgmma_ss_n256_tb(float (&d)[128], uint64_t da, uint64_t db, int scale_d) {
  asm volatile("{\n.reg .pred p;\n.reg .b64 a, b;\nsetp.ne.b32 p, %130, 0;\nadd.s64 a, %128, %131;\nadd.s64 b, %129, %132;\n"
    "wgmma.mma_async.sync.aligned.m64n256k16.f32.bf16.bf16 "
    "{%0, %1, %2, %3, %4, %5, %6, %7, %8, %9, %10, %11, %12, %13, %14, %15, %16, %17, %18, %19, %20, %21, %22, %23, %24, %25, %26, %27, %28, %29, %30, %31, %32, %33, %34, %35, %36, %37, %38, %39, %40, %41, %42, %43, %44, %45, %46, %47, %48, %49, %50, %51, %52, %53, %54, %55, %56, %57, %58, %59, %60, %61, %62, %63, %64, %65, %66, %67, %68, %69, %70, %71, %72, %73, %74, %75, %76, %77, %78, %79, %80, %81, %82, %83, %84, %85, %86, %87, %88, %89, %90, %91, %92, %93, %94, %95, %96, %97, %98, %99, %100, %101, %102, %103, %104, %105, %106, %107, %108, %109, %110, %111, %112, %113, %114, %115, %116, %117, %118, %119, %120, %121, %122, %123, %124, %125, %126, %127}, "
    "a, b, p, 1, 1, 0, 1;\n}\n"
    : "+f"(d[0]), "+f"(d[1]), "+f"(d[2]), "+f"(d[3]), "+f"(d[4]), "+f"(d[5]), "+f"(d[6]), "+f"(d[7]), "+f"(d[8]), "+f"(d[9]), "+f"(d[10]), "+f"(d[11]), "+f"(d[12]), "+f"(d[13]), "+f"(d[14]), "+f"(d[15]), "+f"(d[16]), "+f"(d[17]), "+f"(d[18]), "+f"(d[19]), "+f"(d[20]), "+f"(d[21]), "+f"(d[22]), "+f"(d[23]), "+f"(d[24]), "+f"(d[25]), "+f"(d[26]), "+f"(d[27]), "+f"(d[28]), "+f"(d[29]), "+f"(d[30]), "+f"(d[31]), "+f"(d[32]), "+f"(d[33]), "+f"(d[34]), "+f"(d[35]), "+f"(d[36]), "+f"(d[37]), "+f"(d[38]), "+f"(d[39]), "+f"(d[40]), "+f"(d[41]), "+f"(d[42]), "+f"(d[43]), "+f"(d[44]), "+f"(d[45]), "+f"(d[46]), "+f"(d[47]), "+f"(d[48]), "+f"(d[49]), "+f"(d[50]), "+f"(d[51]), "+f"(d[52]), "+f"(d[53]), "+f"(d[54]), "+f"(d[55]), "+f"(d[56]), "+f"(d[57]), "+f"(d[58]), "+f"(d[59]), "+f"(d[60]), "+f"(d[61]), "+f"(d[62]), "+f"(d[63]), "+f"(d[64]), "+f"(d[65]), "+f"(d[66]), "+f"(d[67]), "+f"(d[68]), "+f"(d[69]), "+f"(d[70]), "+f"(d[71]), "+f"(d[72]), "+f"(d[73]), "+f"(d[74]), "+f"(d[75]), "+f"(d[76]), "+f"(d[77]), "+f"(d[78]), "+f"(d[79]), "+f"(d[80]), "+f"(d[81]), "+f"(d[82]), "+f"(d[83]), "+f"(d[84]), "+f"(d[85]), "+f"(d[86]), "+f"(d[87]), "+f"(d[88]), "+f"(d[89]), "+f"(d[90]), "+f"(d[91]), "+f"(d[92]), "+f"(d[93]), "+f"(d[94]), "+f"(d[95]), "+f"(d[96]), "+f"(d[97]), "+f"(d[98]), "+f"(d[99]), "+f"(d[100]), "+f"(d[101]), "+f"(d[102]), "+f"(d[103]), "+f"(d[104]), "+f"(d[105]), "+f"(d[106]), "+f"(d[107]), "+f"(d[108]), "+f"(d[109]), "+f"(d[110]), "+f"(d[111]), "+f"(d[112]), "+f"(d[113]), "+f"(d[114]), "+f"(d[115]), "+f"(d[116]), "+f"(d[117]), "+f"(d[118]), "+f"(d[119]), "+f"(d[120]), "+f"(d[121]), "+f"(d[122]), "+f"(d[123]), "+f"(d[124]), "+f"(d[125]), "+f"(d[126]), "+f"(d[127])
    : "l"(da), "l"(db), "r"(scale_d), "n"(OA), "n"(OB));
}
template <int OA, int OB> __device__ __forceinline__ void wgmma_qk(float (&d)[64], uint64_t da, uint64_t db, int scale_d) {
  asm volatile("{\n.reg .pred p;\n.reg .b64 a, b;\nsetp.ne.b32 p, %66, 0;\nadd.s64 a, %64, %67;\nadd.s64 b, %65, %68;\n"
    "wgmma.mma_async.sync.aligned.m64n128k16.f32.bf16.bf16 "
    "{%0, %1, %2, %3, %4, %5, %6, %7, %8, %9, %10, %11, %12, %13, %14, %15, %16, %17, %18, %19, %20, %21, %22, %23, %24, %25, %26, %27, %28, %29, %30, %31, %32, %33, %34, %35, %36, %37, %38, %39, %40, %41, %42, %43, %44, %45, %46, %47, %48, %49, %50, %51, %52, %53, %54, %55, %56, %57, %58, %59, %60, %61, %62, %63}, "
    "a, b, p, 1, 1, 0, 0;\n}\n"
    : "+f"(d[0]), "+f"(d[1]), "+f"(d[2]), "+f"(d[3]), "+f"(d[4]), "+f"(d[5]), "+f"(d[6]), "+f"(d[7]), "+f"(d[8]), "+f"(d[9]), "+f"(d[10]), "+f"(d[11]), "+f"(d[12]), "+f"(d[13]), "+f"(d[14]), "+f"(d[15]), "+f"(d[16]), "+f"(d[17]), "+f"(d[18]), "+f"(d[19]), "+f"(d[20]), "+f"(d[21]), "+f"(d[22]), "+f"(d[23]), "+f"(d[24]), "+f"(d[25]), "+f"(d[26]), "+f"(d[27]), "+f"(d[28]), "+f"(d[29]), "+f"(d[30]), "+f"(d[31]), "+f"(d[32]), "+f"(d[33]), "+f"(d[34]), "+f"(d[35]), "+f"(d[36]), "+f"(d[37]), "+f"(d[38]), "+f"(d[39]), "+f"(d[40]), "+f"(d[41]), "+f"(d[42]), "+f"(d[43]), "+f"(d[44]), "+f"(d[45]), "+f"(d[46]), "+f"(d[47]), "+f"(d[48]), "+f"(d[49]), "+f"(d[50]), "+f"(d[51]), "+f"(d[52]), "+f"(d[53]), "+f"(d[54]), "+f"(d[55]), "+f"(d[56]), "+f"(d[57]), "+f"(d[58]), "+f"(d[59]), "+f"(d[60]), "+f"(d[61]), "+f"(d[62]), "+f"(d[63])
    : "l"(da), "l"(db), "r"(scale_d), "n"(OA), "n"(OB));
}
template <int OA, int OB> __device__ __forceinline__ void wgmma_qk(float (&d)[56], uint64_t da, uint64_t db, int scale_d) {
  asm volatile("{\n.reg .pred p;\n.reg .b64 a, b;\nsetp.ne.b32 p, %58, 0;\nadd.s64 a, %56, %59;\nadd.s64 b, %57, %60;\n"
    "wgmma.mma_async.sync.aligned.m64n112k16.f32.bf16.bf16 "
    "{%0, %1, %2, %3, %4, %5, %6, %7, %8, %9, %10, %11, %12, %13, %14, %15, %16, %17, %18, %19, %20, %21, %22, %23, %24, %25, %26, %27, %28, %29, %30, %31, %32, %33, %34, %35, %36, %37, %38, %39, %40, %41, %42, %43, %44, %45, %46, %47, %48, %49, %50, %51, %52, %53, %54, %55}, "
    "a, b, p, 1, 1, 0, 0;\n}\n"
    : "+f"(d[0]), "+f"(d[1]), "+f"(d[2]), "+f"(d[3]), "+f"(d[4]), "+f"(d[5]), "+f"(d[6]), "+f"(d[7]), "+f"(d[8]), "+f"(d[9]), "+f"(d[10]), "+f"(d[11]), "+f"(d[12]), "+f"(d[13]), "+f"(d[14]), "+f"(d[15]), "+f"(d[16]), "+f"(d[17]), "+f"(d[18]), "+f"(d[19]), "+f"(d[20]), "+f"(d[21]), "+f"(d[22]), "+f"(d[23]), "+f"(d[24]), "+f"(d[25]), "+f"(d[26]), "+f"(d[27]), "+f"(d[28]), "+f"(d[29]), "+f"(d[30]), "+f"(d[31]), "+f"(d[32]), "+f"(d[33]), "+f"(d[34]), "+f"(d[35]), "+f"(d[36]), "+f"(d[37]), "+f"(d[38]), "+f"(d[39]), "+f"(d[40]), "+f"(d[41]), "+f"(d[42]), "+f"(d[43]), "+f"(d[44]), "+f"(d[45]), "+f"(d[46]), "+f"(d[47]), "+f"(d[48]), "+f"(d[49]), "+f"(d[50]), "+f"(d[51]), "+f"(d[52]), "+f"(d[53]), "+f"(d[54]), "+f"(d[55])
    : "l"(da), "l"(db), "r"(scale_d), "n"(OA), "n"(OB));
}
template <int OB> __device__ __forceinline__ void wgmma_rs_n256_tb(float (&d)[128], uint32_t a0, uint32_t a1, uint32_t a2, uint32_t a3, uint64_t db, int scale_d) {
  asm volatile("{\n.reg .pred p;\n.reg .b64 b;\nsetp.ne.b32 p, %133, 0;\nadd.s64 b, %132, %134;\n"
    "wgmma.mma_async.sync.aligned.m64n256k16.f32.bf16.bf16 "
    "{%0, %1, %2, %3, %4, %5, %6, %7, %8, %9, %10, %11, %12, %13, %14, %15, %16, %17, %18, %19, %20, %21, %22, %23, %24, %25, %26, %27, %28, %29, %30, %31, %32, %33, %34, %35, %36, %37, %38, %39, %40, %41, %42, %43, %44, %45, %46, %47, %48, %49, %50, %51, %52, %53, %54, %55, %56, %57, %58, %59, %60, %61, %62, %63, %64, %65, %66, %67, %68, %69, %70, %71, %72, %73, %74, %75, %76, %77, %78, %79, %80, %81, %82, %83, %84, %85, %86, %87, %88, %89, %90, %91, %92, %93, %94, %95, %96, %97, %98, %99, %100, %101, %102, %103, %104, %105, %106, %107, %108, %109, %110, %111, %112, %113, %114, %115, %116, %117, %118, %119, %120, %121, %122, %123, %124, %125, %126, %127}, "
    "{%128, %129, %130, %131}, b, p, 1, 1, 1;\n}\n"
    : "+f"(d[0]), "+f"(d[1]), "+f"(d[2]), "+f"(d[3]), "+f"(d[4]), "+f"(d[5]), "+f"(d[6]), "+f"(d[7]), "+f"(d[8]), "+f"(d[9]), "+f"(d[10]), "+f"(d[11]), "+f"(d[12]), "+f"(d[13]), "+f"(d[14]), "+f"(d[15]), "+f"(d[16]), "+f"(d[17]), "+f"(d[18]), "+f"(d[19]), "+f"(d[20]), "+f"(d[21]), "+f"(d[22]), "+f"(d[23]), "+f"(d[24]), "+f"(d[25]), "+f"(d[26]), "+f"(d[27]), "+f"(d[28]), "+f"(d[29]), "+f"(d[30]), "+f"(d[31]), "+f"(d[32]), "+f"(d[33]), "+f"(d[34]), "+f"(d[35]), "+f"(d[36]), "+f"(d[37]), "+f"(d[38]), "+f"(d[39]), "+f"(d[40]), "+f"(d[41]), "+f"(d[42]), "+f"(d[43]), "+f"(d[44]), "+f"(d[45]), "+f"(d[46]), "+f"(d[47]), "+f"(d[48]), "+f"(d[49]), "+f"(d[50]), "+f"(d[51]), "+f"(d[52]), "+f"(d[53]), "+f"(d[54]), "+f"(d[55]), "+f"(d[56]), "+f"(d[57]), "+f"(d[58]), "+f"(d[59]), "+f"(d[60]), "+f"(d[61]), "+f"(d[62]), "+f"(d[63]), "+f"(d[64]), "+f"(d[65]), "+f"(d[66]), "+f"(d[67]), "+f"(d[68]), "+f"(d[69]), "+f"(d[70]), "+f"(d[71]), "+f"(d[72]), "+f"(d[73]), "+f"(d[74]), "+f"(d[75]), "+f"(d[76]), "+f"(d[77]), "+f"(d[78]), "+f"(d[79]), "+f"(d[80]), "+f"(d[81]), "+f"(d[82]), "+f"(d[83]), "+f"(d[84]), "+f"(d[85]), "+f"(d[86]), "+f"(d[87]), "+f"(d[88]), "+f"(d[89]), "+f"(d[90]), "+f"(d[91]), "+f"(d[92]), "+f"(d[93]), "+f"(d[94]), "+f"(d[95]), "+f"(d[96]), "+f"(d[97]), "+f"(d[98]), "+f"(d[99]), "+f"(d[100]), "+f"(d[101]), "+f"(d[102]), "+f"(d[103]), "+f"(d[104]), "+f"(d[105]), "+f"(d[106]), "+f"(d[107]), "+f"(d[108]), "+f"(d[109]), "+f"(d[110]), "+f"(d[111]), "+f"(d[112]), "+f"(d[113]), "+f"(d[114]), "+f"(d[115]), "+f"(d[116]), "+f"(d[117]), "+f"(d[118]), "+f"(d[119]), "+f"(d[120]), "+f"(d[121]), "+f"(d[122]), "+f"(d[123]), "+f"(d[124]), "+f"(d[125]), "+f"(d[126]), "+f"(d[127])
    : "r"(a0), "r"(a1), "r"(a2), "r"(a3), "l"(db), "r"(scale_d), "n"(OB));
}
template <int OB> __device__ __forceinline__ void wgmma_rs_n256_tb_first(float (&d)[128], uint32_t a0, uint32_t a1, uint32_t a2, uint32_t a3, uint64_t db) {
  asm volatile("{\n.reg .pred p;\n.reg .b64 b;\nsetp.ne.b32 p, 0, 0;\nadd.s64 b, %132, %133;\n"
    "wgmma.mma_async.sync.aligned.m64n256k16.f32.bf16.bf16 "
    "{%0, %1, %2, %3, %4, %5, %6, %7, %8, %9, %10, %11, %12, %13, %14, %15, %16, %17, %18, %19, %20, %21, %22, %23, %24, %25, %26, %27, %28, %29, %30, %31, %32, %33, %34, %35, %36, %37, %38, %39, %40, %41, %42, %43, %44, %45, %46, %47, %48, %49, %50, %51, %52, %53, %54, %55, %56, %57, %58, %59, %60, %61, %62, %63, %64, %65, %66, %67, %68, %69, %70, %71, %72, %73, %74, %75, %76, %77, %78, %79, %80, %81, %82, %83, %84, %85, %86, %87, %88, %89, %90, %91, %92, %93, %94, %95, %96, %97, %98, %99, %100, %101, %102, %103, %104, %105, %106, %107, %108, %109, %110, %111, %112, %113, %114, %115, %116, %117, %118, %119, %120, %121, %122, %123, %124, %125, %126, %127}, "
    "{%128, %129, %130, %131}, b, p, 1, 1, 1;\n}\n"
    : "=f"(d[0]), "=f"(d[1]), "=f"(d[2]), "=f"(d[3]), "=f"(d[4]), "=f"(d[5]), "=f"(d[6]), "=f"(d[7]), "=f"(d[8]), "=f"(d[9]), "=f"(d[10]), "=f"(d[11]), "=f"(d[12]), "=f"(d[13]), "=f"(d[14]), "=f"(d[15]), "=f"(d[16]), "=f"(d[17]), "=f"(d[18]), "=f"(d[19]), "=f"(d[20]), "=f"(d[21]), "=f"(d[22]), "=f"(d[23]), "=f"(d[24]), "=f"(d[25]), "=f"(d[26]), "=f"(d[27]), "=f"(d[28]), "=f"(d[29]), "=f"(d[30]), "=f"(d[31]), "=f"(d[32]), "=f"(d[33]), "=f"(d[34]), "=f"(d[35]), "=f"(d[36]), "=f"(d[37]), "=f"(d[38]), "=f"(d[39]), "=f"(d[40]), "=f"(d[41]), "=f"(d[42]), "=f"(d[43]), "=f"(d[44]), "=f"(d[45]), "=f"(d[46]), "=f"(d[47]), "=f"(d[48]), "=f"(d[49]), "=f"(d[50]), "=f"(d[51]), "=f"(d[52]), "=f"(d[53]), "=f"(d[54]), "=f"(d[55]), "=f"(d[56]), "=f"(d[57]), "=f"(d[58]), "=f"(d[59]), "=f"(d[60]), "=f"(d[61]), "=f"(d[62]), "=f"(d[63]), "=f"(d[64]), "=f"(d[65]), "=f"(d[66]), "=f"(d[67]), "=f"(d[68]), "=f"(d[69]), "=f"(d[70]), "=f"(d[71]), "=f"(d[72]), "=f"(d[73]), "=f"(d[74]), "=f"(d[75]), "=f"(d[76]), "=f"(d[77]), "=f"(d[78]), "=f"(d[79]), "=f"(d[80]), "=f"(d[81]), "=f"(d[82]), "=f"(d[83]), "=f"(d[84]), "=f"(d[85]), "=f"(d[86]), "=f"(d[87]), "=f"(d[88]), "=f"(d[89]), "=f"(d[90]), "=f"(d[91]), "=f"(d[92]), "=f"(d[93]), "=f"(d[94]), "=f"(d[95]), "=f"(d[96]), "=f"(d[97]), "=f"(d[98]), "=f"(d[99]), "=f"(d[100]), "=f"(d[101]), "=f"(d[102]), "=f"(d[103]), "=f"(d[104]), "=f"(d[105]), "=f"(d[106]), "=f"(d[107]), "=f"(d[108]), "=f"(d[109]), "=f"(d[110]), "=f"(d[111]), "=f"(d[112]), "=f"(d[113]), "=f"(d[114]), "=f"(d[115]), "=f"(d[116]), "=f"(d[117]), "=f"(d[118]), "=f"(d[119]), "=f"(d[120]), "=f"(d[121]), "=f"(d[122]), "=f"(d[123]), "=f"(d[124]), "=f"(d[125]), "=f"(d[126]), "=f"(d[127])
    : "r"(a0), "r"(a1), "r"(a2), "r"(a3), "l"(db), "n"(OB));
}
template <int OB> __device__ __forceinline__ void wgmma_rs_n128_tb(float (&d)[64], uint32_t a0, uint32_t a1, uint32_t a2, uint32_t a3, uint64_t db, int scale_d) {
  asm volatile("{\n.reg .pred p;\n.reg .b64 b;\nsetp.ne.b32 p, %69, 0;\nadd.s64 b, %68, %70;\n"
    "wgmma.mma_async.sync.aligned.m64n128k16.f32.bf16.bf16 "
    "{%0, %1, %2, %3, %4, %5, %6, %7, %8, %9, %10, %11, %12, %13, %14, %15, %16, %17, %18, %19, %20, %21, %22, %23, %24, %25, %26, %27, %28, %29, %30, %31, %32, %33, %34, %35, %36, %37, %38, %39, %40, %41, %42, %43, %44, %45, %46, %47, %48, %49, %50, %51, %52, %53, %54, %55, %56, %57, %58, %59, %60, %61, %62, %63}, "
    "{%64, %65, %66, %67}, b, p, 1, 1, 1;\n}\n"
    : "+f"(d[0]), "+f"(d[1]), "+f"(d[2]), "+f"(d[3]), "+f"(d[4]), "+f"(d[5]), "+f"(d[6]), "+f"(d[7]), "+f"(d[8]), "+f"(d[9]), "+f"(d[10]), "+f"(d[11]), "+f"(d[12]), "+f"(d[13]), "+f"(d[14]), "+f"(d[15]), "+f"(d[16]), "+f"(d[17]), "+f"(d[18]), "+f"(d[19]), "+f"(d[20]), "+f"(d[21]), "+f"(d[22]), "+f"(d[23]), "+f"(d[24]), "+f"(d[25]), "+f"(d[26]), "+f"(d[27]), "+f"(d[28]), "+f"(d[29]), "+f"(d[30]), "+f"(d[31]), "+f"(d[32]), "+f"(d[33]), "+f"(d[34]), "+f"(d[35]), "+f"(d[36]), "+f"(d[37]), "+f"(d[38]), "+f"(d[39]), "+f"(d[40]), "+f"(d[41]), "+f"(d[42]), "+f"(d[43]), "+f"(d[44]), "+f"(d[45]), "+f"(d[46]), "+f"(d[47]), "+f"(d[48]), "+f"(d[49]), "+f"(d[50]), "+f"(d[51]), "+f"(d[52]), "+f"(d[53]), "+f"(d[54]), "+f"(d[55]), "+f"(d[56]), "+f"(d[57]), "+f"(d[58]), "+f"(d[59]), "+f"(d[60]), "+f"(d[61]), "+f"(d[62]), "+f"(d[63])
    : "r"(a0), "r"(a1), "r"(a2), "r"(a3), "l"(db), "r"(scale_d), "n"(OB));
}
template <int V> using IC = std::integral_constant<int, V>;
template <int I, int N, class F> __device__ __forceinline__ void static_for(F&& f) {
  if constexpr (I < N) { f(std::integral_constant<int, I>{}); static_for<I + 1, N>(f); }
}

constexpr uint32_t SM_Q = 0, SM_BAR = 7 * 32768;
constexpr uint32_t B_FULL = SM_BAR, B_EMPTY = B_FULL + 24, B_WF = B_EMPTY + 24, B_QFULL = B_WF + 32, B_QEMPTY = B_QFULL + 16,
                   B_EVH = B_QEMPTY + 16, B_EVQ = B_EVH + 8, B_EVP0 = B_EVQ + 8, B_BG = B_EVP0 + 16, B_M0 = B_BG + 8, B_HALF = B_M0 + 8,
                   B_HRD = B_HALF + 8, SM_UNSAFE = B_HRD + 8, SM_TS = SM_UNSAFE + 8, SM_ML = (SM_TS + 192 + 15) / 16 * 16, SM_EPOCH = SM_ML + 1024, SM_GE = SM_EPOCH + 4, SM_END = SM_EPOCH + 16;
constexpr uint32_t POS_M = 0x5462;
constexpr int SMEM_BYTES = SM_END;

#define ROW0(u) make_uint4(pack_bf16(o[16 * u], o[16 * u + 1]), pack_bf16(o[16 * u + 4], o[16 * u + 5]), \
                           pack_bf16(o[16 * u + 8], o[16 * u + 9]), pack_bf16(o[16 * u + 12], o[16 * u + 13]))
#define ROW1(u) make_uint4(pack_bf16(o[16 * u + 2], o[16 * u + 3]), pack_bf16(o[16 * u + 6], o[16 * u + 7]), \
                           pack_bf16(o[16 * u + 10], o[16 * u + 11]), pack_bf16(o[16 * u + 14], o[16 * u + 15]))

__global__ void __launch_bounds__(384, 1) gps_kernel(const __grid_constant__ Params P) {
  extern __shared__ __align__(1024) uint8_t smem_raw[];
  constexpr uint32_t sb = 1024;
  if (smem_u32(smem_raw) != sb) return;
  const int cta = blockIdx.x;
  const int wg = __shfl_sync(0xffffffffu, (int)threadIdx.x >> 7, 0);
  const int warp = __shfl_sync(0xffffffffu, ((int)threadIdx.x >> 5) & 3, 0);
  const int lane = threadIdx.x & 31;
#define ROLE                                                                                       \
  const Work& W = P.w[cta_id()];                                                                   \
  [[maybe_unused]] const int n0 = W.nb0 + W.na0, n1 = W.nb1 + W.na1, total = n0 + n1;              \
  [[maybe_unused]] const bool fin = W.role & R_FIN, tail = W.role & R_TAIL;                        \
  [[maybe_unused]] const uint32_t posw = total == 0 || tail ? POS_M : ((total & 1) ? 0x2546 : 0x4326)
  const int g = lane >> 2, t = lane & 3;
  if (wg < 2) {
    const int tid = threadIdx.x & 127;
    ROLE;
    const uint32_t sQ = sb + SM_Q + wg * 32768;
#define st0 tid_is(wg * 128)
    STAMP(st0, wg, 0);
    const int rr = lane >> 3, j = lane & 7;
    const uint4* px[4];
#pragma unroll
    for (int i = 0; i < 4; i++) px[i] = (const uint4*)(P.x + (size_t)min(W.q0 * 128 + wg * 64 + warp * 16 + i * 4 + rr, NN - 1) * 256) + j;
    asm volatile("" : "+l"(px[0]), "+l"(px[1]), "+l"(px[2]), "+l"(px[3]));
    if (cta * 8 + wg * 4 + warp == 131 * 8) {
      const uint4 xs = __ldg((const uint4*)P.x + lane * 312 * 32);
      const uint32_t ep = ld_relaxed(g_flag + F_EPOCH);
      const float d0 = bf_lo(xs.x) - bf_hi(xs.x), d1 = bf_lo(xs.y) - bf_hi(xs.y), d2 = bf_lo(xs.z) - bf_hi(xs.z), d3 = bf_lo(xs.w) - bf_hi(xs.w);
      const int ge = __reduce_max_sync(0xffffffffu, __float_as_uint((d0 * d0 + d1 * d1 + d2 * d2 + d3 * d3) * (0.125f / 1e-5f)) >> 24);
      if (lane == 0) asm volatile("st.relaxed.gpu.global.u32 [%0], %1;" :: "l"(g_flag + F_GE), "r"((ep + 1) * 16 + min(max(63 - ge, 0), 12)) : "memory");
    }
    __syncwarp();
    auto x_load = [&](int c) {
      if (c < 4) {
#pragma unroll
        for (int i = 0; i < 4; i++)
          cp_async16(sQ + warp * 8192 + (i >> 1) * 4096 + c * 1024 + ((i & 1) * 4 + rr) * 128 + ((j ^ ((i & 1) * 4 + rr)) << 4), px[i] + c * 8);
      }
      cp_commit();
    };
    auto start = [&]() {
      bar_sync(4, 384);
      if (wg == 1) bar_arrive(5, 256);
    };

    const uint32_t sF = sQ + warp * 8192 + ((lane >> 3) & 1) * 4096 + (lane & 7) * 128;
    auto frag = [&](int k) { return sF + (k >> 2) * 1024 + ((((k & 3) * 2 + (lane >> 4)) ^ (lane & 7)) << 4); };
    uint32_t hq[64];
    const bool own = (W.own >> wg) & 1;
    auto layernorm = [&]() __attribute__((always_inline)) {
#pragma unroll
      for (int c = 0; c < XD; c++) x_load(c);
      start();
      float c1[4] = {0.f, 0.f, 0.f, 0.f}, ca[4] = {0.f, 0.f, 0.f, 0.f}, cb[4] = {0.f, 0.f, 0.f, 0.f};
#pragma unroll
      for (int k = 0; k < 16; k++) {
        if ((k & 3) == 0) {
          asm volatile("cp.async.wait_group %0;" :: "n"(XD - 1) : "memory");
          __syncwarp();
          x_load(k / 4 + XD);
        }
        ldsm4(frag(k), hq[4 * k], hq[4 * k + 1], hq[4 * k + 2], hq[4 * k + 3]);
        mma16816(c1, hq[4 * k], hq[4 * k + 1], hq[4 * k + 2], hq[4 * k + 3], 0x3f803f80u, 0x3f803f80u);
        mma16816(ca, hq[4 * k], hq[4 * k + 1], hq[4 * k + 2], hq[4 * k + 3], hq[4 * k], hq[4 * k + 2]);
        mma16816(cb, hq[4 * k], hq[4 * k + 1], hq[4 * k + 2], hq[4 * k + 3], hq[4 * k + 1], hq[4 * k + 3]);
      }
      const float mu0 = c1[0] * (1.0f / 256.0f), mu1 = c1[2] * (1.0f / 256.0f);
      const float v0 = fmaf(__shfl_sync(0xffffffffu, g & 1 ? ca[1] : ca[0], g * 4 + (g >> 1)), 1.0f / 256.0f, 1e-5f - mu0 * mu0);
      const float v1 = fmaf(__shfl_sync(0xffffffffu, g & 1 ? cb[3] : cb[2], g * 4 + (g >> 1)), 1.0f / 256.0f, 1e-5f - mu1 * mu1);
      float rs0, rs1;
      asm("rsqrt.approx.ftz.f32 %0, %1;" : "=f"(rs0) : "f"(v0)); asm("rsqrt.approx.ftz.f32 %0, %1;" : "=f"(rs1) : "f"(v1));
      if (W.q0 * 128 + wg * 64 + warp * 16 >= NN) rs0 = rs1 = 0.f;
      float nb0 = -mu0 * rs0, nb1 = -mu1 * rs1;
      const uint32_t sS = sb + SM_ML + (wg * 64 + warp * 16) * 8;
      if (t == 0) {
        asm volatile("st.shared.v2.f32 [%0], {%1,%2};" :: "r"(sS + g * 8), "f"(rs0), "f"(nb0) : "memory");
        asm volatile("st.shared.v2.f32 [%0], {%1,%2};" :: "r"(sS + g * 8 + 64), "f"(rs1), "f"(nb1) : "memory");
      }
      if (__any_sync(0xffffffffu, !(4.f * mu0 * mu0 <= v0) || !(4.f * mu1 * mu1 <= v1))) {
#pragma unroll 1
        for (int r = 0; r < 16; r++) {
          const uint32_t ad = sQ + warp * 8192 + (r >> 3) * 4096 + rr * 1024 + (r & 7) * 128 + ((j ^ (r & 7)) << 4);
          const uint4 v = lds128(ad);
          float f[8] = {bf_lo(v.x), bf_hi(v.x), bf_lo(v.y), bf_hi(v.y), bf_lo(v.z), bf_hi(v.z), bf_lo(v.w), bf_hi(v.w)};
          float sum = 0.f, ss = 0.f, rs;
#pragma unroll
          for (int i = 0; i < 8; i++) sum += f[i];
#pragma unroll 1
          for (int k = 1; k < 32; k *= 2) sum += __shfl_xor_sync(0xffffffffu, sum, k);
          sum *= 1.0f / 256.0f;
#pragma unroll
          for (int i = 0; i < 8; i++) { f[i] -= sum; ss += f[i] * f[i]; }
#pragma unroll 1
          for (int k = 1; k < 32; k *= 2) ss += __shfl_xor_sync(0xffffffffu, ss, k);
          asm("rsqrt.approx.ftz.f32 %0, %1;" : "=f"(rs) : "f"(fmaf(ss, 1.0f / 256.0f, 1e-5f)));
          if (W.q0 * 128 + wg * 64 + warp * 16 >= NN) rs = 0.f;
          sts128(ad, make_uint4(pack_bf16(f[0] * rs, f[1] * rs), pack_bf16(f[2] * rs, f[3] * rs), pack_bf16(f[4] * rs, f[5] * rs), pack_bf16(f[6] * rs, f[7] * rs)));
          if (lane == 0) asm volatile("st.shared.v2.f32 [%0], {%1,%2};" :: "r"(sS + r * 8), "f"(rs), "f"(-sum * rs) : "memory");
        }
        __syncwarp();
#pragma unroll
        for (int k = 0; k < 16; k++) ldsm4(frag(k), hq[4 * k], hq[4 * k + 1], hq[4 * k + 2], hq[4 * k + 3]);
        rs0 = rs1 = 1.f; nb0 = nb1 = 0.f;
      }
      asm volatile("setmaxnreg.inc.sync.aligned.u32 %0;" :: "n"(CREG));
      const uint32_t ah0 = pack_bf16(rs0, rs0), ah1 = pack_bf16(rs1, rs1), n0_ = pack_bf16(nb0, nb0), n1_ = pack_bf16(nb1, nb1);
      const uint32_t al0 = pack_bf16(rs0 - bf_lo(ah0), rs0 - bf_lo(ah0)), al1 = pack_bf16(rs1 - bf_lo(ah1), rs1 - bf_lo(ah1));
#pragma unroll
      for (int i = 0; i < 32; i++) {
        hq[2 * i] = hfma2(hq[2 * i], ah0, hfma2(hq[2 * i], al0, n0_));
        hq[2 * i + 1] = hfma2(hq[2 * i + 1], ah1, hfma2(hq[2 * i + 1], al1, n1_));
      }
      bar_sync(8 + wg, 160);
      if (own) {
        const float ks = __uint_as_float(__float_as_uint(KS) + lds32(sb + SM_GE));
        const uint32_t ks2 = pack_bf16(ks, ks);
        const float e0 = fmaf(bf_hi(__shfl_sync(0xffffffffu, hq[62], lane | 3)), -0.5f * ks, KC), e1 = fmaf(bf_hi(__shfl_sync(0xffffffffu, hq[63], lane | 3)), -0.5f * ks, KC);
#pragma unroll
        for (int k = 0; k < 16; k++)
          stsm4(frag(k), hfma2(hq[4 * k], ks2, KC2), hfma2(hq[4 * k + 1], ks2, KC2),
                k < 15 ? hfma2(hq[4 * k + 2], ks2, KC2) : pack_bf16(fmaf(bf_lo(hq[62]), ks, e0), t == 3 ? KC : fmaf(bf_hi(hq[62]), ks, e0)),
                k < 15 ? hfma2(hq[4 * k + 3], ks2, KC2) : pack_bf16(fmaf(bf_lo(hq[63]), ks, e1), t == 3 ? KC : fmaf(bf_hi(hq[63]), ks, e1)));
      }
      __syncwarp();
      if (lane == 0) mbar_arrive(sb + B_EVH);
      STAMP(st0, wg, 1);
    };

    float o[128];
    int qph = 0, st = tail ? wg : 0, ph = 0;
    auto release = [&](int stg) { if (lane == 0) mbar_arrive(sb + B_EMPTY + 8 * stg); };
    int resume = total > 0 ? -1 : 0;
    auto fill = [&]() __attribute__((always_inline)) {
#pragma unroll
      for (int i = 0; i < 32; i++)
        asm volatile("ld.volatile.shared.v4.f32 {%0,%1,%2,%3}, [%4];" : "=f"(o[4 * i]), "=f"(o[4 * i + 1]), "=f"(o[4 * i + 2]), "=f"(o[4 * i + 3]) : "r"(sb) : "memory");
    };
    auto finish = [&]() __attribute__((always_inline)) {
      STAMP(st0, wg, 11);
      DUMP(st0, wg, 0, 16);
      if (!P.zero) { asm volatile("exit;"); __builtin_unreachable(); }
      fill();
    };
    auto run = [&](auto hot_) __attribute__((always_inline)) {
    constexpr bool HOT = hot_.value;
    const int nloc = P.w[cta_id()].nloc;
    if (!HOT && resume == 0) {
#pragma unroll 1
      for (int i = 0; i < 32; i++) {
        const int r = i * 8 + wg * 4 + warp;
        cp_async16(sb + ((POS_M >> (r >> 6) * 4) & 15) * 32768 + sw_byte(r & 63, lane * 8), (const uint4*)P.wout + r * 32 + lane);
      }
    }
    bool wide = false;
    if (HOT) {
      reg_fence(hq);
      auto qstep = [&](auto k_) {
        constexpr int k = k_.value;
        if (k < 2 || k % 4 == 0) { mbar_wait(k == 0 ? sb + B_M0 : sb + B_WF + 2 * (k & ~3), 0); if (k == 0 || k == 4) bar_sync(5 + wg, 256); wg_fence(); }
        if constexpr (k == 0) wgmma_rs_n256_tb_first<0>(o, hq[0], hq[1], hq[2], hq[3], desc_m(sb, (POS_M & 15) * 2048));
        else wgmma_rs_n256_tb<(k & 3) * 512>(o, hq[4 * k], hq[4 * k + 1], hq[4 * k + 2], hq[4 * k + 3], desc_m(sb, ((POS_M >> (k & ~3)) & 15) * 2048), 1);
      };
      static_for<0, 4>(qstep);
      wg_commit();
      bar_arrive(6 - wg, 256);
      wg_wait<0>();
      if (!tail) release(0);
      static_for<4, 16>(qstep);
      wg_commit();
      bar_arrive(6 - wg, 256);
      wg_wait<0>();
      reg_fence(o); reg_fence(hq);
      if (!tail) release(1);
      STAMP(st0, wg, 2);
      float c0 = (o[124] + (t == 3 ? 2.f : 1.f) * o[125]) * (-0.5f / 4.5f), c1 = (o[126] + (t == 3 ? 2.f : 1.f) * o[127]) * (-0.5f / 4.5f);
      c0 += __shfl_xor_sync(0xffffffffu, c0, 1); c1 += __shfl_xor_sync(0xffffffffu, c1, 1);
      c0 += __shfl_xor_sync(0xffffffffu, c0, 2); c1 += __shfl_xor_sync(0xffffffffu, c1, 2);
      float r0 = t == 3 ? 0.f : o[125], r1 = t == 3 ? 0.f : o[127], r2 = o[124], r3 = o[126];
#pragma unroll
      for (int i = 0; i < 31; i++) { r2 += o[4 * i]; r0 += o[4 * i + 1]; r3 += o[4 * i + 2]; r1 += o[4 * i + 3]; }
      r0 += r2; r1 += r3;
      r0 += __shfl_xor_sync(0xffffffffu, r0, 1); r1 += __shfl_xor_sync(0xffffffffu, r1, 1);
      r0 += __shfl_xor_sync(0xffffffffu, r0, 2); r1 += __shfl_xor_sync(0xffffffffu, r1, 2);
      wide = !(fabsf(c0) <= SAFE_C / KS) || !(fabsf(c1) <= SAFE_C / KS);
      const float ig = __uint_as_float(0x3f800000u - lds32(sb + SM_GE));
      c0 *= ig; c1 *= ig;
      r0 = fmaf(c0, -255.f, fmaf(r0, -ig, PSH / KC)); r1 = fmaf(c1, -255.f, fmaf(r1, -ig, PSH / KC));
      if (own) mbar_wait(sb + B_HRD, 0);
#pragma unroll
      for (int k = 0; k < 16; k++)
        stsm4(frag(k),
              pack_bf16(fmaf(o[8 * k], ig, c0), fmaf(o[8 * k + 1], ig, c0)), pack_bf16(fmaf(o[8 * k + 2], ig, c1), fmaf(o[8 * k + 3], ig, c1)),
              pack_bf16(fmaf(o[8 * k + 4], ig, c0), k == 15 && t == 3 ? r0 : fmaf(o[8 * k + 5], ig, c0)),
              pack_bf16(fmaf(o[8 * k + 6], ig, c1), k == 15 && t == 3 ? r1 : fmaf(o[8 * k + 7], ig, c1)));
      fence_async_smem();
      __syncwarp();
      STAMP(st0, wg, 3);
      if (tail) { bar_sync(7, 256); if (wg == 0) { release(0); release(1); release(2); } }
      }

    if (HOT || (resume && resume < 4)) {
      ROLE;
      float m0, m1;
      const int qh = tail ? 0 : wg, tl = tail;
      uint32_t qo = qh * 2048;
      const uint32_t ko = (2 - tl) * 2048, stop = 1 + tl + (uint32_t)P.zero;
      float l0, l1;
      auto row_sums = [&]() { l0 = __shfl_sync(0xffffffffu, o[125] + 0.f, lane | 3); l1 = __shfl_sync(0xffffffffu, o[127] + 0.f, lane | 3); };
#define PART(u) make_uint4(pack_bf16(o[8 * u] - l0, o[8 * u + 1] - l0), pack_bf16(o[8 * u + 2] - l1, o[8 * u + 3] - l1), \
                           pack_bf16(o[8 * u + 4] - l0, o[8 * u + 5] - l0), pack_bf16(o[8 * u + 6] - l1, o[8 * u + 7] - l1))
      bool unsafe = !HOT;
      m0 = m1 = 0.f;
#pragma unroll 1
      for (int seg = HOT ? 0 : resume - 1; seg < 2; seg++) {
        ROLE;
        const bool last = __any_sync(0xffffffffu, seg || n1 == 0);
        m0 = m1 = !HOT && unsafe ? -INFINITY : 0.f;
        int first = 1;
        auto tile = [&](auto n_, bool endseg) __attribute__((always_inline)) -> bool {
          constexpr int N = n_.value;
          float s[N / 2]; uint32_t p[N / 4];
          if (!mbar_try_wait(sb + B_FULL + 8 * st, ph)) mbar_wait(sb + B_FULL + 8 * st, ph);
          const bool again = !HOT && N == 112 && first && !seg;
          if (HOT || N == 128) bar_sync(5 + wg, 256);
          else asm volatile("{\n.reg .pred p;\nsetp.eq.u32 p, %1, 0;\n@p bar.sync %0, 256;\n}\n" :: "r"(5 + wg), "r"((uint32_t)again) : "memory");
          wg_fence();
          const uint64_t dQ = desc_k(sb + SM_Q, qo), dK = desc_k(sb, ko + st * 4096);
          qo += (uint32_t)P.zero;
          static_for<0, 16>([&](auto k) { constexpr int kk = (k.value + KROT) & 15, off = (kk >> 2) * 64 + (kk & 3) * 2; wgmma_qk<off, off>(s, dQ, dK, k.value > 0); });
          wg_commit();
          if (HOT || N == 128) bar_arrive(6 - wg, 256);
          else asm volatile("{\n.reg .pred p;\nsetp.eq.u32 p, %1, 0;\n@p bar.arrive %0, 256;\n}\n" :: "r"(6 - wg), "r"((uint32_t)again) : "memory");
          if (HOT && N == 112 && first && !seg) {
            float a0 = 0.f, a1 = 0.f, a2 = 0.f, a3 = 0.f;
#pragma unroll
            for (int i = 0; i < 32; i++) { a0 += o[4 * i] * o[4 * i]; a2 += o[4 * i + 1] * o[4 * i + 1]; a1 += o[4 * i + 2] * o[4 * i + 2]; a3 += o[4 * i + 3] * o[4 * i + 3]; }
            a0 += a2; a1 += a3;
            a0 += __shfl_xor_sync(0xffffffffu, a0, 1); a1 += __shfl_xor_sync(0xffffffffu, a1, 1);
            a0 += __shfl_xor_sync(0xffffffffu, a0, 2); a1 += __shfl_xor_sync(0xffffffffu, a1, 2);
            unsafe = __any_sync(0xffffffffu, bar_red_or(tail ? 7 : 1 + wg, tail ? 256 : 128, wide || !(a0 <= SAFE_N2 / (KS * KS)) || !(a1 <= SAFE_N2 / (KS * KS))));
            if (lane == 0) { asm volatile("st.shared.u8 [%0], %1;" :: "r"(sb + SM_UNSAFE + wg), "r"((uint32_t)unsafe) : "memory"); mbar_arrive(sb + B_EVQ); }
          }
          STAMP(N == 112 && first && !seg && st0, wg, 0);
          wg_wait<0>();
          reg_fence(s);
          if (HOT && N == 112 && unsafe) return true;
          if (endseg) { if (lane == 0) mbar_arrive(sb + B_QEMPTY + 8 * wg); }
          if (!HOT && unsafe) {
            float a0 = fmaxf(s[0], s[1]), a1 = fmaxf(s[2], s[3]);
#pragma unroll
            for (int i = 1; i < N / 8; i++) { a0 = fmaxf(a0, fmaxf(s[4 * i], s[4 * i + 1])); a1 = fmaxf(a1, fmaxf(s[4 * i + 2], s[4 * i + 3])); }
            if (__any_sync(0xffffffffu, (a0 > m0 + TAU) || (a1 > m1 + TAU))) {
              a0 = fmaxf(a0, __shfl_xor_sync(0xffffffffu, a0, 1)); a1 = fmaxf(a1, __shfl_xor_sync(0xffffffffu, a1, 1));
              a0 = fmaxf(a0, __shfl_xor_sync(0xffffffffu, a0, 2)); a1 = fmaxf(a1, __shfl_xor_sync(0xffffffffu, a1, 2));
              const float x0 = ceilf(fmaxf(m0, a0)), x1 = ceilf(fmaxf(m1, a1)), sc0 = ex2(m0 - x0), sc1 = ex2(m1 - x1);
              m0 = x0; m1 = x1;
#pragma unroll
              for (int i = 0; i < 32; i++) { o[4 * i] *= sc0; o[4 * i + 1] *= sc0; o[4 * i + 2] *= sc1; o[4 * i + 3] *= sc1; }
            }
#pragma unroll
            for (int i = 0; i < N / 8; i++) { s[4 * i] -= m0; s[4 * i + 1] -= m0; s[4 * i + 2] -= m1; s[4 * i + 3] -= m1; }
          }
          auto pv = [&](auto k) { wgmma_rs_n256_tb<k.value * 512 + (63 << 16)>(o, p[4 * k.value], p[4 * k.value + 1], p[4 * k.value + 2], p[4 * k.value + 3], dK, k.value > 0 || N == 128 ? 1 : !first); };
#pragma unroll
          for (int i = 0; i < 16; i++) { p[i] = pack_bf16(ex2(s[2 * i]), ex2(s[2 * i + 1])); asm volatile("" : "+r"(p[i]) :: "memory"); }
          reg_fence(o);
          do bar_sync(5 + wg, 256); while (P.zero);
          wg_fence();
          static_for<0, 4>(pv);
          wg_commit();
#pragma unroll
          for (int i = 16; i < N / 4; i++) { p[i] = pack_bf16(ex2(s[2 * i]), ex2(s[2 * i + 1])); asm volatile("" : "+r"(p[i]) :: "memory"); }
          wg_fence();
          static_for<4, N / 16>(pv);
          wg_commit();
          bar_arrive(6 - wg, 256);
          if (N == 128) { wg_wait<1>(); if (endseg && last) { if (lane == 0) mbar_arrive(sb + B_HALF); } }
          wg_wait<0>();
          reg_fence(o); reg_fence(p);
          release(st);
          if (st) { st--; ph ^= 1; } else st = stop;
          return false;
        };
#pragma unroll 1
        for (int left = tail ? 8 - wg : (seg ? W.nb1 : W.nb0); left > 0; left--) { if (tile(IC<112>{}, false)) { resume = 1; return; } STAMP(first && !seg && st0, wg, 4); first = 0; }
#pragma unroll 1
        for (int left = tail ? 32 + wg : (seg ? W.na1 : W.na0); left > 0; left--) tile(IC<128>{}, left == 1);
        STAMP(st0 && last, wg, 6);
        {
        ROLE;
        if (last && fin && !(tail && wg == 1)) break;
        row_sums();
        if (last) mbar_wait(sb + (tail ? B_QEMPTY : B_HALF), 0);
        const uint32_t sp = sb + (tail ? 0 : (last ? (posw >> 12) + wg : (wg ? 4 - 2 * st : 6))) * 32768, sm = sb + SM_ML + (tail ? 0 : wg) * 512;
#pragma unroll
        for (int u = 0; u < 16; u++) sts128(sp + (u * 128 + tid) * 16, PART(u));
        if (t == 0) {
          asm volatile("st.shared.v2.f32 [%0], {%1,%2};" :: "r"(sm + (warp * 16 + g) * 8), "f"(m0), "f"(l0) : "memory");
          asm volatile("st.shared.v2.f32 [%0], {%1,%2};" :: "r"(sm + (warp * 16 + g) * 8 + 64), "f"(m1), "f"(l1) : "memory");
        }
        __syncwarp();
        if (lane == 0) mbar_arrive(sb + B_EVP0 + 8 * wg);
        STAMP(st0 && last, wg, 7);
        if (last) break;
        mbar_wait(sb + B_QFULL + 8 * wg, qph); qph ^= 1;
        uint32_t u; asm volatile("ld.shared.u8 %0, [%1];" : "=r"(u) : "r"(sb + SM_UNSAFE + wg) : "memory");
        unsafe = __any_sync(0xffffffffu, u != 0);
        if (HOT && unsafe) { resume = 2; return; }
        }
      }

      if (P.w[cta_id()].role & R_FIN) {
        ROLE;
        if (!(tail && wg == 1)) {
        row_sums();
        const int rl = wg * 64 + warp * 16 + g;
        uint32_t a[64];
#pragma unroll
        for (int i = 0; i < 64; i++) a[i] = pack_bf16(o[2 * i] - (i & 1 ? l1 : l0), o[2 * i + 1] - (i & 1 ? l1 : l0));
        reg_fence(a);
        {
          float2 e0, e1;
          mbar_wait(sb + B_QFULL + 8 * wg, qph);
          asm volatile("ld.shared.v2.f32 {%0,%1}, [%2];" : "=f"(e0.x), "=f"(e0.y) : "r"(sb + SM_ML + rl * 8) : "memory");
          asm volatile("ld.shared.v2.f32 {%0,%1}, [%2];" : "=f"(e1.x), "=f"(e1.y) : "r"(sb + SM_ML + rl * 8 + 64) : "memory");
          STAMP(st0, wg, 7);
          uint32_t fb0 = 0x3f803f80u, fb1 = 0x3f803f80u;
          const float s0 = l0 + e0.y, s1 = l1 + e1.y;
          const bool odd = __any_sync(0xffffffffu, m0 != e0.x || m1 != e1.x || !(fmaxf(s0, s1) < 0x1p40f) || !(fminf(s0, s1) > 0x1p-40f));
          if (HOT && odd) { resume = 3; return; }
          uint4 v[16];
#pragma unroll
          for (int u = 0; u < 16; u++) v[u] = lds128(sQ + (u * 128 + tid) * 16);
          if (!HOT && odd) {
            const float x0 = fmaxf(m0, e0.x), x1 = fmaxf(m1, e1.x);
            const float d0 = fmaxf(m0 - x0, -1000.f), d1 = fmaxf(m1 - x1, -1000.f), f0 = fmaxf(e0.x - x0, -1000.f), f1 = fmaxf(e1.x - x1, -1000.f);
            l0 = l0 * ex2(d0) + e0.y * ex2(f0); l1 = l1 * ex2(d1) + e1.y * ex2(f1);
            const int E0 = fexp(l0), E1 = fexp(l1);
            const uint32_t fa0 = pow2_bf2((int)d0 - E0), fa1 = pow2_bf2((int)d1 - E1);
            fb0 = pow2_bf2((int)f0 - E0); fb1 = pow2_bf2((int)f1 - E1);
            l0 = __uint_as_float(__float_as_uint(l0) - (E0 << 23)); l1 = __uint_as_float(__float_as_uint(l1) - (E1 << 23));
#pragma unroll
            for (int i = 0; i < 32; i++) { a[2 * i] = hmul2(a[2 * i], fa0); a[2 * i + 1] = hmul2(a[2 * i + 1], fa1); }
          } else { l0 = s0; l1 = s1; }
#pragma unroll
          for (int u = 0; u < 16; u++) {
            a[4 * u] = hfma2(v[u].x, fb0, a[4 * u]); a[4 * u + 1] = hfma2(v[u].y, fb1, a[4 * u + 1]);
            a[4 * u + 2] = hfma2(v[u].z, fb0, a[4 * u + 2]); a[4 * u + 3] = hfma2(v[u].w, fb1, a[4 * u + 3]);
          }
        }
        float fs0, fs1;
        const float kl = __uint_as_float(__float_as_uint(KS / KC) + lds32(sb + SM_GE));
        asm("rcp.approx.ftz.f32 %0, %1;" : "=f"(fs0) : "f"(l0 * kl)); asm("rcp.approx.ftz.f32 %0, %1;" : "=f"(fs1) : "f"(l1 * kl));
        STAMP(st0, wg, 8);
        reg_fence(a);
        bar_sync(5 + wg, 256);
        uint64_t dW[4];
        float y0[64], y1[64];
        auto half0 = [&](auto u_) {
          constexpr int u = u_.value;
          if (u % 4 == 0) { mbar_wait(sb + B_WF + 2 * u, 1); wg_fence(); dW[u / 4] = desc_mn(sb, ((posw >> u) & 15) * 2048); }
          wgmma_rs_n128_tb<(u & 3) * 512>(y0, a[4 * u], a[4 * u + 1], a[4 * u + 2], a[4 * u + 3], dW[u / 4], u != 0);
        };
        auto half1 = [&](auto u_) {
          constexpr int u = u_.value;
          wgmma_rs_n128_tb<(u & 3) * 512 + 128>(y1, a[4 * u], a[4 * u + 1], a[4 * u + 2], a[4 * u + 3], dW[u / 4], u != 0);
        };
        const bool wr = W.q0 * 128 + wg * 64 + warp * 16 < NN;
        uint4* po = (uint4*)(P.out + (size_t)(W.q0 * 128 + rl) * 256) + t;
        auto emit = [&](const float* y, uint4* dst) {
          if (wr) {
            red_bf16x8(dst, make_uint4(pack_bf16(y[0] * fs0, y[1] * fs0), pack_bf16(y[4] * fs0, y[5] * fs0), pack_bf16(y[8] * fs0, y[9] * fs0), pack_bf16(y[12] * fs0, y[13] * fs0)));
            red_bf16x8(dst + 8 * 32, make_uint4(pack_bf16(y[2] * fs1, y[3] * fs1), pack_bf16(y[6] * fs1, y[7] * fs1), pack_bf16(y[10] * fs1, y[11] * fs1), pack_bf16(y[14] * fs1, y[15] * fs1)));
          }
          wg_fence();
        };
        static_for<0, 16>(half0);
        wg_commit();
        static_for<0, 4>(half1);
        wg_commit();
        wg_wait<1>();
        reg_fence(y0);
        emit(y0, po); static_for<4, 8>(half1);
        emit(y0 + 16, po + 4); static_for<8, 12>(half1);
        emit(y0 + 32, po + 8); static_for<12, 16>(half1);
        wg_commit();
        bar_arrive(6 - wg, 256);
        emit(y0 + 48, po + 12);
        wg_wait<0>();
        reg_fence(a); reg_fence(y1);
        STAMP(st0, wg, 9);
#pragma unroll
        for (int u = 0; u < 4; u++) emit(y1 + 16 * u, po + 16 + 4 * u);
        }
        if (!tail) { STAMP(st0, wg, 11); DUMP(st0, wg, 0, 16); asm volatile("exit;"); __builtin_unreachable(); }
        if (wg == 1) { bar_sync(6, 256); bar_arrive(5, 256); } else qph ^= 1;
        __syncwarp();
        if (lane == 0) mbar_arrive(sb + B_QEMPTY + 8 * wg);
        fill();
        resume = 4;
      }
        }
#pragma unroll 1
    for (int step = HOT || resume ? 0 : -4; step < (HOT && resume == 4 ? 0 : nloc); step++) {
      ROLE;
      const bool helper = HOT || (resume && resume < 4);
      const bool isw = !HOT && step < 0;
      if (isw) {
        const uint4* src = (const uint4*)(step < -2 ? P.wmsg : P.wv) + ((step & 1) * 128 + wg * 64 + warp) * 32 + lane;
        float cw[8] = {0.f, 0.f, 0.f, 0.f, 0.f, 0.f, 0.f, 0.f};
#pragma unroll 1
        for (int i = 0; i < 16; i++) cp_async16(sQ + sw_byte(i * 4 + warp, lane * 8), src + i * 128);
        cp_commit();
#pragma unroll
        for (int i = 0; i < 8; i++) {
          const uint4 v = __ldg((const uint4*)(step < -2 ? P.wmsg : P.wv) + (248 + i) * 32 + lane);
          const float k = step < -2 ? 0.f : (i == 7 ? -1.0f / 4.5f : -0.5f / 4.5f);
          cw[0] += bf_lo(v.x) * k; cw[1] += bf_hi(v.x) * k; cw[2] += bf_lo(v.y) * k; cw[3] += bf_hi(v.y) * k;
          cw[4] += bf_lo(v.z) * k; cw[5] += bf_hi(v.z) * k; cw[6] += bf_lo(v.w) * k; cw[7] += bf_hi(v.w) * k;
        }
        asm volatile("cp.async.wait_group 0;" ::: "memory");
#pragma unroll 1
        for (int i = 0; i < 16; i++) {
          const uint32_t ad = sQ + sw_byte(i * 4 + warp, lane * 8);
          const uint4 v = lds128(ad);
          uint4 w4 = make_uint4(pack_bf16(bf_lo(v.x) + cw[0], bf_hi(v.x) + cw[1]), pack_bf16(bf_lo(v.y) + cw[2], bf_hi(v.y) + cw[3]),
                                pack_bf16(bf_lo(v.z) + cw[4], bf_hi(v.z) + cw[5]), pack_bf16(bf_lo(v.w) + cw[6], bf_hi(v.w) + cw[7]));
          if (step == -1 && wg * 64 + i * 4 + warp == 127) w4 = make_uint4(0, 0, 0, 0);
          sts128(ad, w4);
        }
        fence_async_smem();
        bar_sync(7, 256);
      } else {
        SSTAMP(0);
        mbar_wait(sb + B_QFULL + 8 * wg, qph); qph ^= 1;
        STAMP(st0 && step == 0, wg, 8);
        SSTAMP(1);
        bar_sync(5 + wg, 256);
        SSTAMP(2);
      }
#pragma unroll 1
      for (int c = 0; c < 4; c++) {
        if (step == 0) mbar_wait(sb + B_WF + 8 * c, helper);
        const int turn2 = helper ? 3 : 4;
        if (c == turn2) bar_sync(5 + wg, 256);
        wg_fence();
        const uint64_t dA = desc_k(sb + SM_Q, wg * 2048 + c * 64), dW = desc_mn(sb, ((posw >> c * 4) & 15) * 2048);
        static_for<0, 4>([&](auto k) { wgmma_ss_n256_tb<k.value * 2, k.value * 512>(o, dA, dW, k.value > 0 ? 1 : c); });
        wg_commit();
        if ((c == 3 || c == turn2 - 1) && !isw) bar_arrive(6 - wg, 256);
        wg_wait<1>();
      }
      wg_wait<0>();
      reg_fence(o);
      {
        STAMP(st0 && step == 0, wg, 9);
        SSTAMP(3);
        if (isw) bar_sync(1 + wg, 128); else if (lane == 0) mbar_arrive(sb + B_QEMPTY + 8 * wg);
        uint8_t* dw = (uint8_t*)(step < -2 ? g_Wmo : g_Wvo) + ((step & 1) * 2 + wg) * 32768 + warp * 8192 + g * 128;
        const int row0 = (W.loc0 + step) * 128 + wg * 64 + warp * 16;
        uint4 r[16];
#pragma unroll
        for (int u = 0; u < 8; u++) { r[2 * u] = ROW0(u); r[2 * u + 1] = ROW1(u); }
        if (isw) {
#pragma unroll
          for (int u = 0; u < 16; u++) *(uint4*)(dw + (u >> 2) * 1024 + ((((u & 2) * 2 + t) ^ g) << 4) + (u & 1) * 4096) = r[u];
        } else if (row0 < NN) {
          uint4* po = (uint4*)(P.out + (size_t)(row0 + g) * 256) + t;
          uint32_t c1 = clk();
#pragma unroll
          for (int u = 0; u < 16; u++) {
            red_bf16x8(po + (u >> 1) * 4 + (u & 1) * 256, r[u]);
            if (!HOT) { c1 += PACE; while ((int)(clk() - c1) < 0) {} }
          }
        }
        if (!HOT && step == -1) { bar_sync(7, 256); if (tid_is(0)) flag_release(F_W); __syncwarp(); STAMP(st0, wg, 3); }
      }
    }
    if (HOT && resume == 4) return;
    finish();
    };
    if (total == 0) {
      start();
      asm volatile("setmaxnreg.inc.sync.aligned.u32 %0;" :: "n"(CREG));
      fill();
    } else {
      layernorm();
      run(std::true_type{});
    }
    run(std::false_type{});
    asm volatile("setmaxnreg.dec.sync.aligned.u32 %0;" :: "n"(504 - 2 * CREG));
  } else {
    STAMP(lane == 0 && warp == 0, 2, 0);
        const int mi = cta >> 3;
    const uint32_t sW = sb + 3 * 32768;
    uint4 wa[4], wb[8];
    {
      const uint4* pq = (const uint4*)(P.wq + ((mi & 15) * 16 + g) * 256) + warp * 8 + t;
      const uint4* pk = (const uint4*)(P.wk + ((cta & 7) * 32 + g) * 256) + warp * 8 + t;
#pragma unroll
      for (int i = 0; i < 4; i++) wa[i] = __ldg(pq + (i >> 1) * 256 + (i & 1) * 4);
#pragma unroll
      for (int i = 0; i < 8; i++) wb[i] = __ldg(pk + (i >> 1) * 256 + (i & 1) * 4);
    }
    if (threadIdx.x == 352) {
      for (int i = 0; i < 3; i++) { mbar_init(sb + B_FULL + 8 * i, 1); mbar_init(sb + B_EMPTY + 8 * i, cta == 130 ? 4 : 8); }
      for (int i = 0; i < 4; i++) mbar_init(sb + B_WF + 8 * i, 1);
      for (int i = 0; i < 2; i++) { mbar_init(sb + B_QFULL + 8 * i, 1); mbar_init(sb + B_QEMPTY + 8 * i, 4); mbar_init(sb + B_EVP0 + 8 * i, 4); }
      mbar_init(sb + B_EVH, 8); mbar_init(sb + B_EVQ, 8); mbar_init(sb + B_HALF, 8); mbar_init(sb + B_BG, 1); mbar_init(sb + B_M0, 1); mbar_init(sb + B_HRD, 1);
      asm volatile("fence.mbarrier_init.release.cluster;" ::: "memory");
    }
    __syncwarp();
    do bar_sync(4, 384); while (P.zero);
    {
#pragma unroll
      for (int n = 0; n < 4; n++) {
        float c[4] = {0.f, 0.f, 0.f, 0.f};
#pragma unroll
        for (int u = 0; u < 2; u++) {
          mma16816(c, wa[u].x, wa[2 + u].x, wa[u].y, wa[2 + u].y, wb[2 * n + u].x, wb[2 * n + u].y);
          mma16816(c, wa[u].z, wa[2 + u].z, wa[u].w, wa[2 + u].w, wb[2 * n + u].z, wb[2 * n + u].w);
        }
        asm volatile("st.shared.v2.f32 [%0], {%1,%2};" :: "r"(sW + ((warp * 16 + g) * 40 + n * 8 + 2 * t) * 4), "f"(c[0]), "f"(c[1]) : "memory");
        asm volatile("st.shared.v2.f32 [%0], {%1,%2};" :: "r"(sW + ((warp * 16 + g + 8) * 40 + n * 8 + 2 * t) * 4), "f"(c[2]), "f"(c[3]) : "memory");
      }
      STAMP(lane == 0 && warp == 0, 2, 7);
      bar_sync(3, 128);
      if (warp < 2) {
        float c[8] = {0.f, 0.f, 0.f, 0.f, 0.f, 0.f, 0.f, 0.f};
#pragma unroll
        for (int k = 0; k < 4; k++) {
          const uint4 v = lds128(sW + ((k * 16 + warp * 8 + g) * 40 + t * 8) * 4), w = lds128(sW + ((k * 16 + warp * 8 + g) * 40 + t * 8 + 4) * 4);
          c[0] += __uint_as_float(v.x); c[1] += __uint_as_float(v.y); c[2] += __uint_as_float(v.z); c[3] += __uint_as_float(v.w);
          c[4] += __uint_as_float(w.x); c[5] += __uint_as_float(w.y); c[6] += __uint_as_float(w.z); c[7] += __uint_as_float(w.w);
        }
        const float ms = 1.4426950408889634f / 16.0f / KS;
        const uint4 m4 = make_uint4(pack_bf16(c[0] * ms, c[1] * ms), pack_bf16(c[2] * ms, c[3] * ms), pack_bf16(c[4] * ms, c[5] * ms), pack_bf16(c[6] * ms, c[7] * ms));
        sts128(sW + 16384 + (warp * 8 + g) * 64 + ((t ^ (g >> 1)) << 4), m4);
      }
    }
    asm volatile("setmaxnreg.dec.sync.aligned.u32 %0;" :: "n"(504 - 2 * CREG));
    STAMP(lane == 0 && warp == 0, 2, 13);
    bar_sync(3, 128);
#define ep1 (lds32(sb + SM_EPOCH) + 1)
    if (threadIdx.x == 256 && cta < 128) {
      fence_async_smem();
      bulk_s2g(g_M + cta * 64, sW + 16384, 1024);
      bulk_commit();
      bulk_wait_all();
      red_relaxed(g_flag + F_M + (cta >> 5));
    }
    if (warp == 2 && cta < 131) {
      uint2 f;
#pragma unroll 1
      for (uint32_t it = 0; it < (1u << 23); it++) {
        __nanosleep(150);
        asm volatile("ld.relaxed.gpu.global.v2.u32 {%0,%1}, [%2];" : "=r"(f.x), "=r"(f.y) : "l"(g_flag + F_EPOCH) : "memory");
        if (__all_sync(0xffffffffu, f.y >> 4 == ((f.x + 1) & 0xfffffff))) break;
      }
      asm volatile("st.shared.u32 [%0], %1;" :: "r"(sb + SM_GE), "r"((f.y & 15) << 23) : "memory");
      bar_arrive(8, 160); bar_arrive(9, 160);
    }
    __syncwarp();
    ROLE;
    if (warp == 3 && W.own) {
      mbar_wait_w(sb + B_EVH, 0);
      if (W.role < R_SIG) mbar_wait_w(sb + B_WF + 8, 0);
      if (lane == 0) {
        fence_async_smem();
        const int h0 = W.own == 2, nh = W.own == 3 ? 2 : 1;
        bulk_s2g(g_h + W.hp * 4096 + h0 * 2048, sb + SM_Q + h0 * 32768, nh * 32768);
        bulk_s2g(g_stat + W.q0 * 128 + h0 * 64, sb + SM_ML + h0 * 512, nh * 512);
        bulk_commit();
        bulk_wait_read();
        mbar_arrive(sb + B_HRD);
        bulk_wait_all();
        if (W.role >= R_SIG) red_relaxed(g_flag + F_H1 - 1 + W.role / R_SIG);
        red_relaxed(g_flag + F_H);
      }
      __syncwarp();
      STAMP(lane == 0, 2, 6);
    }
    if (warp == 0) {
      if (lane == 0) {
        STAMP(true, 2, 1);
        const uint32_t epoch = ld_relaxed(g_flag + F_EPOCH);
        if (total > 0) {
#pragma unroll
          for (int c = 0; c < 3; c++) mbar_expect_tx(sb + B_WF + 8 * c, c == 0 ? WCH_B - 8192 : WCH_B);
          mbar_expect_tx(sb + B_M0, 8192);
          int c = 0;
#pragma unroll 1
          for (uint32_t it = 0; c < 4; it++) {
            uint4 f;
            asm volatile("ld.relaxed.gpu.global.v4.u32 {%0,%1,%2,%3}, [%4];" : "=r"(f.x), "=r"(f.y), "=r"(f.z), "=r"(f.w) : "l"(g_flag + F_M) : "memory");
            uint32_t tm;
            asm volatile("mad.lo.u32 %0, %1, 32, 32;" : "=r"(tm) : "r"(epoch));
            int ok = (int)(f.x - tm) < 0 ? 0 : (int)(f.y - tm) < 0 ? 1 : (int)(f.z - tm) < 0 ? 2 : (int)(f.w - tm) < 0 ? 3 : 4;
            if (it > (1u << 23)) ok = 4;
            if (ok > c) {
              asm volatile("fence.acquire.gpu;" ::: "memory"); fence_async_gmem();
              if (c == 0) bulk_g2s(sb + (POS_M & 15) * 32768, g_M, 8192, sb + B_M0);
            }
#pragma unroll 1
            for (; c < ok; c++) {
              const uint32_t skip = c == 0 ? 8192 : 0;
              bulk_g2s(sb + ((POS_M >> c * 4) & 15) * 32768 + skip, pofs<const uint8_t>(g_M, c * WCH_B + skip), WCH_B - skip, sb + B_WF + 8 * c);
              STAMP(c == 0, 2, 2);
            }
          }
        }
        asm volatile("st.shared.u32 [%0], %1;" :: "r"(sb + SM_EPOCH), "r"(epoch) : "memory");
        if (total > 0) mbar_expect_tx(sb + B_WF + 24, WCH_B);
        int st = 0, ph = 0, qph = 0;
        const int nsl = tail ? 3 : 2;
        auto next_slot = [&]() { mbar_wait(sb + B_EMPTY + 8 * st, ph); if (++st == nsl) { st = 0; ph ^= 1; } };
        const uint4* wsrc = fin ? g_Wvo : g_Wmo;
        auto w_load = [&](int c0, int c1) {
#pragma unroll 1
          for (int c = c0; c < c1; c++) {
            mbar_expect_tx(sb + B_WF + 8 * c, WCH_B);
            bulk_g2s(sb + ((posw >> c * 4) & 15) * 32768, pofs<const uint8_t>(wsrc, c * WCH_B), WCH_B, sb + B_WF + 8 * c);
          }
        };
        auto q_load = [&](const uint4* src, bool wait_empty) {
#pragma unroll 1
          for (int h = 0; h < 2; h++) {
            if (wait_empty) mbar_wait(sb + B_QEMPTY + 8 * h, qph);
            mbar_expect_tx(sb + B_QFULL + 8 * h, 32768);
            bulk_g2s_last(sb + SM_Q + h * 32768, src + h * 2048, 32768, sb + B_QFULL + 8 * h);
          }
          if (wait_empty) qph ^= 1;
        };
        auto part_out = [&](int slot, int h, uint32_t region, int parity) {
          mbar_wait(sb + B_EVP0 + 8 * h, parity);
          fence_async_smem();
          bulk_s2g(g_part + slot * 4096 + h * 2048, sb + region * 32768, 32768);
          bulk_s2g(g_ml + slot * 128 + h * 64, sb + SM_ML + h * 512, 512);
          bulk_commit();
        };
        auto announce = [&](int f) {
          red_relaxed(g_flag + f);
        };
        if (total > 0) {
          STAMP(true, 2, 3);
          const int q1 = W.q0 + 2 * W.own - 3;
          if (!tail) { flag_wait(F_H1 + (fin ? 0 : W.own), (epoch + 1) * (fin ? NH1_0 : (W.own == 1 ? NH1_1 : NH1_2))); fence_async_gmem(); }
          STAMP(true, 2, 4);
          uint32_t ko = W.k0 * 8192;
#pragma unroll 1
          for (int j = 0; j < total; j++) {
            if (j == (tail ? 0 : 1)) { flag_wait(F_H, (epoch + 1) * NHSIG); fence_async_gmem(); }
            if (j == n0) {
              flag_wait(F_QP + q1 * LN_, (epoch + 1)); fence_async_gmem();
              const uint32_t u = __ldcg(g_unsafe + q1);
              asm volatile("st.shared.u32 [%0], %1;" :: "r"(sb + SM_UNSAFE), "r"(u) : "memory");
              ko = W.k1 * 8192;
            }
            if (j == n0 + 1) q_load(g_qp + q1 * 4096, true);
            if (j == total - 1) { flag_wait(F_W, (epoch + 1)); fence_async_gmem(); if (!tail) w_load(0, 1); }
            const uint32_t bytes = (j < n0 ? j < W.nb0 : j - n0 < W.nb1) ? 112 * 512 : 128 * 512, s0 = st;
            const uint32_t region = (tail ? 1 : 2) + 2 * s0, skip = j == n0 + 1 ? 32768 : 0;
            if (skip) part_out(W.slotA, 0, 6, 0);
            next_slot();
            mbar_expect_tx(sb + B_FULL + 8 * s0, bytes);
            bulk_g2s(sb + region * 32768 + skip, pofs<const uint8_t>(g_h, ko + skip), bytes - skip, sb + B_FULL + 8 * s0);
            if (skip) {
              part_out(W.slotA, 1, region, 0);
              bulk_wait_read();
              bulk_g2s(sb + region * 32768, pofs<const uint8_t>(g_h, ko), skip, sb + B_FULL + 8 * s0);
              bulk_wait_all();
              announce(F_PART + W.slotA * LN_);
            }
            ko += bytes;
          }
          next_slot();
          if (tail) { next_slot(); next_slot(); }
        } else { flag_wait(F_W, (epoch + 1)); fence_async_gmem(); }
        STAMP(true, 2, 5);
        const bool staged = total > 0 && !tail;
        w_load(staged, staged ? (fin ? 2 : 3) : 4);
        if (tail) {
          mbar_wait(sb + B_BG, 0); mbar_wait(sb + B_EVP0 + 8, 0); mbar_arrive(sb + B_QFULL);
          qph = 1; wsrc = g_Wmo;
          mbar_wait(sb + B_QEMPTY, 1);
          w_load(0, 4);
        }
#pragma unroll 1
        for (int i = 0; i < W.nloc; i++) {
          const int tl = W.loc0 + i, last = tl * 128 + 127 < NN ? tl * 128 + 127 : NN - 1;
          flag_wait(F_AGG + ((last >= NGW) + (last >= 4 * NGW) + (last >= 9 * NGW)) * LN_, (epoch + 1) * NGW); fence_async_gmem();
          if (total == 0) g_flag[F_EPOCH] = epoch + 1;
          q_load(g_agg + tl * 4096, total > 0 || i > 0);
        }
        if (fin && !tail) {
          int h = 0, c = 2, have = W.slotB >= 0 ? 2 : 0;
          mbar_wait(sb + B_BG, 0);
#pragma unroll 1
          for (uint32_t it = 0; (h < 2 || c < 4) && it < (1u << 23); it++) {
            if (have < 2) {
              uint2 f;
              asm volatile("ld.relaxed.gpu.global.v2.u32 {%0,%1}, [%2];" : "=r"(f.x), "=r"(f.y) : "l"(g_flag + F_PART + W.slotA * LN_) : "memory");
              have = (int)(f.x - (epoch + 1)) < 0 ? 0 : ((int)(f.y - (epoch + 1)) < 0 ? 1 : 2);
            }
            if (h < have && mbar_try_wait_nb(sb + B_QEMPTY + 8 * h, 0)) {
              asm volatile("fence.acquire.gpu;" ::: "memory"); fence_async_gmem();
              STAMP(true, 2, 14 + h);
              mbar_expect_tx(sb + B_QFULL + 8 * h, 32768 + 512);
              bulk_g2s(sb + SM_ML + h * 512, g_ml + W.slotA * 128 + h * 64, 512, sb + B_QFULL + 8 * h);
              bulk_g2s(sb + SM_Q + h * 32768, g_part + W.slotA * 4096 + h * 2048, 32768, sb + B_QFULL + 8 * h);
              h++;
            }
            const bool half = mbar_try_wait_nb(sb + B_HALF, 0);
            const int c1 = half ? 4 : (h > 0 ? 3 : 2);
            if (c < c1) { w_load(c, c1); c = c1; }
          }
        } else if (!fin && total > 0) {
#pragma unroll 1
          for (int h = 0; h < 2; h++) part_out(W.slotB, h, (posw >> 12) + h, 1);
          asm volatile("cp.async.bulk.wait_group.read 1;" ::: "memory");
          w_load(3, 4);
          asm volatile("cp.async.bulk.wait_group 1;" ::: "memory");
          announce(F_PART + W.slotB * LN_);
          STAMP(true, 2, 14);
          bulk_wait_all();
          announce(F_PART + W.slotB * LN_ + 1);
          STAMP(true, 2, 15);
        }
        DUMP(true, 2, 14, 16);
        DUMP(true, 2, 0, 8);
      }
      return;
    }
  }
    {
      const int gw = cta * 3 + warp - 1;
      ROLE;
      if (total > 0) {
        mbar_wait_w(sb + B_EVQ, 0);
        const uint32_t c0 = clk();
        if (warp == 3 && W.own) {
          const uint4 s0 = lds128(sb + SM_ML + (W.own == 2) * 512 + lane * 16), s1 = lds128(sb + SM_ML + (W.own >> 1) * 512 + lane * 16);
          const float rm = __uint_as_float(min(min(s0.x - 1, s0.z - 1), min(s1.x - 1, s1.z - 1)) + 1);
          const uint32_t ex = __reduce_max_sync(0xffffffffu, __float_as_uint(rm > 0.f ? fmaf(-1e-5f * rm, rm, 1.000001f) : 0.f) >> 24);
          if (lane == 0) asm volatile("red.relaxed.gpu.global.max.u32 [%0], %1;" :: "l"(g_flag + F_RHO), "r"(ep1 * 64 + ex) : "memory");
          flag_release_w(F_RC);
        }
        if (warp == 1 && (W.role & R_PUB)) {
          g_unsafe[W.q0] = lds32(sb + SM_UNSAFE);
#pragma unroll 1
          for (int k = 0; k < 4; k++) {
            __nanosleep(2000);
            if (lane == 0) bulk_s2g(pofs<uint4>(g_qp, W.q0 * 65536 + k * 16384), sb + SM_Q + k * 16384, 16384);
            bulk_commit();
          }
          bulk_wait_all();
          flag_release_w(F_QP + W.q0 * LN_);
        }
        while (__any_sync(0xffffffffu, clk() - c0 < GSTART)) __nanosleep(500);
        STAMP(lane == 0 && warp == 1, 2, 8);
#define ovf_cnt pofs<uint32_t>(g_flag, (F_OVF + (ep1 & 1) * LN_) * 4)
        if (gw == 0) g_flag[F_OVF + ((ep1 + 1) & 1) * LN_] = 0;
#pragma unroll 1
        for (int e0 = gw * 32; e0 < NE; e0 += NGW * 32 * 7) {
          int d[7], s[7], pos[7];
          const int* pd = pofs<const int>(P.dst, (e0 + lane) * 4);
          const int* ps = pofs<const int>(P.src, (e0 + lane) * 4);
#pragma unroll
          for (int k = 0; k < 7; k++) { const bool ok = e0 + k * NGW * 32 < NE; d[k] = ok ? __ldcs(pd + k * NGW * 32) : -1; s[k] = ok ? __ldcs(ps + k * NGW * 32) : 0; }
          uint32_t ov = 0;
#pragma unroll
          for (int k = 0; k < 7; k++) {
            pos[k] = 0;
            if (d[k] >= 0) asm volatile("atom.relaxed.gpu.global.add.u32 %0, [%1], 1;" : "=r"(pos[k]) : "l"(pofs<int>(g_cnt, d[k] << 2)) : "memory");
            s[k] = (uint32_t)(uintptr_t)g_u + s[k] * 512;
            if (d[k] >= 0 && pos[k] < CAP) asm volatile("st.volatile.global.u32 [%0], %1;" :: "l"(pofs<int>(g_bin, (d[k] * CAPS + pos[k]) << 2)), "r"(s[k]) : "memory");
            ov |= (pos[k] >= CAP) << k;
          }
          if (__any_sync(0xffffffffu, ov != 0)) {
            uint32_t at;
            asm volatile("atom.relaxed.gpu.global.add.u32 %0, [%1], %2;" : "=r"(at) : "l"(ovf_cnt), "r"(__popc(ov)) : "memory");
#pragma unroll
            for (int k = 0; k < 7; k++) if ((ov >> k) & 1) g_ovf[at++] = make_int2(d[k], s[k]);
          }
        }
        flag_wait_w(F_RC, ep1 * NHSIG);
        const uint32_t ush = max(62 - (int)(__shfl_sync(0xffffffffu, ld_relaxed(g_flag + F_RHO), 0) & 63), 0) << 23;
        const float us = __uint_as_float(__float_as_uint(US) + ush);
#pragma unroll 1
        for (int n0 = gw; n0 < NN; n0 += 4 * NGW) {
          uint4 xv[4]; float2 st[4];
#pragma unroll
          for (int k = 0; k < 4; k++) {
            const int n = n0 + k * NGW < NN ? n0 + k * NGW : n0;
            xv[k] = ldcs_v(pofs<const uint4>(P.x, n * 512 + lane * 16));
            st[k] = __ldcg(pofs<const float2>(g_stat, n * 8));
          }
#pragma unroll
          for (int k = 3; k >= 0; k--) {
            const int n = n0 + k * NGW;
            const float a = st[k].x * us, c = fmaf(st[k].y, us, UB + 8388608.0f);
#define FIX(w) __byte_perm(__float_as_uint(fmaf(bf_lo(w), a, c)), __float_as_uint(fmaf(bf_hi(w), a, c)), 0x5410)
            if (n < NN) {
              *pofs<uint4>(P.out, n * 512 + lane * 16) = xv[k];
              *pofs<uint4>(g_u, n * 512 + lane * 16) = make_uint4(FIX(xv[k].x), FIX(xv[k].y), FIX(xv[k].z), FIX(xv[k].w));
            }
          }
        }
        flag_release_w(F_BIN);
        STAMP(lane == 0 && warp == 1, 2, 9);
        flag_wait_w(F_BIN, ep1 * NGW);
        STAMP(lane == 0 && warp == 1, 2, 10);
        const int myn = gw + lane * NGW < NN ? gw + lane * NGW : gw;
        int cnts = __ldcg(g_cnt + myn);
        cnts = gw + lane * NGW < NN ? (cnts > CAP ? CAP + 1 : cnts) | ((int)__ldg((const unsigned short*)P.dinv + myn) << 16) : 0;
        __syncwarp();
        g_cnt[myn] = 0;
        const uint32_t uhi = (uintptr_t)g_u >> 32, lx = lane * 16;
        uint32_t obin = gw * CAPS * 4;
        auto bin = [&](uint32_t ofs, int r, int first) {
          uint32_t en;
          asm volatile("{\n.reg .pred p;\nsetp.lt.u32 p, %2, %3;\nmov.u32 %0, 0;\n@p ld.global.cg.u32 %0, [%1];\n}\n"
                       : "=&r"(en) : "l"(pofs<const uint32_t>(g_bin, ofs + first * 4 + lx / 4)), "r"(lx + first * 16), "r"((__shfl_sync(0xffffffffu, cnts, r) & 0xffff) * 16) : "memory");
          return en;
        };
        uint32_t ent = bin(obin, 0, 0), entn = bin(obin + NGW * CAPS * 4, 1, 0);
        int cd = __shfl_sync(0xffffffffu, cnts, 0), cb = min(cd & 0xffff, CAP), e = 0;
        uint32_t sa[4] = {0, 0, 0, 0}, sh[4] = {0, 0, 0, 0};
        auto add = [&](uint32_t x, uint32_t y, uint32_t z, uint32_t w) {
          sa[0] += x; sa[1] += y; sa[2] += z; sa[3] += w;
          sh[0] += x >> 16; sh[1] += y >> 16; sh[2] += z >> 16; sh[3] += w >> 16;
        };
        int rnd = -1, rows = -1, cdo = 0;
#pragma unroll 1
        for (;;) {
          const bool hold = rows >= 0 && rnd == 8;
          const int m = hold ? 0 : cb - e;
          uint4 v[8];
          if (m >= 8) {
#pragma unroll
            for (int k = 0; k < 8; k++) v[k] = ldcg_v(addr64(__shfl_sync(0xffffffffu, ent, k) + lx, uhi));
          } else {
#pragma unroll
            for (int k = 0; k < 8; k++) {
              v[k] = make_uint4(0, 0, 0, 0);
              if (k < 7) ldcg_if(v[k], addr64(__shfl_sync(0xffffffffu, ent, k) + lx, uhi), k < m);
            }
          }
          if (rows >= 0) {
            const int n = gw + rnd * NGW;
            if (n < NN) {
              const float di = __uint_as_float(cdo & 0xffff0000u) * __uint_as_float(__float_as_uint(1.0f / US) - ush), nl = -di * UB * (float)rows;
#define AGG(k) pack_bf16(fmaf((float)(sa[k] - (sh[k] << 16)), di, nl), fmaf((float)sh[k], di, nl))
              *pofs<uint4>(g_agg, ((n >> 3) * 4096 + (n & 7) * 144) ^ ((lx & 0x70) | ((lx & 0x180) << 3))) = make_uint4(AGG(0), AGG(1), AGG(2), AGG(3));
            }
#pragma unroll
            for (int k = 0; k < 4; k++) sa[k] = sh[k] = 0;
            rows = -1;
            if (rnd == 0 || rnd == 3 || rnd == 8 || rnd == NRND - 1) flag_release_w(F_AGG + ((rnd > 0) + (rnd > 3) + (rnd > 8)) * LN_);
            if (rnd == NRND - 1) break;
            if (hold) {
              if (fin && W.slotB >= 0) {
#pragma unroll 1
                for (int k = 0; k < 2; k++) flag_wait_w(F_PART + (k ? W.slotB : W.slotA) * LN_, ep1);
#pragma unroll 1
                for (int b = warp - 1; b < 8; b += 3) {
                  float2* ma = g_ml + W.slotA * 128 + b * 16 + g;
                  const float2* mb = g_ml + W.slotB * 128 + b * 16 + g;
                  const float2 a0 = __ldcg(ma), a1 = __ldcg(ma + 8), b0 = __ldcg(mb), b1 = __ldcg(mb + 8);
                  const float x0 = fmaxf(a0.x, b0.x), x1 = fmaxf(a1.x, b1.x);
                  const float fa0 = ex2(a0.x - x0), fa1 = ex2(a1.x - x1), fb0 = ex2(b0.x - x0), fb1 = ex2(b1.x - x1);
                  __syncwarp();
                  if (t == 0) { ma[0] = make_float2(x0, a0.y * fa0 + b0.y * fb0); ma[8] = make_float2(x1, a1.y * fa1 + b1.y * fb1); }
                  const uint32_t ofs = ((b >> 2) * 2048 + (b & 3) * 32 + lane) * 16;
#pragma unroll 1
                  for (int u = 0; u < 16; u += 4) {
                    uint4* pa = pofs<uint4>(g_part, W.slotA * 65536 + ofs + u * 2048);
                    const uint4* pb = pofs<const uint4>(g_part, W.slotB * 65536 + ofs + u * 2048);
                    uint4 va[4], vb[4];
#pragma unroll
                    for (int k = 0; k < 4; k++) { va[k] = ldcg_v(pa + k * 128); vb[k] = ldcs_v(pb + k * 128); }
#define FOLD(w, fa, fb) pack_bf16(bf_lo(va[k].w) * fa + bf_lo(vb[k].w) * fb, bf_hi(va[k].w) * fa + bf_hi(vb[k].w) * fb)
#pragma unroll
                    for (int k = 3; k >= 0; k--) pa[k * 128] = make_uint4(FOLD(x, fa0, fb0), FOLD(y, fa1, fb1), FOLD(z, fa0, fb0), FOLD(w, fa1, fb1));
                  }
                }
                bar_sync(3, 96);
                if (warp == 1) asm volatile("fence.acq_rel.gpu;" ::: "memory");
              }
              if (fin && warp == 1 && lane == 0) mbar_arrive(sb + B_BG);
              while (__any_sync(0xffffffffu, clk() - c0 < GPAUSE)) __nanosleep(500);
              continue;
            }
          }
#define SUM8(f) (v[7].f + v[6].f + v[5].f + v[4].f + v[3].f + v[2].f + v[1].f + v[0].f)
          add(SUM8(x), SUM8(y), SUM8(z), SUM8(w));
          e += 8;
          if (e < cb) {
            ent = __shfl_down_sync(0xffffffffu, ent, 8);
            if (e == 32) ent = bin(obin, rnd + 1, 32);
            continue;
          }
          rnd++; rows = cb; cdo = cd;
          if ((cd & 0xffff) > CAP) {
            const int no = __shfl_sync(0xffffffffu, (int)ld_relaxed(ovf_cnt), 0);
#pragma unroll 1
            for (int i0 = 0; i0 < no; i0 += 32) {
              int2 en = __ldcg(g_ovf + min(i0 + lane, no - 1));
              uint32_t mk = __ballot_sync(0xffffffffu, en.x == gw + rnd * NGW && i0 + lane < no);
              rows += __popc(mk);
#pragma unroll 1
              while (mk) {
                const int bit = __ffs(mk) - 1; mk &= mk - 1;
                const uint4 r = ldcg_v(addr64((uint32_t)__shfl_sync(0xffffffffu, en.y, bit) + lx, uhi));
                add(r.x, r.y, r.z, r.w);
              }
            }
          }
          obin += NGW * CAPS * 4;
          ent = entn; entn = bin(obin + NGW * CAPS * 4, rnd + 2, 0);
          cd = __shfl_sync(0xffffffffu, cnts, rnd + 1); cb = min(cd & 0xffff, CAP); e = 0;
        }
      }
      STAMP(lane == 0 && warp == 1, 2, 11);
      if (warp == 2 && fin && lane == 0) {
        prefetch_l2(pofs<uint8_t>(P.out, W.q0 * 65536), tail ? 8192 : 65536);
        if (W.slotB >= 0) prefetch_l2(pofs<uint8_t>(g_part, W.slotA * 65536), 65536);
        flag_wait(F_W, ep1);
        prefetch_l2(pofs<uint8_t>(g_Wvo, (cta & 63) * 4096), 4096);
      }
      DUMP(warp == 1 && lane == 0, 2, 8, 14);
    }
}

}

extern "C" void kernel_launch(void* const* d_in, const int* in_sizes, int n_in, void* d_out, int out_size) {
  Params P;
  P.x = (const __nv_bfloat16*)d_in[0];
  P.src = (const int*)d_in[1];
  P.dst = (const int*)d_in[2];
  P.dinv = (const __nv_bfloat16*)d_in[3];
  P.wmsg = (const __nv_bfloat16*)d_in[4];
  P.wq = (const __nv_bfloat16*)d_in[5];
  P.wk = (const __nv_bfloat16*)d_in[6];
  P.wv = (const __nv_bfloat16*)d_in[7];
  P.wout = (const __nv_bfloat16*)d_in[8];
  P.out = (__nv_bfloat16*)d_out;
  P.zero = 0;
  for (int c = 0; c < NCTA; c++) P.w[c] = make_work(c);
  static void* scr = nullptr;
  if (!scr) {
    cudaFuncSetAttribute(gps_kernel, cudaFuncAttributeMaxDynamicSharedMemorySize, SMEM_BYTES);
    cudaGetSymbolAddress(&scr, g_scr);
  }
  P.s = (Scratch*)((((uintptr_t)scr + SCR_ALIGN - 1) & ~(uintptr_t)(SCR_ALIGN - 1)) + SCR_OFS);
  P.u = (uint4*)(((uintptr_t)P.s->u + 511) & ~(uintptr_t)511);
  if (((uintptr_t)P.u >> 32) != (((uintptr_t)(P.u + NN * 32) - 1) >> 32)) P.u += NN * 32;
  gps_kernel<<<NCTA, 384, SMEM_BYTES>>>(P);
}
```

```cpp
#include <cuda_runtime.h>
#include <cuda_bf16.h>
#include <stdint.h>
#include <stddef.h>
#include <type_traits>
#define FB 5
#define MB 5
#define GSTART 40000
#define XD 3
#define NTAIL 5
#define PACE 64
#define GPAUSE 112000
#define CREG 224
#define BACKOFF 1000

namespace {

constexpr int NN = 10000;
constexpr int NE = 160000;
constexpr int NQT = 79;
constexpr int NCTA = 132;
constexpr int CAP = 64;
constexpr int CAPS = 64;
constexpr int NHSIG = 105;
constexpr uint32_t WCH_B = 32768;
constexpr int NGW = (NCTA - 1) * 3;
constexpr float TAU = 16.0f;
constexpr float SAFE_N2 = 31.0f, SAFE_C = 0.6f;
#define KOFF 3
#define PSH -8.0f
constexpr float US = 256.0f, UB = 4095.0f;
constexpr float KS = 0.25f, KC = KOFF * KS;
constexpr uint32_t KC2 = KOFF == 2 ? 0x3f003f00u : (KOFF == 1 ? 0x3e803e80u : 0x3f403f40u);

constexpr int NAGG = 4;
constexpr int NRND = (NN + NGW - 1) / NGW;
constexpr int NSLOT = 105;
constexpr int F_EPOCH = 0, F_GE = 1, F_H = 2, F_M = 4  , F_H1 = 8  , F_RHO = 11, F_RC = 12, LN_ = 32;
constexpr int F_BIN = LN_, F_W = 2 * LN_, F_OVF = 3 * LN_  , F_QP = 5 * LN_, F_AGG = F_QP + NQT * LN_,
              F_PART = F_AGG + NAGG * LN_, F_END = F_PART + NSLOT * LN_;

struct Scratch {
  uint32_t flag[F_END];
  alignas(4096) uint4 M[8192];
  uint4 Wvo[8192], Wmo[8192];
  float2 ml[NSLOT * 128];
  uint32_t unsafe[96];
  int cnt[NN + 32];
  float2 stat[NQT * 128];
  alignas(4096) uint4 h[NQT * 4096];
  uint4 u[2 * NN * 32 + 32];
  uint4 qp[NQT * 4096];
  uint4 agg[NQT * 4096];
  uint4 part[NSLOT * 4096];
  int bin[NN * CAPS];
  int2 ovf[NE];
};
static_assert(offsetof(Scratch, h) % 128 == 0, "alignment");
#define SCR_ALIGN (2u << 20)
#define SCR_OFS 0
__device__ uint4 g_scr[(sizeof(Scratch) + SCR_ALIGN + SCR_OFS) / 16];
struct alignas(16) Work { short k0, k1; signed char q0, hp, nb0, na0, nb1, na1, slotA, slotB, loc0, nloc, own, role; };
constexpr int R_FIN = 1, R_PUB = 2, R_TAIL = 4, R_SIG = 8  ;
struct Params {
  const __nv_bfloat16 *x, *wq, *wk;
  Scratch* s;
  uint4* u;
  __nv_bfloat16* out;
  const __nv_bfloat16 *wout, *wmsg, *wv, *dinv;
  const int *src, *dst;
  long long zero;
  Work w[NCTA];
};
constexpr int first_cnt(int k) { return 2 * ((k + 6) / 8 - k / 8 + 1); }
constexpr int NH1_0 = 2, NH1_1 = first_cnt(48 * 8 - MB), NH1_2 = first_cnt(48 * 8 - MB + 16 * 8 - (15 - MB) / 2);
constexpr int NSERV = NQT - 52;
inline Work make_work(int c) {
  Work w;
  const int gi = c / 5, r = c % 5, q = gi * 3;
  const bool helper = r & 1, mid = r == 2;
  w.q0 = helper ? q + 1 : q + (r >> 1);
  const int hb1 = (15 - MB) / 2, hb3 = 15 - MB - hb1;
  w.nb0 = helper ? (r == 1 ? hb1 : hb3) : (mid ? MB : FB);
  w.na0 = (helper ? 16 : 48) - w.nb0;
  w.k0 = helper ? (48 * 8 - MB) + (r >> 1) * (16 * 8 - hb1) : 0;
  w.k1 = 48 * 8 - FB;
  w.nb1 = helper ? (FB < 7 ? 7 : 15) - FB : 0;
  w.na1 = helper ? (FB < 7 ? 31 : 32) - w.nb1 : 0;
  w.slotA = 4 * gi + (helper ? r - 1 : (mid ? 0 : (r >> 1) + 1));
  w.slotB = helper ? 4 * gi + r : (mid ? 4 * gi + 2 : -1);
  w.loc0 = NSERV + gi * 2 + (r >> 1);
  w.nloc = helper;
  w.own = helper ? (r + 1) >> 1 : (mid ? 0 : 3);
  w.role = helper ? 0 : (mid ? R_FIN : R_FIN | R_PUB);
  const int k1st[3] = {0, 48 * 8 - MB, 48 * 8 - MB + 16 * 8 - hb1};
  int pos[NQT], sig[NQT];
  for (int i = 0; i < NQT; i++) { pos[i] = i; sig[i] = 0; }
  for (int i = 0; i < 3; i++)
    for (int p = k1st[i] / 8; p <= (k1st[i] + 6) / 8; p++) {
      int m = 1, at = 0;
      while (sig[m]) m += 3;
      while (pos[at] != p) at++;
      pos[at] = pos[m]; pos[m] = p; sig[m] = 1 + i;
    }
  w.hp = c < 131 ? pos[w.q0] : 0;
  if (helper && c < 130) w.role |= sig[w.q0] * R_SIG;
  if (c == 130) { w.nb0 = 15; w.na0 = 65; w.slotA = NSLOT - 1; w.own = 1; w.role = R_FIN | R_TAIL; w.loc0 = NSERV - NTAIL; w.nloc = NTAIL; }
  if (c == 131) { w.nb0 = w.na0 = w.nb1 = w.na1 = 0; w.loc0 = 0; w.nloc = NSERV - NTAIL; w.own = 0; }
  return w;
}
#define g_flag P.s->flag
#define g_M P.s->M
#define g_Wvo P.s->Wvo
#define g_Wmo P.s->Wmo
#define g_ml P.s->ml
#define g_unsafe P.s->unsafe
#define g_cnt P.s->cnt
#define g_h P.s->h
#define g_u P.u
#define g_stat P.s->stat
#define g_qp P.s->qp
#define g_agg P.s->agg
#define g_part P.s->part
#define g_bin P.s->bin
#define g_ovf P.s->ovf

__device__ __forceinline__ uint32_t smem_u32(const void* p) { return (uint32_t)__cvta_generic_to_shared(p); }
__device__ __forceinline__ void mbar_init(uint32_t bar, uint32_t cnt) { asm volatile("mbarrier.init.shared::cta.b64 [%0], %1;" :: "r"(bar), "r"(cnt) : "memory"); }
__device__ __forceinline__ void mbar_arrive(uint32_t bar) { asm volatile("mbarrier.arrive.shared::cta.b64 _, [%0];" :: "r"(bar) : "memory"); }
__device__ __forceinline__ void mbar_expect_tx(uint32_t bar, uint32_t bytes) { asm volatile("mbarrier.arrive.expect_tx.shared::cta.b64 _, [%0], %1;" :: "r"(bar), "r"(bytes) : "memory"); }
__device__ __forceinline__ bool mbar_try_wait(uint32_t bar, uint32_t parity) {
  uint32_t ok;
  asm volatile("{\n.reg .pred p;\nmbarrier.try_wait.parity.shared::cta.b64 p, [%1], %2;\nselp.b32 %0, 1, 0, p;\n}\n" : "=r"(ok) : "r"(bar), "r"(parity) : "memory");
  return ok;
}
__device__ __forceinline__ bool mbar_try_wait_nb(uint32_t bar, uint32_t parity) {
  uint32_t ok;
  asm volatile("{\n.reg .pred p;\nmbarrier.test_wait.parity.shared::cta.b64 p, [%1], %2;\nselp.b32 %0, 1, 0, p;\n}\n" : "=r"(ok) : "r"(bar), "r"(parity) : "memory");
  return ok;
}
__device__ __forceinline__ void mbar_wait(uint32_t bar, uint32_t parity) {
#pragma unroll 1
  for (uint32_t it = 0; it < (1u << 25); it++) if (mbar_try_wait(bar, parity)) break;
}
__device__ __forceinline__ void bulk_s2g(void* dst, uint32_t src, uint32_t bytes) {
  asm volatile("cp.async.bulk.global.shared::cta.bulk_group [%0], [%1], %2;" :: "l"(dst), "r"(src), "r"(bytes) : "memory");
}
__device__ __forceinline__ void bulk_commit() { asm volatile("cp.async.bulk.commit_group;" ::: "memory"); }
__device__ __forceinline__ void bulk_wait_read() { asm volatile("cp.async.bulk.wait_group.read 0;" ::: "memory"); }
__device__ __forceinline__ void bulk_wait_all() { asm volatile("cp.async.bulk.wait_group 0;" ::: "memory"); }
__device__ __forceinline__ bool bar_red_or(int id, int cnt, bool c) {
  uint32_t r;
  asm volatile("{\n.reg .pred p, q;\nsetp.ne.b32 q, %3, 0;\nbar.red.or.pred p, %1, %2, q;\nselp.b32 %0, 1, 0, p;\n}\n"
               : "=r"(r) : "r"(id), "r"(cnt), "r"((uint32_t)c) : "memory");
  return r != 0;
}
template <class T> __device__ __forceinline__ T* pofs(const void* base, uint32_t off) {
  asm volatile("" : "+r"(off));
  return (T*)((uint8_t*)base + off);
}
__device__ __forceinline__ const void* addr64(uint32_t lo, uint32_t hi) { uint64_t a; asm("mov.b64 %0, {%1, %2};" : "=l"(a) : "r"(lo), "r"(hi)); return (const void*)a; }
__device__ __forceinline__ uint4 ldcg_v(const void* a) {
  uint4 v;
  asm volatile("ld.volatile.global.v4.u32 {%0,%1,%2,%3}, [%4];" : "=r"(v.x), "=r"(v.y), "=r"(v.z), "=r"(v.w) : "l"(a) : "memory");
  return v;
}
__device__ __forceinline__ uint4 ldcs_v(const void* a) {
  uint4 v;
  asm volatile("ld.global.cs.v4.u32 {%0,%1,%2,%3}, [%4];" : "=r"(v.x), "=r"(v.y), "=r"(v.z), "=r"(v.w) : "l"(a) : "memory");
  return v;
}
__device__ __forceinline__ void prefetch_l2(const void* a, uint32_t bytes) { asm volatile("cp.async.bulk.prefetch.L2.global [%0], %1;" :: "l"(a), "r"(bytes) : "memory"); }
__device__ __forceinline__ void ldcg_if(uint4& v, const void* a, bool c) {
  asm volatile("{\n.reg .pred p;\nsetp.ne.b32 p, %5, 0;\n@p ld.volatile.global.v4.u32 {%0,%1,%2,%3}, [%4];\n}\n"
               : "+r"(v.x), "+r"(v.y), "+r"(v.z), "+r"(v.w) : "l"(a), "r"((uint32_t)c) : "memory");
}
__device__ __forceinline__ void cp_async16(uint32_t dst, const void* src) {
  asm volatile("cp.async.cg.shared.global [%0], [%1], 16;" :: "r"(dst), "l"(src) : "memory");
}
__device__ __forceinline__ void red_bf16x8(void* a, uint4 v) {
  asm volatile("red.global.add.noftz.v4.bf16x2 [%0], {%1,%2,%3,%4};" :: "l"(a), "r"(v.x), "r"(v.y), "r"(v.z), "r"(v.w) : "memory");
}
__device__ __forceinline__ uint32_t clk() { uint32_t c; asm volatile("mov.u32 %0, %%clock;" : "=r"(c) :: "memory"); return c; }
__device__ __forceinline__ void stsm4(uint32_t a, uint32_t r0, uint32_t r1, uint32_t r2, uint32_t r3) {
  asm volatile("stmatrix.sync.aligned.m8n8.x4.shared.b16 [%0], {%1,%2,%3,%4};" :: "r"(a), "r"(r0), "r"(r1), "r"(r2), "r"(r3) : "memory");
}
__device__ __forceinline__ void ldsm4(uint32_t a, uint32_t& r0, uint32_t& r1, uint32_t& r2, uint32_t& r3) {
  asm volatile("ldmatrix.sync.aligned.m8n8.x4.shared.b16 {%0,%1,%2,%3}, [%4];" : "=r"(r0), "=r"(r1), "=r"(r2), "=r"(r3) : "r"(a) : "memory");
}
__device__ __forceinline__ void red_relaxed(uint32_t* p) { asm volatile("red.relaxed.gpu.global.add.u32 [%0], 1;" :: "l"(p) : "memory"); }
__device__ __forceinline__ uint32_t lds32(uint32_t a) { uint32_t v; asm volatile("ld.shared.u32 %0, [%1];" : "=r"(v) : "r"(a) : "memory"); return v; }
__device__ __forceinline__ void cp_commit() { asm volatile("cp.async.commit_group;" ::: "memory"); }
__device__ __forceinline__ uint32_t hmul2(uint32_t a, uint32_t b) { uint32_t d; asm("mul.rn.bf16x2 %0, %1, %2;" : "=r"(d) : "r"(a), "r"(b)); return d; }
__device__ __forceinline__ uint32_t hfma2(uint32_t a, uint32_t b, uint32_t c) { uint32_t d; asm("fma.rn.bf16x2 %0, %1, %2, %3;" : "=r"(d) : "r"(a), "r"(b), "r"(c)); return d; }
__device__ __forceinline__ uint32_t pow2_bf2(int n) { return (uint32_t)max(n + 127, 0) * 0x00800080u; }
__device__ __forceinline__ int fexp(float x) { return (int)(__float_as_uint(x) >> 23) - 127; }
__device__ __forceinline__ void bulk_g2s(uint32_t dst, const void* src, uint32_t bytes, uint32_t bar) {
  asm volatile("cp.async.bulk.shared::cta.global.mbarrier::complete_tx::bytes [%0], [%1], %2, [%3];"
    :: "r"(dst), "l"(src), "r"(bytes), "r"(bar) : "memory");
}
__device__ __forceinline__ void bulk_g2s_last(uint32_t dst, const void* src, uint32_t bytes, uint32_t bar) {
  asm volatile("{\n.reg .b64 p;\ncreatepolicy.fractional.L2::evict_first.b64 p;\n"
    "cp.async.bulk.shared::cta.global.mbarrier::complete_tx::bytes.L2::cache_hint [%0], [%1], %2, [%3], p;\n}\n"
    :: "r"(dst), "l"(src), "r"(bytes), "r"(bar) : "memory");
}
__device__ __forceinline__ void wg_fence() { asm volatile("wgmma.fence.sync.aligned;" ::: "memory"); }
__device__ __forceinline__ void wg_commit() { asm volatile("wgmma.commit_group.sync.aligned;" ::: "memory"); }
template<int N> __device__ __forceinline__ void wg_wait() { asm volatile("wgmma.wait_group.sync.aligned %0;" :: "n"(N) : "memory"); }
__device__ __forceinline__ void bar_sync(int id, int cnt) { asm volatile("bar.sync %0, %1;" :: "r"(id), "r"(cnt) : "memory"); }
__device__ __forceinline__ void fence_async_smem() { asm volatile("fence.proxy.async.shared::cta;" ::: "memory"); }
__device__ __forceinline__ void fence_async_gmem() { asm volatile("fence.proxy.async.global;" ::: "memory"); }
__device__ __forceinline__ void bar_arrive(int id, int cnt) { asm volatile("bar.arrive %0, %1;" :: "r"(id), "r"(cnt) : "memory"); }
__device__ __forceinline__ void red_release(uint32_t* p) { asm volatile("red.release.gpu.global.add.u32 [%0], 1;" :: "l"(p) : "memory"); }
__device__ __forceinline__ void red_release_w(uint32_t* p) {
  __syncwarp();
  asm volatile("{\n.reg .pred q;\n.reg .b32 l;\nmov.u32 l, %%laneid;\nsetp.eq.u32 q, l, 0;\n@q fence.release.gpu;\n@q red.relaxed.gpu.global.add.u32 [%0], 1;\n}\n" :: "l"(p) : "memory");
}
__device__ __forceinline__ void mbar_wait_w(uint32_t bar, uint32_t parity) {
#pragma unroll 1
  for (uint32_t it = 0; it < (1u << 25); it++) if (__all_sync(0xffffffffu, mbar_try_wait(bar, parity))) break;
}
#define flag_release_w(f) red_release_w(g_flag + (f))
#define flag_wait_w(f, target) poll_acquire_w(g_flag + (f), target)
#define flag_release(f) red_release(g_flag + (f))
__device__ __forceinline__ uint32_t ld_relaxed(const uint32_t* p) {
  uint32_t v; asm volatile("ld.relaxed.gpu.global.u32 %0, [%1];" : "=r"(v) : "l"(p) : "memory"); return v;
}
#define flag_wait(f, target) poll_acquire(g_flag + (f), target)
__device__ __forceinline__ void poll_acquire(const uint32_t* p, uint32_t target) {
#pragma unroll 1
  for (uint32_t it = 0; it < (1u << 23); it++) if ((int)(ld_relaxed(p) - target) >= 0) break;
  asm volatile("fence.acquire.gpu;" ::: "memory");
}
__device__ __forceinline__ void poll_acquire_w(const uint32_t* p, uint32_t target) {
#pragma unroll 1
  for (uint32_t it = 0; it < (1u << 23); it++) {
    if (__all_sync(0xffffffffu, (int)(ld_relaxed(p) - target) >= 0)) break;
    if (BACKOFF) __nanosleep(BACKOFF);
  }
  asm volatile("fence.acquire.gpu;" ::: "memory");
}
template<int N> __device__ __forceinline__ void reg_fence(float (&d)[N]) {
#pragma unroll
  for (int i = 0; i < N; i++) asm volatile("" : "+f"(d[i]) :: "memory");
}
template<int N> __device__ __forceinline__ void reg_fence(uint32_t (&d)[N]) {
#pragma unroll
  for (int i = 0; i < N; i++) asm volatile("" : "+r"(d[i]) :: "memory");
}
__device__ __forceinline__ float ex2(float x) { float y; asm("ex2.approx.ftz.f32 %0, %1;" : "=f"(y) : "f"(x)); return y; }
__device__ __forceinline__ uint32_t pack_bf16(float lo, float hi) { uint32_t r; asm("cvt.rn.bf16x2.f32 %0, %1, %2;" : "=r"(r) : "f"(hi), "f"(lo)); return r; }
__device__ __forceinline__ float bf_lo(uint32_t w) { return __uint_as_float(w << 16); }
__device__ __forceinline__ float bf_hi(uint32_t w) { return __uint_as_float(w & 0xffff0000u); }
__device__ __forceinline__ uint64_t desc_k(uint32_t addr, uint32_t add) { return (uint64_t)((((addr & 0x3FFFF) >> 4) | (1u << 16)) + add) | (0x40000100ull << 32); }
__device__ __forceinline__ uint64_t desc_mn(uint32_t addr, uint32_t add) { return (uint64_t)((((addr & 0x3FFFF) >> 4) | ((1024u >> 4) << 16)) + add) | (0x40000100ull << 32); }
__device__ __forceinline__ uint64_t desc_m(uint32_t addr, uint32_t add) { return (uint64_t)((((addr & 0x3FFFF) >> 4) | ((1024u >> 4) << 16)) + add) | (0x80000020ull << 32); }
__device__ __forceinline__ void sts128(uint32_t a, uint4 v) { asm volatile("st.shared.v4.u32 [%0], {%1,%2,%3,%4};" :: "r"(a), "r"(v.x), "r"(v.y), "r"(v.z), "r"(v.w) : "memory"); }
__device__ __forceinline__ uint4 lds128(uint32_t a) { uint4 v; asm volatile("ld.shared.v4.u32 {%0,%1,%2,%3}, [%4];" : "=r"(v.x), "=r"(v.y), "=r"(v.z), "=r"(v.w) : "r"(a) : "memory"); return v; }
__device__ __forceinline__ void mma16816(float (&c)[4], uint32_t a0, uint32_t a1, uint32_t a2, uint32_t a3, uint32_t b0, uint32_t b1) {
  asm volatile("mma.sync.aligned.m16n8k16.row.col.f32.bf16.bf16.f32 {%0,%1,%2,%3}, {%4,%5,%6,%7}, {%8,%9}, {%0,%1,%2,%3};"
    : "+f"(c[0]), "+f"(c[1]), "+f"(c[2]), "+f"(c[3]) : "r"(a0), "r"(a1), "r"(a2), "r"(a3), "r"(b0), "r"(b1));
}
__device__ __forceinline__ uint32_t sw_byte(int r, int c) {
  return (uint32_t)((r >> 3) * 4096 + (c >> 6) * 1024 + (r & 7) * 128 + ((((c >> 3) & 7) ^ (r & 7)) << 4) + (c & 7) * 2);
}
__device__ __forceinline__ int cta_id() { int c; asm volatile("mov.u32 %0, %%ctaid.x;" : "=r"(c)); return c; }
__device__ __forceinline__ bool tid_is(int v) { int t; asm volatile("mov.u32 %0, %%tid.x;" : "=r"(t)); return t == v; }
#define STAMP(cond, who, i)
#define CSTAMP(cond, who, i)
#define DUMP(cond, who, i0, i1)
#define XSTAMP(cond, i)
#define SSTAMP(i)

template <int OA, int OB> __device__ __forceinline__ void wgmma_ss_n256_tb(float (&d)[128], uint64_t da, uint64_t db, int scale_d) {
  asm volatile("{\n.reg .pred p;\n.reg .b64 a, b;\nsetp.ne.b32 p, %130, 0;\nadd.s64 a, %128, %131;\nadd.s64 b, %129, %132;\n"
    "wgmma.mma_async.sync.aligned.m64n256k16.f32.bf16.bf16 "
    "{%0, %1, %2, %3, %4, %5, %6, %7, %8, %9, %10, %11, %12, %13, %14, %15, %16, %17, %18, %19, %20, %21, %22, %23, %24, %25, %26, %27, %28, %29, %30, %31, %32, %33, %34, %35, %36, %37, %38, %39, %40, %41, %42, %43, %44, %45, %46, %47, %48, %49, %50, %51, %52, %53, %54, %55, %56, %57, %58, %59, %60, %61, %62, %63, %64, %65, %66, %67, %68, %69, %70, %71, %72, %73, %74, %75, %76, %77, %78, %79, %80, %81, %82, %83, %84, %85, %86, %87, %88, %89, %90, %91, %92, %93, %94, %95, %96, %97, %98, %99, %100, %101, %102, %103, %104, %105, %106, %107, %108, %109, %110, %111, %112, %113, %114, %115, %116, %117, %118, %119, %120, %121, %122, %123, %124, %125, %126, %127}, "
    "a, b, p, 1, 1, 0, 1;\n}\n"
    : "+f"(d[0]), "+f"(d[1]), "+f"(d[2]), "+f"(d[3]), "+f"(d[4]), "+f"(d[5]), "+f"(d[6]), "+f"(d[7]), "+f"(d[8]), "+f"(d[9]), "+f"(d[10]), "+f"(d[11]), "+f"(d[12]), "+f"(d[13]), "+f"(d[14]), "+f"(d[15]), "+f"(d[16]), "+f"(d[17]), "+f"(d[18]), "+f"(d[19]), "+f"(d[20]), "+f"(d[21]), "+f"(d[22]), "+f"(d[23]), "+f"(d[24]), "+f"(d[25]), "+f"(d[26]), "+f"(d[27]), "+f"(d[28]), "+f"(d[29]), "+f"(d[30]), "+f"(d[31]), "+f"(d[32]), "+f"(d[33]), "+f"(d[34]), "+f"(d[35]), "+f"(d[36]), "+f"(d[37]), "+f"(d[38]), "+f"(d[39]), "+f"(d[40]), "+f"(d[41]), "+f"(d[42]), "+f"(d[43]), "+f"(d[44]), "+f"(d[45]), "+f"(d[46]), "+f"(d[47]), "+f"(d[48]), "+f"(d[49]), "+f"(d[50]), "+f"(d[51]), "+f"(d[52]), "+f"(d[53]), "+f"(d[54]), "+f"(d[55]), "+f"(d[56]), "+f"(d[57]), "+f"(d[58]), "+f"(d[59]), "+f"(d[60]), "+f"(d[61]), "+f"(d[62]), "+f"(d[63]), "+f"(d[64]), "+f"(d[65]), "+f"(d[66]), "+f"(d[67]), "+f"(d[68]), "+f"(d[69]), "+f"(d[70]), "+f"(d[71]), "+f"(d[72]), "+f"(d[73]), "+f"(d[74]), "+f"(d[75]), "+f"(d[76]), "+f"(d[77]), "+f"(d[78]), "+f"(d[79]), "+f"(d[80]), "+f"(d[81]), "+f"(d[82]), "+f"(d[83]), "+f"(d[84]), "+f"(d[85]), "+f"(d[86]), "+f"(d[87]), "+f"(d[88]), "+f"(d[89]), "+f"(d[90]), "+f"(d[91]), "+f"(d[92]), "+f"(d[93]), "+f"(d[94]), "+f"(d[95]), "+f"(d[96]), "+f"(d[97]), "+f"(d[98]), "+f"(d[99]), "+f"(d[100]), "+f"(d[101]), "+f"(d[102]), "+f"(d[103]), "+f"(d[104]), "+f"(d[105]), "+f"(d[106]), "+f"(d[107]), "+f"(d[108]), "+f"(d[109]), "+f"(d[110]), "+f"(d[111]), "+f"(d[112]), "+f"(d[113]), "+f"(d[114]), "+f"(d[115]), "+f"(d[116]), "+f"(d[117]), "+f"(d[118]), "+f"(d[119]), "+f"(d[120]), "+f"(d[121]), "+f"(d[122]), "+f"(d[123]), "+f"(d[124]), "+f"(d[125]), "+f"(d[126]), "+f"(d[127])
    : "l"(da), "l"(db), "r"(scale_d), "n"(OA), "n"(OB));
}
template <int OA, int OB> __device__ __forceinline__ void wgmma_qk(float (&d)[64], uint64_t da, uint64_t db, int scale_d) {
  asm volatile("{\n.reg .pred p;\n.reg .b64 a, b;\nsetp.ne.b32 p, %66, 0;\nadd.s64 a, %64, %67;\nadd.s64 b, %65, %68;\n"
    "wgmma.mma_async.sync.aligned.m64n128k16.f32.bf16.bf16 "
    "{%0, %1, %2, %3, %4, %5, %6, %7, %8, %9, %10, %11, %12, %13, %14, %15, %16, %17, %18, %19, %20, %21, %22, %23, %24, %25, %26, %27, %28, %29, %30, %31, %32, %33, %34, %35, %36, %37, %38, %39, %40, %41, %42, %43, %44, %45, %46, %47, %48, %49, %50, %51, %52, %53, %54, %55, %56, %57, %58, %59, %60, %61, %62, %63}, "
    "a, b, p, 1, 1, 0, 0;\n}\n"
    : "+f"(d[0]), "+f"(d[1]), "+f"(d[2]), "+f"(d[3]), "+f"(d[4]), "+f"(d[5]), "+f"(d[6]), "+f"(d[7]), "+f"(d[8]), "+f"(d[9]), "+f"(d[10]), "+f"(d[11]), "+f"(d[12]), "+f"(d[13]), "+f"(d[14]), "+f"(d[15]), "+f"(d[16]), "+f"(d[17]), "+f"(d[18]), "+f"(d[19]), "+f"(d[20]), "+f"(d[21]), "+f"(d[22]), "+f"(d[23]), "+f"(d[24]), "+f"(d[25]), "+f"(d[26]), "+f"(d[27]), "+f"(d[28]), "+f"(d[29]), "+f"(d[30]), "+f"(d[31]), "+f"(d[32]), "+f"(d[33]), "+f"(d[34]), "+f"(d[35]), "+f"(d[36]), "+f"(d[37]), "+f"(d[38]), "+f"(d[39]), "+f"(d[40]), "+f"(d[41]), "+f"(d[42]), "+f"(d[43]), "+f"(d[44]), "+f"(d[45]), "+f"(d[46]), "+f"(d[47]), "+f"(d[48]), "+f"(d[49]), "+f"(d[50]), "+f"(d[51]), "+f"(d[52]), "+f"(d[53]), "+f"(d[54]), "+f"(d[55]), "+f"(d[56]), "+f"(d[57]), "+f"(d[58]), "+f"(d[59]), "+f"(d[60]), "+f"(d[61]), "+f"(d[62]), "+f"(d[63])
    : "l"(da), "l"(db), "r"(scale_d), "n"(OA), "n"(OB));
}
template <int OA, int OB> __device__ __forceinline__ void wgmma_qk(float (&d)[56], uint64_t da, uint64_t db, int scale_d) {
  asm volatile("{\n.reg .pred p;\n.reg .b64 a, b;\nsetp.ne.b32 p, %58, 0;\nadd.s64 a, %56, %59;\nadd.s64 b, %57, %60;\n"
    "wgmma.mma_async.sync.aligned.m64n112k16.f32.bf16.bf16 "
    "{%0, %1, %2, %3, %4, %5, %6, %7, %8, %9, %10, %11, %12, %13, %14, %15, %16, %17, %18, %19, %20, %21, %22, %23, %24, %25, %26, %27, %28, %29, %30, %31, %32, %33, %34, %35, %36, %37, %38, %39, %40, %41, %42, %43, %44, %45, %46, %47, %48, %49, %50, %51, %52, %53, %54, %55}, "
    "a, b, p, 1, 1, 0, 0;\n}\n"
    : "+f"(d[0]), "+f"(d[1]), "+f"(d[2]), "+f"(d[3]), "+f"(d[4]), "+f"(d[5]), "+f"(d[6]), "+f"(d[7]), "+f"(d[8]), "+f"(d[9]), "+f"(d[10]), "+f"(d[11]), "+f"(d[12]), "+f"(d[13]), "+f"(d[14]), "+f"(d[15]), "+f"(d[16]), "+f"(d[17]), "+f"(d[18]), "+f"(d[19]), "+f"(d[20]), "+f"(d[21]), "+f"(d[22]), "+f"(d[23]), "+f"(d[24]), "+f"(d[25]), "+f"(d[26]), "+f"(d[27]), "+f"(d[28]), "+f"(d[29]), "+f"(d[30]), "+f"(d[31]), "+f"(d[32]), "+f"(d[33]), "+f"(d[34]), "+f"(d[35]), "+f"(d[36]), "+f"(d[37]), "+f"(d[38]), "+f"(d[39]), "+f"(d[40]), "+f"(d[41]), "+f"(d[42]), "+f"(d[43]), "+f"(d[44]), "+f"(d[45]), "+f"(d[46]), "+f"(d[47]), "+f"(d[48]), "+f"(d[49]), "+f"(d[50]), "+f"(d[51]), "+f"(d[52]), "+f"(d[53]), "+f"(d[54]), "+f"(d[55])
    : "l"(da), "l"(db), "r"(scale_d), "n"(OA), "n"(OB));
}
template <int OB> __device__ __forceinline__ void wgmma_rs_n256_tb(float (&d)[128], uint32_t a0, uint32_t a1, uint32_t a2, uint32_t a3, uint64_t db, int scale_d) {
  asm volatile("{\n.reg .pred p;\n.reg .b64 b;\nsetp.ne.b32 p, %133, 0;\nadd.s64 b, %132, %134;\n"
    "wgmma.mma_async.sync.aligned.m64n256k16.f32.bf16.bf16 "
    "{%0, %1, %2, %3, %4, %5, %6, %7, %8, %9, %10, %11, %12, %13, %14, %15, %16, %17, %18, %19, %20, %21, %22, %23, %24, %25, %26, %27, %28, %29, %30, %31, %32, %33, %34, %35, %36, %37, %38, %39, %40, %41, %42, %43, %44, %45, %46, %47, %48, %49, %50, %51, %52, %53, %54, %55, %56, %57, %58, %59, %60, %61, %62, %63, %64, %65, %66, %67, %68, %69, %70, %71, %72, %73, %74, %75, %76, %77, %78, %79, %80, %81, %82, %83, %84, %85, %86, %87, %88, %89, %90, %91, %92, %93, %94, %95, %96, %97, %98, %99, %100, %101, %102, %103, %104, %105, %106, %107, %108, %109, %110, %111, %112, %113, %114, %115, %116, %117, %118, %119, %120, %121, %122, %123, %124, %125, %126, %127}, "
    "{%128, %129, %130, %131}, b, p, 1, 1, 1;\n}\n"
    : "+f"(d[0]), "+f"(d[1]), "+f"(d[2]), "+f"(d[3]), "+f"(d[4]), "+f"(d[5]), "+f"(d[6]), "+f"(d[7]), "+f"(d[8]), "+f"(d[9]), "+f"(d[10]), "+f"(d[11]), "+f"(d[12]), "+f"(d[13]), "+f"(d[14]), "+f"(d[15]), "+f"(d[16]), "+f"(d[17]), "+f"(d[18]), "+f"(d[19]), "+f"(d[20]), "+f"(d[21]), "+f"(d[22]), "+f"(d[23]), "+f"(d[24]), "+f"(d[25]), "+f"(d[26]), "+f"(d[27]), "+f"(d[28]), "+f"(d[29]), "+f"(d[30]), "+f"(d[31]), "+f"(d[32]), "+f"(d[33]), "+f"(d[34]), "+f"(d[35]), "+f"(d[36]), "+f"(d[37]), "+f"(d[38]), "+f"(d[39]), "+f"(d[40]), "+f"(d[41]), "+f"(d[42]), "+f"(d[43]), "+f"(d[44]), "+f"(d[45]), "+f"(d[46]), "+f"(d[47]), "+f"(d[48]), "+f"(d[49]), "+f"(d[50]), "+f"(d[51]), "+f"(d[52]), "+f"(d[53]), "+f"(d[54]), "+f"(d[55]), "+f"(d[56]), "+f"(d[57]), "+f"(d[58]), "+f"(d[59]), "+f"(d[60]), "+f"(d[61]), "+f"(d[62]), "+f"(d[63]), "+f"(d[64]), "+f"(d[65]), "+f"(d[66]), "+f"(d[67]), "+f"(d[68]), "+f"(d[69]), "+f"(d[70]), "+f"(d[71]), "+f"(d[72]), "+f"(d[73]), "+f"(d[74]), "+f"(d[75]), "+f"(d[76]), "+f"(d[77]), "+f"(d[78]), "+f"(d[79]), "+f"(d[80]), "+f"(d[81]), "+f"(d[82]), "+f"(d[83]), "+f"(d[84]), "+f"(d[85]), "+f"(d[86]), "+f"(d[87]), "+f"(d[88]), "+f"(d[89]), "+f"(d[90]), "+f"(d[91]), "+f"(d[92]), "+f"(d[93]), "+f"(d[94]), "+f"(d[95]), "+f"(d[96]), "+f"(d[97]), "+f"(d[98]), "+f"(d[99]), "+f"(d[100]), "+f"(d[101]), "+f"(d[102]), "+f"(d[103]), "+f"(d[104]), "+f"(d[105]), "+f"(d[106]), "+f"(d[107]), "+f"(d[108]), "+f"(d[109]), "+f"(d[110]), "+f"(d[111]), "+f"(d[112]), "+f"(d[113]), "+f"(d[114]), "+f"(d[115]), "+f"(d[116]), "+f"(d[117]), "+f"(d[118]), "+f"(d[119]), "+f"(d[120]), "+f"(d[121]), "+f"(d[122]), "+f"(d[123]), "+f"(d[124]), "+f"(d[125]), "+f"(d[126]), "+f"(d[127])
    : "r"(a0), "r"(a1), "r"(a2), "r"(a3), "l"(db), "r"(scale_d), "n"(OB));
}
template <int OB> __device__ __forceinline__ void wgmma_rs_n256_tb_first(float (&d)[128], uint32_t a0, uint32_t a1, uint32_t a2, uint32_t a3, uint64_t db) {
  asm volatile("{\n.reg .pred p;\n.reg .b64 b;\nsetp.ne.b32 p, 0, 0;\nadd.s64 b, %132, %133;\n"
    "wgmma.mma_async.sync.aligned.m64n256k16.f32.bf16.bf16 "
    "{%0, %1, %2, %3, %4, %5, %6, %7, %8, %9, %10, %11, %12, %13, %14, %15, %16, %17, %18, %19, %20, %21, %22, %23, %24, %25, %26, %27, %28, %29, %30, %31, %32, %33, %34, %35, %36, %37, %38, %39, %40, %41, %42, %43, %44, %45, %46, %47, %48, %49, %50, %51, %52, %53, %54, %55, %56, %57, %58, %59, %60, %61, %62, %63, %64, %65, %66, %67, %68, %69, %70, %71, %72, %73, %74, %75, %76, %77, %78, %79, %80, %81, %82, %83, %84, %85, %86, %87, %88, %89, %90, %91, %92, %93, %94, %95, %96, %97, %98, %99, %100, %101, %102, %103, %104, %105, %106, %107, %108, %109, %110, %111, %112, %113, %114, %115, %116, %117, %118, %119, %120, %121, %122, %123, %124, %125, %126, %127}, "
    "{%128, %129, %130, %131}, b, p, 1, 1, 1;\n}\n"
    : "=f"(d[0]), "=f"(d[1]), "=f"(d[2]), "=f"(d[3]), "=f"(d[4]), "=f"(d[5]), "=f"(d[6]), "=f"(d[7]), "=f"(d[8]), "=f"(d[9]), "=f"(d[10]), "=f"(d[11]), "=f"(d[12]), "=f"(d[13]), "=f"(d[14]), "=f"(d[15]), "=f"(d[16]), "=f"(d[17]), "=f"(d[18]), "=f"(d[19]), "=f"(d[20]), "=f"(d[21]), "=f"(d[22]), "=f"(d[23]), "=f"(d[24]), "=f"(d[25]), "=f"(d[26]), "=f"(d[27]), "=f"(d[28]), "=f"(d[29]), "=f"(d[30]), "=f"(d[31]), "=f"(d[32]), "=f"(d[33]), "=f"(d[34]), "=f"(d[35]), "=f"(d[36]), "=f"(d[37]), "=f"(d[38]), "=f"(d[39]), "=f"(d[40]), "=f"(d[41]), "=f"(d[42]), "=f"(d[43]), "=f"(d[44]), "=f"(d[45]), "=f"(d[46]), "=f"(d[47]), "=f"(d[48]), "=f"(d[49]), "=f"(d[50]), "=f"(d[51]), "=f"(d[52]), "=f"(d[53]), "=f"(d[54]), "=f"(d[55]), "=f"(d[56]), "=f"(d[57]), "=f"(d[58]), "=f"(d[59]), "=f"(d[60]), "=f"(d[61]), "=f"(d[62]), "=f"(d[63]), "=f"(d[64]), "=f"(d[65]), "=f"(d[66]), "=f"(d[67]), "=f"(d[68]), "=f"(d[69]), "=f"(d[70]), "=f"(d[71]), "=f"(d[72]), "=f"(d[73]), "=f"(d[74]), "=f"(d[75]), "=f"(d[76]), "=f"(d[77]), "=f"(d[78]), "=f"(d[79]), "=f"(d[80]), "=f"(d[81]), "=f"(d[82]), "=f"(d[83]), "=f"(d[84]), "=f"(d[85]), "=f"(d[86]), "=f"(d[87]), "=f"(d[88]), "=f"(d[89]), "=f"(d[90]), "=f"(d[91]), "=f"(d[92]), "=f"(d[93]), "=f"(d[94]), "=f"(d[95]), "=f"(d[96]), "=f"(d[97]), "=f"(d[98]), "=f"(d[99]), "=f"(d[100]), "=f"(d[101]), "=f"(d[102]), "=f"(d[103]), "=f"(d[104]), "=f"(d[105]), "=f"(d[106]), "=f"(d[107]), "=f"(d[108]), "=f"(d[109]), "=f"(d[110]), "=f"(d[111]), "=f"(d[112]), "=f"(d[113]), "=f"(d[114]), "=f"(d[115]), "=f"(d[116]), "=f"(d[117]), "=f"(d[118]), "=f"(d[119]), "=f"(d[120]), "=f"(d[121]), "=f"(d[122]), "=f"(d[123]), "=f"(d[124]), "=f"(d[125]), "=f"(d[126]), "=f"(d[127])
    : "r"(a0), "r"(a1), "r"(a2), "r"(a3), "l"(db), "n"(OB));
}
template <int OB> __device__ __forceinline__ void wgmma_rs_n128_tb(float (&d)[64], uint32_t a0, uint32_t a1, uint32_t a2, uint32_t a3, uint64_t db, int scale_d) {
  asm volatile("{\n.reg .pred p;\n.reg .b64 b;\nsetp.ne.b32 p, %69, 0;\nadd.s64 b, %68, %70;\n"
    "wgmma.mma_async.sync.aligned.m64n128k16.f32.bf16.bf16 "
    "{%0, %1, %2, %3, %4, %5, %6, %7, %8, %9, %10, %11, %12, %13, %14, %15, %16, %17, %18, %19, %20, %21, %22, %23, %24, %25, %26, %27, %28, %29, %30, %31, %32, %33, %34, %35, %36, %37, %38, %39, %40, %41, %42, %43, %44, %45, %46, %47, %48, %49, %50, %51, %52, %53, %54, %55, %56, %57, %58, %59, %60, %61, %62, %63}, "
    "{%64, %65, %66, %67}, b, p, 1, 1, 1;\n}\n"
    : "+f"(d[0]), "+f"(d[1]), "+f"(d[2]), "+f"(d[3]), "+f"(d[4]), "+f"(d[5]), "+f"(d[6]), "+f"(d[7]), "+f"(d[8]), "+f"(d[9]), "+f"(d[10]), "+f"(d[11]), "+f"(d[12]), "+f"(d[13]), "+f"(d[14]), "+f"(d[15]), "+f"(d[16]), "+f"(d[17]), "+f"(d[18]), "+f"(d[19]), "+f"(d[20]), "+f"(d[21]), "+f"(d[22]), "+f"(d[23]), "+f"(d[24]), "+f"(d[25]), "+f"(d[26]), "+f"(d[27]), "+f"(d[28]), "+f"(d[29]), "+f"(d[30]), "+f"(d[31]), "+f"(d[32]), "+f"(d[33]), "+f"(d[34]), "+f"(d[35]), "+f"(d[36]), "+f"(d[37]), "+f"(d[38]), "+f"(d[39]), "+f"(d[40]), "+f"(d[41]), "+f"(d[42]), "+f"(d[43]), "+f"(d[44]), "+f"(d[45]), "+f"(d[46]), "+f"(d[47]), "+f"(d[48]), "+f"(d[49]), "+f"(d[50]), "+f"(d[51]), "+f"(d[52]), "+f"(d[53]), "+f"(d[54]), "+f"(d[55]), "+f"(d[56]), "+f"(d[57]), "+f"(d[58]), "+f"(d[59]), "+f"(d[60]), "+f"(d[61]), "+f"(d[62]), "+f"(d[63])
    : "r"(a0), "r"(a1), "r"(a2), "r"(a3), "l"(db), "r"(scale_d), "n"(OB));
}
template <int V> using IC = std::integral_constant<int, V>;
template <int I, int N, class F> __device__ __forceinline__ void static_for(F&& f) {
  if constexpr (I < N) { f(std::integral_constant<int, I>{}); static_for<I + 1, N>(f); }
}

constexpr uint32_t SM_Q = 0, SM_BAR = 7 * 32768;
constexpr uint32_t B_FULL = SM_BAR, B_EMPTY = B_FULL + 24, B_WF = B_EMPTY + 24, B_QFULL = B_WF + 32, B_QEMPTY = B_QFULL + 16,
                   B_EVH = B_QEMPTY + 16, B_EVQ = B_EVH + 8, B_EVP0 = B_EVQ + 8, B_BG = B_EVP0 + 16, B_M0 = B_BG + 8, B_HALF = B_M0 + 8,
                   B_HRD = B_HALF + 8, SM_UNSAFE = B_HRD + 8, SM_TS = SM_UNSAFE + 8, SM_ML = (SM_TS + 192 + 15) / 16 * 16, SM_EPOCH = SM_ML + 1024, SM_GE = SM_EPOCH + 4, SM_END = SM_EPOCH + 16;
constexpr uint32_t POS_M = 0x5462;
constexpr int SMEM_BYTES = SM_END;

#define ROW0(u) make_uint4(pack_bf16(o[16 * u], o[16 * u + 1]), pack_bf16(o[16 * u + 4], o[16 * u + 5]), \
                           pack_bf16(o[16 * u + 8], o[16 * u + 9]), pack_bf16(o[16 * u + 12], o[16 * u + 13]))
#define ROW1(u) make_uint4(pack_bf16(o[16 * u + 2], o[16 * u + 3]), pack_bf16(o[16 * u + 6], o[16 * u + 7]), \
                           pack_bf16(o[16 * u + 10], o[16 * u + 11]), pack_bf16(o[16 * u + 14], o[16 * u + 15]))

__global__ void __launch_bounds__(384, 1) gps_kernel(const __grid_constant__ Params P) {
  extern __shared__ __align__(1024) uint8_t smem_raw[];
  constexpr uint32_t sb = 1024;
  if (smem_u32(smem_raw) != sb) return;
  const int cta = blockIdx.x;
  const int wg = __shfl_sync(0xffffffffu, (int)threadIdx.x >> 7, 0);
  const int warp = __shfl_sync(0xffffffffu, ((int)threadIdx.x >> 5) & 3, 0);
  const int lane = threadIdx.x & 31;
#define ROLE                                                                                       \
  const Work& W = P.w[cta_id()];                                                                   \
  [[maybe_unused]] const int n0 = W.nb0 + W.na0, n1 = W.nb1 + W.na1, total = n0 + n1;              \
  [[maybe_unused]] const bool fin = W.role & R_FIN, tail = W.role & R_TAIL;                        \
  [[maybe_unused]] const uint32_t posw = total == 0 || tail ? POS_M : ((total & 1) ? 0x2546 : 0x4326)
  const int g = lane >> 2, t = lane & 3;
  if (wg < 2) {
    const int tid = threadIdx.x & 127;
    ROLE;
    const uint32_t sQ = sb + SM_Q + wg * 32768;
#define st0 tid_is(wg * 128)
    STAMP(st0, wg, 0);
    const int rr = lane >> 3, j = lane & 7;
    const uint4* px[4];
#pragma unroll
    for (int i = 0; i < 4; i++) px[i] = (const uint4*)(P.x + (size_t)min(W.q0 * 128 + wg * 64 + warp * 16 + i * 4 + rr, NN - 1) * 256) + j;
    asm volatile("" : "+l"(px[0]), "+l"(px[1]), "+l"(px[2]), "+l"(px[3]));
    if (cta * 8 + wg * 4 + warp == 131 * 8) {
      const uint4 xs = __ldg((const uint4*)P.x + lane * 312 * 32);
      const uint32_t ep = ld_relaxed(g_flag + F_EPOCH);
      const float d0 = bf_lo(xs.x) - bf_hi(xs.x), d1 = bf_lo(xs.y) - bf_hi(xs.y), d2 = bf_lo(xs.z) - bf_hi(xs.z), d3 = bf_lo(xs.w) - bf_hi(xs.w);
      const int ge = __reduce_max_sync(0xffffffffu, __float_as_uint((d0 * d0 + d1 * d1 + d2 * d2 + d3 * d3) * (0.125f / 1e-5f)) >> 24);
      if (lane == 0) asm volatile("st.relaxed.gpu.global.u32 [%0], %1;" :: "l"(g_flag + F_GE), "r"((ep + 1) * 16 + min(max(63 - ge, 0), 12)) : "memory");
    }
    __syncwarp();
    auto x_load = [&](int c) {
      if (c < 4) {
#pragma unroll
        for (int i = 0; i < 4; i++)
          cp_async16(sQ + warp * 8192 + (i >> 1) * 4096 + c * 1024 + ((i & 1) * 4 + rr) * 128 + ((j ^ ((i & 1) * 4 + rr)) << 4), px[i] + c * 8);
      }
      cp_commit();
    };
    auto start = [&]() {
      bar_sync(4, 384);
      if (wg == 1) bar_arrive(5, 256);
    };

    const uint32_t sF = sQ + warp * 8192 + ((lane >> 3) & 1) * 4096 + (lane & 7) * 128;
    auto frag = [&](int k) { return sF + (k >> 2) * 1024 + ((((k & 3) * 2 + (lane >> 4)) ^ (lane & 7)) << 4); };
    uint32_t hq[64];
    const bool own = (W.own >> wg) & 1;
    auto layernorm = [&]() __attribute__((always_inline)) {
#pragma unroll
      for (int c = 0; c < XD; c++) x_load(c);
      start();
      float c1[4] = {0.f, 0.f, 0.f, 0.f}, ca[4] = {0.f, 0.f, 0.f, 0.f}, cb[4] = {0.f, 0.f, 0.f, 0.f};
#pragma unroll
      for (int k = 0; k < 16; k++) {
        if ((k & 3) == 0) {
          asm volatile("cp.async.wait_group %0;" :: "n"(XD - 1) : "memory");
          __syncwarp();
          x_load(k / 4 + XD);
        }
        ldsm4(frag(k), hq[4 * k], hq[4 * k + 1], hq[4 * k + 2], hq[4 * k + 3]);
        mma16816(c1, hq[4 * k], hq[4 * k + 1], hq[4 * k + 2], hq[4 * k + 3], 0x3f803f80u, 0x3f803f80u);
        mma16816(ca, hq[4 * k], hq[4 * k + 1], hq[4 * k + 2], hq[4 * k + 3], hq[4 * k], hq[4 * k + 2]);
        mma16816(cb, hq[4 * k], hq[4 * k + 1], hq[4 * k + 2], hq[4 * k + 3], hq[4 * k + 1], hq[4 * k + 3]);
      }
      const float mu0 = c1[0] * (1.0f / 256.0f), mu1 = c1[2] * (1.0f / 256.0f);
      const float v0 = fmaf(__shfl_sync(0xffffffffu, g & 1 ? ca[1] : ca[0], g * 4 + (g >> 1)), 1.0f / 256.0f, 1e-5f - mu0 * mu0);
      const float v1 = fmaf(__shfl_sync(0xffffffffu, g & 1 ? cb[3] : cb[2], g * 4 + (g >> 1)), 1.0f / 256.0f, 1e-5f - mu1 * mu1);
      float rs0, rs1;
      asm("rsqrt.approx.ftz.f32 %0, %1;" : "=f"(rs0) : "f"(v0)); asm("rsqrt.approx.ftz.f32 %0, %1;" : "=f"(rs1) : "f"(v1));
      if (W.q0 * 128 + wg * 64 + warp * 16 >= NN) rs0 = rs1 = 0.f;
      float nb0 = -mu0 * rs0, nb1 = -mu1 * rs1;
      const uint32_t sS = sb + SM_ML + (wg * 64 + warp * 16) * 8;
      if (t == 0) {
        asm volatile("st.shared.v2.f32 [%0], {%1,%2};" :: "r"(sS + g * 8), "f"(rs0), "f"(nb0) : "memory");
        asm volatile("st.shared.v2.f32 [%0], {%1,%2};" :: "r"(sS + g * 8 + 64), "f"(rs1), "f"(nb1) : "memory");
      }
      if (__any_sync(0xffffffffu, !(4.f * mu0 * mu0 <= v0) || !(4.f * mu1 * mu1 <= v1))) {
#pragma unroll 1
        for (int r = 0; r < 16; r++) {
          const uint32_t ad = sQ + warp * 8192 + (r >> 3) * 4096 + rr * 1024 + (r & 7) * 128 + ((j ^ (r & 7)) << 4);
          const uint4 v = lds128(ad);
          float f[8] = {bf_lo(v.x), bf_hi(v.x), bf_lo(v.y), bf_hi(v.y), bf_lo(v.z), bf_hi(v.z), bf_lo(v.w), bf_hi(v.w)};
          float sum = 0.f, ss = 0.f, rs;
#pragma unroll
          for (int i = 0; i < 8; i++) sum += f[i];
#pragma unroll 1
          for (int k = 1; k < 32; k *= 2) sum += __shfl_xor_sync(0xffffffffu, sum, k);
          sum *= 1.0f / 256.0f;
#pragma unroll
          for (int i = 0; i < 8; i++) { f[i] -= sum; ss += f[i] * f[i]; }
#pragma unroll 1
          for (int k = 1; k < 32; k *= 2) ss += __shfl_xor_sync(0xffffffffu, ss, k);
          asm("rsqrt.approx.ftz.f32 %0, %1;" : "=f"(rs) : "f"(fmaf(ss, 1.0f / 256.0f, 1e-5f)));
          if (W.q0 * 128 + wg * 64 + warp * 16 >= NN) rs = 0.f;
          sts128(ad, make_uint4(pack_bf16(f[0] * rs, f[1] * rs), pack_bf16(f[2] * rs, f[3] * rs), pack_bf16(f[4] * rs, f[5] * rs), pack_bf16(f[6] * rs, f[7] * rs)));
          if (lane == 0) asm volatile("st.shared.v2.f32 [%0], {%1,%2};" :: "r"(sS + r * 8), "f"(rs), "f"(-sum * rs) : "memory");
        }
        __syncwarp();
#pragma unroll
        for (int k = 0; k < 16; k++) ldsm4(frag(k), hq[4 * k], hq[4 * k + 1], hq[4 * k + 2], hq[4 * k + 3]);
        rs0 = rs1 = 1.f; nb0 = nb1 = 0.f;
      }
      asm volatile("setmaxnreg.inc.sync.aligned.u32 %0;" :: "n"(CREG));
      const uint32_t ah0 = pack_bf16(rs0, rs0), ah1 = pack_bf16(rs1, rs1), n0_ = pack_bf16(nb0, nb0), n1_ = pack_bf16(nb1, nb1);
      const uint32_t al0 = pack_bf16(rs0 - bf_lo(ah0), rs0 - bf_lo(ah0)), al1 = pack_bf16(rs1 - bf_lo(ah1), rs1 - bf_lo(ah1));
#pragma unroll
      for (int i = 0; i < 32; i++) {
        hq[2 * i] = hfma2(hq[2 * i], ah0, hfma2(hq[2 * i], al0, n0_));
        hq[2 * i + 1] = hfma2(hq[2 * i + 1], ah1, hfma2(hq[2 * i + 1], al1, n1_));
      }
      bar_sync(8 + wg, 160);
      if (own) {
        const float ks = __uint_as_float(__float_as_uint(KS) + lds32(sb + SM_GE));
        const uint32_t ks2 = pack_bf16(ks, ks);
        const float e0 = fmaf(bf_hi(__shfl_sync(0xffffffffu, hq[62], lane | 3)), -0.5f * ks, KC), e1 = fmaf(bf_hi(__shfl_sync(0xffffffffu, hq[63], lane | 3)), -0.5f * ks, KC);
#pragma unroll
        for (int k = 0; k < 16; k++)
          stsm4(frag(k), hfma2(hq[4 * k], ks2, KC2), hfma2(hq[4 * k + 1], ks2, KC2),
                k < 15 ? hfma2(hq[4 * k + 2], ks2, KC2) : pack_bf16(fmaf(bf_lo(hq[62]), ks, e0), t == 3 ? KC : fmaf(bf_hi(hq[62]), ks, e0)),
                k < 15 ? hfma2(hq[4 * k + 3], ks2, KC2) : pack_bf16(fmaf(bf_lo(hq[63]), ks, e1), t == 3 ? KC : fmaf(bf_hi(hq[63]), ks, e1)));
      }
      __syncwarp();
      if (lane == 0) mbar_arrive(sb + B_EVH);
      STAMP(st0, wg, 1);
    };

    float o[128];
    int qph = 0, st = tail ? wg : 0, ph = 0;
    auto release = [&](int stg) { if (lane == 0) mbar_arrive(sb + B_EMPTY + 8 * stg); };
    int resume = total > 0 ? -1 : 0;
    auto fill = [&]() __attribute__((always_inline)) {
#pragma unroll
      for (int i = 0; i < 32; i++)
        asm volatile("ld.volatile.shared.v4.f32 {%0,%1,%2,%3}, [%4];" : "=f"(o[4 * i]), "=f"(o[4 * i + 1]), "=f"(o[4 * i + 2]), "=f"(o[4 * i + 3]) : "r"(sb) : "memory");
    };
    auto finish = [&]() __attribute__((always_inline)) {
      STAMP(st0, wg, 11);
      DUMP(st0, wg, 0, 16);
      if (!P.zero) { asm volatile("exit;"); __builtin_unreachable(); }
      fill();
    };
    auto run = [&](auto hot_) __attribute__((always_inline)) {
    constexpr bool HOT = hot_.value;
    const int nloc = P.w[cta_id()].nloc;
    if (!HOT && resume == 0) {
#pragma unroll 1
      for (int i = 0; i < 32; i++) {
        const int r = i * 8 + wg * 4 + warp;
        cp_async16(sb + ((POS_M >> (r >> 6) * 4) & 15) * 32768 + sw_byte(r & 63, lane * 8), (const uint4*)P.wout + r * 32 + lane);
      }
    }
    bool wide = false;
    if (HOT) {
      reg_fence(hq);
      auto qstep = [&](auto k_) {
        constexpr int k = k_.value;
        if (k < 2 || k % 4 == 0) { mbar_wait(k == 0 ? sb + B_M0 : sb + B_WF + 2 * (k & ~3), 0); if (k == 0 || k == 4) bar_sync(5 + wg, 256); wg_fence(); }
        if constexpr (k == 0) wgmma_rs_n256_tb_first<0>(o, hq[0], hq[1], hq[2], hq[3], desc_m(sb, (POS_M & 15) * 2048));
        else wgmma_rs_n256_tb<(k & 3) * 512>(o, hq[4 * k], hq[4 * k + 1], hq[4 * k + 2], hq[4 * k + 3], desc_m(sb, ((POS_M >> (k & ~3)) & 15) * 2048), 1);
      };
      static_for<0, 4>(qstep);
      wg_commit();
      bar_arrive(6 - wg, 256);
      wg_wait<0>();
      if (!tail) release(0);
      static_for<4, 16>(qstep);
      wg_commit();
      bar_arrive(6 - wg, 256);
      wg_wait<0>();
      reg_fence(o); reg_fence(hq);
      if (!tail) release(1);
      STAMP(st0, wg, 2);
      float c0 = (o[124] + (t == 3 ? 2.f : 1.f) * o[125]) * (-0.5f / 4.5f), c1 = (o[126] + (t == 3 ? 2.f : 1.f) * o[127]) * (-0.5f / 4.5f);
      c0 += __shfl_xor_sync(0xffffffffu, c0, 1); c1 += __shfl_xor_sync(0xffffffffu, c1, 1);
      c0 += __shfl_xor_sync(0xffffffffu, c0, 2); c1 += __shfl_xor_sync(0xffffffffu, c1, 2);
      float r0 = t == 3 ? 0.f : o[125], r1 = t == 3 ? 0.f : o[127], r2 = o[124], r3 = o[126];
#pragma unroll
      for (int i = 0; i < 31; i++) { r2 += o[4 * i]; r0 += o[4 * i + 1]; r3 += o[4 * i + 2]; r1 += o[4 * i + 3]; }
      r0 += r2; r1 += r3;
      r0 += __shfl_xor_sync(0xffffffffu, r0, 1); r1 += __shfl_xor_sync(0xffffffffu, r1, 1);
      r0 += __shfl_xor_sync(0xffffffffu, r0, 2); r1 += __shfl_xor_sync(0xffffffffu, r1, 2);
      wide = !(fabsf(c0) <= SAFE_C / KS) || !(fabsf(c1) <= SAFE_C / KS);
      const float ig = __uint_as_float(0x3f800000u - lds32(sb + SM_GE));
      c0 *= ig; c1 *= ig;
      r0 = fmaf(c0, -255.f, fmaf(r0, -ig, PSH / KC)); r1 = fmaf(c1, -255.f, fmaf(r1, -ig, PSH / KC));
      if (own) mbar_wait(sb + B_HRD, 0);
#pragma unroll
      for (int k = 0; k < 16; k++)
        stsm4(frag(k),
              pack_bf16(fmaf(o[8 * k], ig, c0), fmaf(o[8 * k + 1], ig, c0)), pack_bf16(fmaf(o[8 * k + 2], ig, c1), fmaf(o[8 * k + 3], ig, c1)),
              pack_bf16(fmaf(o[8 * k + 4], ig, c0), k == 15 && t == 3 ? r0 : fmaf(o[8 * k + 5], ig, c0)),
              pack_bf16(fmaf(o[8 * k + 6], ig, c1), k == 15 && t == 3 ? r1 : fmaf(o[8 * k + 7], ig, c1)));
      fence_async_smem();
      __syncwarp();
      STAMP(st0, wg, 3);
      if (tail) { bar_sync(7, 256); if (wg == 0) { release(0); release(1); release(2); } }
      }

    if (HOT || (resume && resume < 4)) {
      ROLE;
      float m0, m1;
      const int qh = tail ? 0 : wg, tl = tail;
      uint32_t qo = qh * 2048;
      const uint32_t ko = (2 - tl) * 2048, stop = 1 + tl + (uint32_t)P.zero;
      float l0, l1;
      auto row_sums = [&]() { l0 = __shfl_sync(0xffffffffu, o[125] + 0.f, lane | 3); l1 = __shfl_sync(0xffffffffu, o[127] + 0.f, lane | 3); };
#define PART(u) make_uint4(pack_bf16(o[8 * u] - l0, o[8 * u + 1] - l0), pack_bf16(o[8 * u + 2] - l1, o[8 * u + 3] - l1), \
                           pack_bf16(o[8 * u + 4] - l0, o[8 * u + 5] - l0), pack_bf16(o[8 * u + 6] - l1, o[8 * u + 7] - l1))
      bool unsafe = !HOT;
      m0 = m1 = 0.f;
#pragma unroll 1
      for (int seg = HOT ? 0 : resume - 1; seg < 2; seg++) {
        ROLE;
        const bool last = __any_sync(0xffffffffu, seg || n1 == 0);
        m0 = m1 = !HOT && unsafe ? -INFINITY : 0.f;
        int first = 1;
        auto tile = [&](auto n_, bool endseg) __attribute__((always_inline)) -> bool {
          constexpr int N = n_.value;
          float s[N / 2]; uint32_t p[N / 4];
          if (!mbar_try_wait(sb + B_FULL + 8 * st, ph)) mbar_wait(sb + B_FULL + 8 * st, ph);
          const bool again = !HOT && N == 112 && first && !seg;
          if (HOT || N == 128) bar_sync(5 + wg, 256);
          else asm volatile("{\n.reg .pred p;\nsetp.eq.u32 p, %1, 0;\n@p bar.sync %0, 256;\n}\n" :: "r"(5 + wg), "r"((uint32_t)again) : "memory");
          wg_fence();
          const uint64_t dQ = desc_k(sb + SM_Q, qo), dK = desc_k(sb, ko + st * 4096);
          qo += (uint32_t)P.zero;
          static_for<0, 16>([&](auto k) { constexpr int off = (k.value >> 2) * 64 + (k.value & 3) * 2; wgmma_qk<off, off>(s, dQ, dK, k.value > 0); });
          wg_commit();
          if (HOT || N == 128) bar_arrive(6 - wg, 256);
          else asm volatile("{\n.reg .pred p;\nsetp.eq.u32 p, %1, 0;\n@p bar.arrive %0, 256;\n}\n" :: "r"(6 - wg), "r"((uint32_t)again) : "memory");
          if (HOT && N == 112 && first && !seg) {
            float a0 = 0.f, a1 = 0.f, a2 = 0.f, a3 = 0.f;
#pragma unroll
            for (int i = 0; i < 32; i++) { a0 += o[4 * i] * o[4 * i]; a2 += o[4 * i + 1] * o[4 * i + 1]; a1 += o[4 * i + 2] * o[4 * i + 2]; a3 += o[4 * i + 3] * o[4 * i + 3]; }
            a0 += a2; a1 += a3;
            a0 += __shfl_xor_sync(0xffffffffu, a0, 1); a1 += __shfl_xor_sync(0xffffffffu, a1, 1);
            a0 += __shfl_xor_sync(0xffffffffu, a0, 2); a1 += __shfl_xor_sync(0xffffffffu, a1, 2);
            unsafe = __any_sync(0xffffffffu, bar_red_or(tail ? 7 : 1 + wg, tail ? 256 : 128, wide || !(a0 <= SAFE_N2 / (KS * KS)) || !(a1 <= SAFE_N2 / (KS * KS))));
            if (lane == 0) { asm volatile("st.shared.u8 [%0], %1;" :: "r"(sb + SM_UNSAFE + wg), "r"((uint32_t)unsafe) : "memory"); mbar_arrive(sb + B_EVQ); }
          }
          STAMP(N == 112 && first && !seg && st0, wg, 0);
          wg_wait<0>();
          reg_fence(s);
          if (HOT && N == 112 && unsafe) return true;
          if (endseg) { if (lane == 0) mbar_arrive(sb + B_QEMPTY + 8 * wg); }
          if (!HOT && unsafe) {
            float a0 = fmaxf(s[0], s[1]), a1 = fmaxf(s[2], s[3]);
#pragma unroll
            for (int i = 1; i < N / 8; i++) { a0 = fmaxf(a0, fmaxf(s[4 * i], s[4 * i + 1])); a1 = fmaxf(a1, fmaxf(s[4 * i + 2], s[4 * i + 3])); }
            if (__any_sync(0xffffffffu, (a0 > m0 + TAU) || (a1 > m1 + TAU))) {
              a0 = fmaxf(a0, __shfl_xor_sync(0xffffffffu, a0, 1)); a1 = fmaxf(a1, __shfl_xor_sync(0xffffffffu, a1, 1));
              a0 = fmaxf(a0, __shfl_xor_sync(0xffffffffu, a0, 2)); a1 = fmaxf(a1, __shfl_xor_sync(0xffffffffu, a1, 2));
              const float x0 = ceilf(fmaxf(m0, a0)), x1 = ceilf(fmaxf(m1, a1)), sc0 = ex2(m0 - x0), sc1 = ex2(m1 - x1);
              m0 = x0; m1 = x1;
#pragma unroll
              for (int i = 0; i < 32; i++) { o[4 * i] *= sc0; o[4 * i + 1] *= sc0; o[4 * i + 2] *= sc1; o[4 * i + 3] *= sc1; }
            }
#pragma unroll
            for (int i = 0; i < N / 8; i++) { s[4 * i] -= m0; s[4 * i + 1] -= m0; s[4 * i + 2] -= m1; s[4 * i + 3] -= m1; }
          }
          auto pv = [&](auto k) { wgmma_rs_n256_tb<k.value * 512 + (63 << 16)>(o, p[4 * k.value], p[4 * k.value + 1], p[4 * k.value + 2], p[4 * k.value + 3], dK, k.value > 0 || N == 128 ? 1 : !first); };
#pragma unroll
          for (int i = 0; i < 16; i++) { p[i] = pack_bf16(ex2(s[2 * i]), ex2(s[2 * i + 1])); asm volatile("" : "+r"(p[i]) :: "memory"); }
          reg_fence(o);
          do bar_sync(5 + wg, 256); while (P.zero);
          wg_fence();
          static_for<0, 4>(pv);
          wg_commit();
#pragma unroll
          for (int i = 16; i < N / 4; i++) { p[i] = pack_bf16(ex2(s[2 * i]), ex2(s[2 * i + 1])); asm volatile("" : "+r"(p[i]) :: "memory"); }
          wg_fence();
          static_for<4, N / 16>(pv);
          wg_commit();
          bar_arrive(6 - wg, 256);
          if (N == 128) { wg_wait<1>(); if (endseg && last) { if (lane == 0) mbar_arrive(sb + B_HALF); } }
          wg_wait<0>();
          reg_fence(o); reg_fence(p);
          release(st);
          if (st) { st--; ph ^= 1; } else st = stop;
          return false;
        };
#pragma unroll 1
        for (int left = tail ? 8 - wg : (seg ? W.nb1 : W.nb0); left > 0; left--) { if (tile(IC<112>{}, false)) { resume = 1; return; } STAMP(first && !seg && st0, wg, 4); first = 0; }
#pragma unroll 1
        for (int left = tail ? 32 + wg : (seg ? W.na1 : W.na0); left > 0; left--) tile(IC<128>{}, left == 1);
        STAMP(st0 && last, wg, 6);
        {
        ROLE;
        if (last && fin && !(tail && wg == 1)) break;
        row_sums();
        if (last) mbar_wait(sb + (tail ? B_QEMPTY : B_HALF), 0);
        const uint32_t sp = sb + (tail ? 0 : (last ? (posw >> 12) + wg : (wg ? 4 - 2 * st : 6))) * 32768, sm = sb + SM_ML + (tail ? 0 : wg) * 512;
#pragma unroll
        for (int u = 0; u < 16; u++) sts128(sp + (u * 128 + tid) * 16, PART(u));
        if (t == 0) {
          asm volatile("st.shared.v2.f32 [%0], {%1,%2};" :: "r"(sm + (warp * 16 + g) * 8), "f"(m0), "f"(l0) : "memory");
          asm volatile("st.shared.v2.f32 [%0], {%1,%2};" :: "r"(sm + (warp * 16 + g) * 8 + 64), "f"(m1), "f"(l1) : "memory");
        }
        __syncwarp();
        if (lane == 0) mbar_arrive(sb + B_EVP0 + 8 * wg);
        STAMP(st0 && last, wg, 7);
        if (last) break;
        mbar_wait(sb + B_QFULL + 8 * wg, qph); qph ^= 1;
        uint32_t u; asm volatile("ld.shared.u8 %0, [%1];" : "=r"(u) : "r"(sb + SM_UNSAFE + wg) : "memory");
        unsafe = __any_sync(0xffffffffu, u != 0);
        if (HOT && unsafe) { resume = 2; return; }
        }
      }

      if (P.w[cta_id()].role & R_FIN) {
        ROLE;
        if (!(tail && wg == 1)) {
        row_sums();
        const int rl = wg * 64 + warp * 16 + g;
        uint32_t a[64];
#pragma unroll
        for (int i = 0; i < 64; i++) a[i] = pack_bf16(o[2 * i] - (i & 1 ? l1 : l0), o[2 * i + 1] - (i & 1 ? l1 : l0));
        reg_fence(a);
        {
          float2 e0, e1;
          mbar_wait(sb + B_QFULL + 8 * wg, qph);
          asm volatile("ld.shared.v2.f32 {%0,%1}, [%2];" : "=f"(e0.x), "=f"(e0.y) : "r"(sb + SM_ML + rl * 8) : "memory");
          asm volatile("ld.shared.v2.f32 {%0,%1}, [%2];" : "=f"(e1.x), "=f"(e1.y) : "r"(sb + SM_ML + rl * 8 + 64) : "memory");
          STAMP(st0, wg, 7);
          uint32_t fb0 = 0x3f803f80u, fb1 = 0x3f803f80u;
          const float s0 = l0 + e0.y, s1 = l1 + e1.y;
          const bool odd = __any_sync(0xffffffffu, m0 != e0.x || m1 != e1.x || !(fmaxf(s0, s1) < 0x1p40f) || !(fminf(s0, s1) > 0x1p-40f));
          if (HOT && odd) { resume = 3; return; }
          uint4 v[16];
#pragma unroll
          for (int u = 0; u < 16; u++) v[u] = lds128(sQ + (u * 128 + tid) * 16);
          if (!HOT && odd) {
            const float x0 = fmaxf(m0, e0.x), x1 = fmaxf(m1, e1.x);
            const float d0 = fmaxf(m0 - x0, -1000.f), d1 = fmaxf(m1 - x1, -1000.f), f0 = fmaxf(e0.x - x0, -1000.f), f1 = fmaxf(e1.x - x1, -1000.f);
            l0 = l0 * ex2(d0) + e0.y * ex2(f0); l1 = l1 * ex2(d1) + e1.y * ex2(f1);
            const int E0 = fexp(l0), E1 = fexp(l1);
            const uint32_t fa0 = pow2_bf2((int)d0 - E0), fa1 = pow2_bf2((int)d1 - E1);
            fb0 = pow2_bf2((int)f0 - E0); fb1 = pow2_bf2((int)f1 - E1);
            l0 = __uint_as_float(__float_as_uint(l0) - (E0 << 23)); l1 = __uint_as_float(__float_as_uint(l1) - (E1 << 23));
#pragma unroll
            for (int i = 0; i < 32; i++) { a[2 * i] = hmul2(a[2 * i], fa0); a[2 * i + 1] = hmul2(a[2 * i + 1], fa1); }
          } else { l0 = s0; l1 = s1; }
#pragma unroll
          for (int u = 0; u < 16; u++) {
            a[4 * u] = hfma2(v[u].x, fb0, a[4 * u]); a[4 * u + 1] = hfma2(v[u].y, fb1, a[4 * u + 1]);
            a[4 * u + 2] = hfma2(v[u].z, fb0, a[4 * u + 2]); a[4 * u + 3] = hfma2(v[u].w, fb1, a[4 * u + 3]);
          }
        }
        float fs0, fs1;
        const float kl = __uint_as_float(__float_as_uint(KS / KC) + lds32(sb + SM_GE));
        asm("rcp.approx.ftz.f32 %0, %1;" : "=f"(fs0) : "f"(l0 * kl)); asm("rcp.approx.ftz.f32 %0, %1;" : "=f"(fs1) : "f"(l1 * kl));
        STAMP(st0, wg, 8);
        reg_fence(a);
        bar_sync(5 + wg, 256);
        uint64_t dW[4];
        float y0[64], y1[64];
        auto half0 = [&](auto u_) {
          constexpr int u = u_.value;
          if (u % 4 == 0) { mbar_wait(sb + B_WF + 2 * u, 1); wg_fence(); dW[u / 4] = desc_mn(sb, ((posw >> u) & 15) * 2048); }
          wgmma_rs_n128_tb<(u & 3) * 512>(y0, a[4 * u], a[4 * u + 1], a[4 * u + 2], a[4 * u + 3], dW[u / 4], u != 0);
        };
        auto half1 = [&](auto u_) {
          constexpr int u = u_.value;
          wgmma_rs_n128_tb<(u & 3) * 512 + 128>(y1, a[4 * u], a[4 * u + 1], a[4 * u + 2], a[4 * u + 3], dW[u / 4], u != 0);
        };
        const bool wr = W.q0 * 128 + wg * 64 + warp * 16 < NN;
        uint4* po = (uint4*)(P.out + (size_t)(W.q0 * 128 + rl) * 256) + t;
        auto emit = [&](const float* y, uint4* dst) {
          if (wr) {
            red_bf16x8(dst, make_uint4(pack_bf16(y[0] * fs0, y[1] * fs0), pack_bf16(y[4] * fs0, y[5] * fs0), pack_bf16(y[8] * fs0, y[9] * fs0), pack_bf16(y[12] * fs0, y[13] * fs0)));
            red_bf16x8(dst + 8 * 32, make_uint4(pack_bf16(y[2] * fs1, y[3] * fs1), pack_bf16(y[6] * fs1, y[7] * fs1), pack_bf16(y[10] * fs1, y[11] * fs1), pack_bf16(y[14] * fs1, y[15] * fs1)));
          }
          wg_fence();
        };
        static_for<0, 16>(half0);
        wg_commit();
        static_for<0, 4>(half1);
        wg_commit();
        wg_wait<1>();
        reg_fence(y0);
        emit(y0, po); static_for<4, 8>(half1);
        emit(y0 + 16, po + 4); static_for<8, 12>(half1);
        emit(y0 + 32, po + 8); static_for<12, 16>(half1);
        wg_commit();
        bar_arrive(6 - wg, 256);
        emit(y0 + 48, po + 12);
        wg_wait<0>();
        reg_fence(a); reg_fence(y1);
        STAMP(st0, wg, 9);
#pragma unroll
        for (int u = 0; u < 4; u++) emit(y1 + 16 * u, po + 16 + 4 * u);
        }
        if (!tail) { STAMP(st0, wg, 11); DUMP(st0, wg, 0, 16); asm volatile("exit;"); __builtin_unreachable(); }
        if (wg == 1) { bar_sync(6, 256); bar_arrive(5, 256); } else qph ^= 1;
        __syncwarp();
        if (lane == 0) mbar_arrive(sb + B_QEMPTY + 8 * wg);
        fill();
        resume = 4;
      }
        }
#pragma unroll 1
    for (int step = HOT || resume ? 0 : -4; step < (HOT && resume == 4 ? 0 : nloc); step++) {
      ROLE;
      const bool helper = HOT || (resume && resume < 4);
      const bool isw = !HOT && step < 0;
      if (isw) {
        const uint4* src = (const uint4*)(step < -2 ? P.wmsg : P.wv) + ((step & 1) * 128 + wg * 64 + warp) * 32 + lane;
        float cw[8] = {0.f, 0.f, 0.f, 0.f, 0.f, 0.f, 0.f, 0.f};
#pragma unroll 1
        for (int i = 0; i < 16; i++) cp_async16(sQ + sw_byte(i * 4 + warp, lane * 8), src + i * 128);
        cp_commit();
#pragma unroll
        for (int i = 0; i < 8; i++) {
          const uint4 v = __ldg((const uint4*)(step < -2 ? P.wmsg : P.wv) + (248 + i) * 32 + lane);
          const float k = step < -2 ? 0.f : (i == 7 ? -1.0f / 4.5f : -0.5f / 4.5f);
          cw[0] += bf_lo(v.x) * k; cw[1] += bf_hi(v.x) * k; cw[2] += bf_lo(v.y) * k; cw[3] += bf_hi(v.y) * k;
          cw[4] += bf_lo(v.z) * k; cw[5] += bf_hi(v.z) * k; cw[6] += bf_lo(v.w) * k; cw[7] += bf_hi(v.w) * k;
        }
        asm volatile("cp.async.wait_group 0;" ::: "memory");
#pragma unroll 1
        for (int i = 0; i < 16; i++) {
          const uint32_t ad = sQ + sw_byte(i * 4 + warp, lane * 8);
          const uint4 v = lds128(ad);
          uint4 w4 = make_uint4(pack_bf16(bf_lo(v.x) + cw[0], bf_hi(v.x) + cw[1]), pack_bf16(bf_lo(v.y) + cw[2], bf_hi(v.y) + cw[3]),
                                pack_bf16(bf_lo(v.z) + cw[4], bf_hi(v.z) + cw[5]), pack_bf16(bf_lo(v.w) + cw[6], bf_hi(v.w) + cw[7]));
          if (step == -1 && wg * 64 + i * 4 + warp == 127) w4 = make_uint4(0, 0, 0, 0);
          sts128(ad, w4);
        }
        fence_async_smem();
        bar_sync(7, 256);
      } else {
        SSTAMP(0);
        mbar_wait(sb + B_QFULL + 8 * wg, qph); qph ^= 1;
        STAMP(st0 && step == 0, wg, 8);
        SSTAMP(1);
        bar_sync(5 + wg, 256);
        SSTAMP(2);
      }
#pragma unroll 1
      for (int c = 0; c < 4; c++) {
        if (step == 0) mbar_wait(sb + B_WF + 8 * c, helper);
        const int turn2 = helper ? 3 : 4;
        if (c == turn2) bar_sync(5 + wg, 256);
        wg_fence();
        const uint64_t dA = desc_k(sb + SM_Q, wg * 2048 + c * 64), dW = desc_mn(sb, ((posw >> c * 4) & 15) * 2048);
        static_for<0, 4>([&](auto k) { wgmma_ss_n256_tb<k.value * 2, k.value * 512>(o, dA, dW, k.value > 0 ? 1 : c); });
        wg_commit();
        if ((c == 3 || c == turn2 - 1) && !isw) bar_arrive(6 - wg, 256);
        wg_wait<1>();
      }
      wg_wait<0>();
      reg_fence(o);
      {
        STAMP(st0 && step == 0, wg, 9);
        SSTAMP(3);
        if (isw) bar_sync(1 + wg, 128); else if (lane == 0) mbar_arrive(sb + B_QEMPTY + 8 * wg);
        uint8_t* dw = (uint8_t*)(step < -2 ? g_Wmo : g_Wvo) + ((step & 1) * 2 + wg) * 32768 + warp * 8192 + g * 128;
        const int row0 = (W.loc0 + step) * 128 + wg * 64 + warp * 16;
        uint4 r[16];
#pragma unroll
        for (int u = 0; u < 8; u++) { r[2 * u] = ROW0(u); r[2 * u + 1] = ROW1(u); }
        if (isw) {
#pragma unroll
          for (int u = 0; u < 16; u++) *(uint4*)(dw + (u >> 2) * 1024 + ((((u & 2) * 2 + t) ^ g) << 4) + (u & 1) * 4096) = r[u];
        } else if (row0 < NN) {
          uint4* po = (uint4*)(P.out + (size_t)(row0 + g) * 256) + t;
          uint32_t c1 = clk();
#pragma unroll
          for (int u = 0; u < 16; u++) {
            red_bf16x8(po + (u >> 1) * 4 + (u & 1) * 256, r[u]);
            if (!HOT) { c1 += PACE; while ((int)(clk() - c1) < 0) {} }
          }
        }
        if (!HOT && step == -1) { bar_sync(7, 256); if (tid_is(0)) flag_release(F_W); __syncwarp(); STAMP(st0, wg, 3); }
      }
    }
    if (HOT && resume == 4) return;
    finish();
    };
    if (total == 0) {
      start();
      asm volatile("setmaxnreg.inc.sync.aligned.u32 %0;" :: "n"(CREG));
      fill();
    } else {
      layernorm();
      run(std::true_type{});
    }
    run(std::false_type{});
    asm volatile("setmaxnreg.dec.sync.aligned.u32 %0;" :: "n"(504 - 2 * CREG));
  } else {
    STAMP(lane == 0 && warp == 0, 2, 0);
        const int mi = cta >> 3;
    const uint32_t sW = sb + 3 * 32768;
    uint4 wa[4], wb[8];
    {
      const uint4* pq = (const uint4*)(P.wq + ((mi & 15) * 16 + g) * 256) + warp * 8 + t;
      const uint4* pk = (const uint4*)(P.wk + ((cta & 7) * 32 + g) * 256) + warp * 8 + t;
#pragma unroll
      for (int i = 0; i < 4; i++) wa[i] = __ldg(pq + (i >> 1) * 256 + (i & 1) * 4);
#pragma unroll
      for (int i = 0; i < 8; i++) wb[i] = __ldg(pk + (i >> 1) * 256 + (i & 1) * 4);
    }
    if (threadIdx.x == 352) {
      for (int i = 0; i < 3; i++) { mbar_init(sb + B_FULL + 8 * i, 1); mbar_init(sb + B_EMPTY + 8 * i, cta == 130 ? 4 : 8); }
      for (int i = 0; i < 4; i++) mbar_init(sb + B_WF + 8 * i, 1);
      for (int i = 0; i < 2; i++) { mbar_init(sb + B_QFULL + 8 * i, 1); mbar_init(sb + B_QEMPTY + 8 * i, 4); mbar_init(sb + B_EVP0 + 8 * i, 4); }
      mbar_init(sb + B_EVH, 8); mbar_init(sb + B_EVQ, 8); mbar_init(sb + B_HALF, 8); mbar_init(sb + B_BG, 1); mbar_init(sb + B_M0, 1); mbar_init(sb + B_HRD, 1);
      asm volatile("fence.mbarrier_init.release.cluster;" ::: "memory");
    }
    __syncwarp();
    do bar_sync(4, 384); while (P.zero);
    {
#pragma unroll
      for (int n = 0; n < 4; n++) {
        float c[4] = {0.f, 0.f, 0.f, 0.f};
#pragma unroll
        for (int u = 0; u < 2; u++) {
          mma16816(c, wa[u].x, wa[2 + u].x, wa[u].y, wa[2 + u].y, wb[2 * n + u].x, wb[2 * n + u].y);
          mma16816(c, wa[u].z, wa[2 + u].z, wa[u].w, wa[2 + u].w, wb[2 * n + u].z, wb[2 * n + u].w);
        }
        asm volatile("st.shared.v2.f32 [%0], {%1,%2};" :: "r"(sW + ((warp * 16 + g) * 40 + n * 8 + 2 * t) * 4), "f"(c[0]), "f"(c[1]) : "memory");
        asm volatile("st.shared.v2.f32 [%0], {%1,%2};" :: "r"(sW + ((warp * 16 + g + 8) * 40 + n * 8 + 2 * t) * 4), "f"(c[2]), "f"(c[3]) : "memory");
      }
      STAMP(lane == 0 && warp == 0, 2, 7);
      bar_sync(3, 128);
      if (warp < 2) {
        float c[8] = {0.f, 0.f, 0.f, 0.f, 0.f, 0.f, 0.f, 0.f};
#pragma unroll
        for (int k = 0; k < 4; k++) {
          const uint4 v = lds128(sW + ((k * 16 + warp * 8 + g) * 40 + t * 8) * 4), w = lds128(sW + ((k * 16 + warp * 8 + g) * 40 + t * 8 + 4) * 4);
          c[0] += __uint_as_float(v.x); c[1] += __uint_as_float(v.y); c[2] += __uint_as_float(v.z); c[3] += __uint_as_float(v.w);
          c[4] += __uint_as_float(w.x); c[5] += __uint_as_float(w.y); c[6] += __uint_as_float(w.z); c[7] += __uint_as_float(w.w);
        }
        const float ms = 1.4426950408889634f / 16.0f / KS;
        const uint4 m4 = make_uint4(pack_bf16(c[0] * ms, c[1] * ms), pack_bf16(c[2] * ms, c[3] * ms), pack_bf16(c[4] * ms, c[5] * ms), pack_bf16(c[6] * ms, c[7] * ms));
        sts128(sW + 16384 + (warp * 8 + g) * 64 + ((t ^ (g >> 1)) << 4), m4);
      }
    }
    asm volatile("setmaxnreg.dec.sync.aligned.u32 %0;" :: "n"(504 - 2 * CREG));
    STAMP(lane == 0 && warp == 0, 2, 13);
    bar_sync(3, 128);
#define ep1 (lds32(sb + SM_EPOCH) + 1)
    if (threadIdx.x == 256 && cta < 128) {
      fence_async_smem();
      bulk_s2g(g_M + cta * 64, sW + 16384, 1024);
      bulk_commit();
      bulk_wait_all();
      red_relaxed(g_flag + F_M + (cta >> 5));
    }
    if (warp == 2 && cta < 131) {
      uint2 f;
#pragma unroll 1
      for (uint32_t it = 0; it < (1u << 23); it++) {
        __nanosleep(150);
        asm volatile("ld.relaxed.gpu.global.v2.u32 {%0,%1}, [%2];" : "=r"(f.x), "=r"(f.y) : "l"(g_flag + F_EPOCH) : "memory");
        if (__all_sync(0xffffffffu, f.y >> 4 == ((f.x + 1) & 0xfffffff))) break;
      }
      asm volatile("st.shared.u32 [%0], %1;" :: "r"(sb + SM_GE), "r"((f.y & 15) << 23) : "memory");
      bar_arrive(8, 160); bar_arrive(9, 160);
    }
    __syncwarp();
    ROLE;
    if (warp == 3 && W.own) {
      mbar_wait_w(sb + B_EVH, 0);
      if (W.role < R_SIG) mbar_wait_w(sb + B_WF + 8, 0);
      if (lane == 0) {
        fence_async_smem();
        const int h0 = W.own == 2, nh = W.own == 3 ? 2 : 1;
        bulk_s2g(g_h + W.hp * 4096 + h0 * 2048, sb + SM_Q + h0 * 32768, nh * 32768);
        bulk_s2g(g_stat + W.q0 * 128 + h0 * 64, sb + SM_ML + h0 * 512, nh * 512);
        bulk_commit();
        bulk_wait_read();
        mbar_arrive(sb + B_HRD);
        bulk_wait_all();
        if (W.role >= R_SIG) red_relaxed(g_flag + F_H1 - 1 + W.role / R_SIG);
        red_relaxed(g_flag + F_H);
      }
      __syncwarp();
      STAMP(lane == 0, 2, 6);
    }
    if (warp == 0) {
      if (lane == 0) {
        STAMP(true, 2, 1);
        const uint32_t epoch = ld_relaxed(g_flag + F_EPOCH);
        if (total > 0) {
#pragma unroll
          for (int c = 0; c < 3; c++) mbar_expect_tx(sb + B_WF + 8 * c, c == 0 ? WCH_B - 8192 : WCH_B);
          mbar_expect_tx(sb + B_M0, 8192);
          int c = 0;
#pragma unroll 1
          for (uint32_t it = 0; c < 4; it++) {
            uint4 f;
            asm volatile("ld.relaxed.gpu.global.v4.u32 {%0,%1,%2,%3}, [%4];" : "=r"(f.x), "=r"(f.y), "=r"(f.z), "=r"(f.w) : "l"(g_flag + F_M) : "memory");
            uint32_t tm;
            asm volatile("mad.lo.u32 %0, %1, 32, 32;" : "=r"(tm) : "r"(epoch));
            int ok = (int)(f.x - tm) < 0 ? 0 : (int)(f.y - tm) < 0 ? 1 : (int)(f.z - tm) < 0 ? 2 : (int)(f.w - tm) < 0 ? 3 : 4;
            if (it > (1u << 23)) ok = 4;
            if (ok > c) {
              asm volatile("fence.acquire.gpu;" ::: "memory"); fence_async_gmem();
              if (c == 0) bulk_g2s(sb + (POS_M & 15) * 32768, g_M, 8192, sb + B_M0);
            }
#pragma unroll 1
            for (; c < ok; c++) {
              const uint32_t skip = c == 0 ? 8192 : 0;
              bulk_g2s(sb + ((POS_M >> c * 4) & 15) * 32768 + skip, pofs<const uint8_t>(g_M, c * WCH_B + skip), WCH_B - skip, sb + B_WF + 8 * c);
              STAMP(c == 0, 2, 2);
            }
          }
        }
        asm volatile("st.shared.u32 [%0], %1;" :: "r"(sb + SM_EPOCH), "r"(epoch) : "memory");
        if (total > 0) mbar_expect_tx(sb + B_WF + 24, WCH_B);
        int st = 0, ph = 0, qph = 0;
        const int nsl = tail ? 3 : 2;
        auto next_slot = [&]() { mbar_wait(sb + B_EMPTY + 8 * st, ph); if (++st == nsl) { st = 0; ph ^= 1; } };
        const uint4* wsrc = fin ? g_Wvo : g_Wmo;
        auto w_load = [&](int c0, int c1) {
#pragma unroll 1
          for (int c = c0; c < c1; c++) {
            mbar_expect_tx(sb + B_WF + 8 * c, WCH_B);
            bulk_g2s(sb + ((posw >> c * 4) & 15) * 32768, pofs<const uint8_t>(wsrc, c * WCH_B), WCH_B, sb + B_WF + 8 * c);
          }
        };
        auto q_load = [&](const uint4* src, bool wait_empty) {
#pragma unroll 1
          for (int h = 0; h < 2; h++) {
            if (wait_empty) mbar_wait(sb + B_QEMPTY + 8 * h, qph);
            mbar_expect_tx(sb + B_QFULL + 8 * h, 32768);
            bulk_g2s_last(sb + SM_Q + h * 32768, src + h * 2048, 32768, sb + B_QFULL + 8 * h);
          }
          if (wait_empty) qph ^= 1;
        };
        auto part_out = [&](int slot, int h, uint32_t region, int parity) {
          mbar_wait(sb + B_EVP0 + 8 * h, parity);
          fence_async_smem();
          bulk_s2g(g_part + slot * 4096 + h * 2048, sb + region * 32768, 32768);
          bulk_s2g(g_ml + slot * 128 + h * 64, sb + SM_ML + h * 512, 512);
          bulk_commit();
        };
        auto announce = [&](int f) {
          red_relaxed(g_flag + f);
        };
        if (total > 0) {
          STAMP(true, 2, 3);
          const int q1 = W.q0 + 2 * W.own - 3;
          if (!tail) { flag_wait(F_H1 + (fin ? 0 : W.own), (epoch + 1) * (fin ? NH1_0 : (W.own == 1 ? NH1_1 : NH1_2))); fence_async_gmem(); }
          STAMP(true, 2, 4);
          uint32_t ko = W.k0 * 8192;
#pragma unroll 1
          for (int j = 0; j < total; j++) {
            if (j == (tail ? 0 : 1)) { flag_wait(F_H, (epoch + 1) * NHSIG); fence_async_gmem(); }
            if (j == n0) {
              flag_wait(F_QP + q1 * LN_, (epoch + 1)); fence_async_gmem();
              const uint32_t u = __ldcg(g_unsafe + q1);
              asm volatile("st.shared.u32 [%0], %1;" :: "r"(sb + SM_UNSAFE), "r"(u) : "memory");
              ko = W.k1 * 8192;
            }
            if (j == n0 + 1) q_load(g_qp + q1 * 4096, true);
            if (j == total - 1) { flag_wait(F_W, (epoch + 1)); fence_async_gmem(); if (!tail) w_load(0, 1); }
            const uint32_t bytes = (j < n0 ? j < W.nb0 : j - n0 < W.nb1) ? 112 * 512 : 128 * 512, s0 = st;
            const uint32_t region = (tail ? 1 : 2) + 2 * s0, skip = j == n0 + 1 ? 32768 : 0;
            if (skip) part_out(W.slotA, 0, 6, 0);
            next_slot();
            mbar_expect_tx(sb + B_FULL + 8 * s0, bytes);
            bulk_g2s(sb + region * 32768 + skip, pofs<const uint8_t>(g_h, ko + skip), bytes - skip, sb + B_FULL + 8 * s0);
            if (skip) {
              part_out(W.slotA, 1, region, 0);
              bulk_wait_read();
              bulk_g2s(sb + region * 32768, pofs<const uint8_t>(g_h, ko), skip, sb + B_FULL + 8 * s0);
              bulk_wait_all();
              announce(F_PART + W.slotA * LN_);
            }
            ko += bytes;
          }
          next_slot();
          if (tail) { next_slot(); next_slot(); }
        } else { flag_wait(F_W, (epoch + 1)); fence_async_gmem(); }
        STAMP(true, 2, 5);
        const bool staged = total > 0 && !tail;
        w_load(staged, staged ? (fin ? 2 : 3) : 4);
        if (tail) {
          mbar_wait(sb + B_BG, 0); mbar_wait(sb + B_EVP0 + 8, 0); mbar_arrive(sb + B_QFULL);
          qph = 1; wsrc = g_Wmo;
          mbar_wait(sb + B_QEMPTY, 1);
          w_load(0, 4);
        }
#pragma unroll 1
        for (int i = 0; i < W.nloc; i++) {
          const int tl = W.loc0 + i, last = tl * 128 + 127 < NN ? tl * 128 + 127 : NN - 1;
          flag_wait(F_AGG + ((last >= NGW) + (last >= 4 * NGW) + (last >= 9 * NGW)) * LN_, (epoch + 1) * NGW); fence_async_gmem();
          if (total == 0) g_flag[F_EPOCH] = epoch + 1;
          q_load(g_agg + tl * 4096, total > 0 || i > 0);
        }
        if (fin && !tail) {
          int h = 0, c = 2, have = W.slotB >= 0 ? 2 : 0;
          mbar_wait(sb + B_BG, 0);
#pragma unroll 1
          for (uint32_t it = 0; (h < 2 || c < 4) && it < (1u << 23); it++) {
            if (have < 2) {
              uint2 f;
              asm volatile("ld.relaxed.gpu.global.v2.u32 {%0,%1}, [%2];" : "=r"(f.x), "=r"(f.y) : "l"(g_flag + F_PART + W.slotA * LN_) : "memory");
              have = (int)(f.x - (epoch + 1)) < 0 ? 0 : ((int)(f.y - (epoch + 1)) < 0 ? 1 : 2);
            }
            if (h < have && mbar_try_wait_nb(sb + B_QEMPTY + 8 * h, 0)) {
              asm volatile("fence.acquire.gpu;" ::: "memory"); fence_async_gmem();
              STAMP(true, 2, 14 + h);
              mbar_expect_tx(sb + B_QFULL + 8 * h, 32768 + 512);
              bulk_g2s(sb + SM_ML + h * 512, g_ml + W.slotA * 128 + h * 64, 512, sb + B_QFULL + 8 * h);
              bulk_g2s(sb + SM_Q + h * 32768, g_part + W.slotA * 4096 + h * 2048, 32768, sb + B_QFULL + 8 * h);
              h++;
            }
            const bool half = mbar_try_wait_nb(sb + B_HALF, 0);
            const int c1 = half ? 4 : (h > 0 ? 3 : 2);
            if (c < c1) { w_load(c, c1); c = c1; }
          }
        } else if (!fin && total > 0) {
#pragma unroll 1
          for (int h = 0; h < 2; h++) part_out(W.slotB, h, (posw >> 12) + h, 1);
          asm volatile("cp.async.bulk.wait_group.read 1;" ::: "memory");
          w_load(3, 4);
          asm volatile("cp.async.bulk.wait_group 1;" ::: "memory");
          announce(F_PART + W.slotB * LN_);
          STAMP(true, 2, 14);
          bulk_wait_all();
          announce(F_PART + W.slotB * LN_ + 1);
          STAMP(true, 2, 15);
        }
        DUMP(true, 2, 14, 16);
        DUMP(true, 2, 0, 8);
      }
      return;
    }
  }
    {
      const int gw = cta * 3 + warp - 1;
      ROLE;
      if (total > 0) {
        mbar_wait_w(sb + B_EVQ, 0);
        const uint32_t c0 = clk();
        if (warp == 3 && W.own) {
          const uint4 s0 = lds128(sb + SM_ML + (W.own == 2) * 512 + lane * 16), s1 = lds128(sb + SM_ML + (W.own >> 1) * 512 + lane * 16);
          const float rm = __uint_as_float(min(min(s0.x - 1, s0.z - 1), min(s1.x - 1, s1.z - 1)) + 1);
          const uint32_t ex = __reduce_max_sync(0xffffffffu, __float_as_uint(rm > 0.f ? fmaf(-1e-5f * rm, rm, 1.000001f) : 0.f) >> 24);
          if (lane == 0) asm volatile("red.relaxed.gpu.global.max.u32 [%0], %1;" :: "l"(g_flag + F_RHO), "r"(ep1 * 64 + ex) : "memory");
          flag_release_w(F_RC);
        }
        if (warp == 1 && (W.role & R_PUB)) {
          g_unsafe[W.q0] = lds32(sb + SM_UNSAFE);
#pragma unroll 1
          for (int k = 0; k < 4; k++) {
            __nanosleep(1000);
            if (lane == 0) bulk_s2g(pofs<uint4>(g_qp, W.q0 * 65536 + k * 16384), sb + SM_Q + k * 16384, 16384);
            bulk_commit();
          }
          bulk_wait_all();
          flag_release_w(F_QP + W.q0 * LN_);
        }
        while (__any_sync(0xffffffffu, clk() - c0 < GSTART)) __nanosleep(500);
        STAMP(lane == 0 && warp == 1, 2, 8);
#define ovf_cnt pofs<uint32_t>(g_flag, (F_OVF + (ep1 & 1) * LN_) * 4)
        if (gw == 0) g_flag[F_OVF + ((ep1 + 1) & 1) * LN_] = 0;
#pragma unroll 1
        for (int e0 = gw * 32; e0 < NE; e0 += NGW * 32 * 7) {
          int d[7], s[7], pos[7];
          const int* pd = pofs<const int>(P.dst, (e0 + lane) * 4);
          const int* ps = pofs<const int>(P.src, (e0 + lane) * 4);
#pragma unroll
          for (int k = 0; k < 7; k++) { const bool ok = e0 + k * NGW * 32 < NE; d[k] = ok ? __ldcs(pd + k * NGW * 32) : -1; s[k] = ok ? __ldcs(ps + k * NGW * 32) : 0; }
          uint32_t ov = 0;
#pragma unroll
          for (int k = 0; k < 7; k++) {
            pos[k] = 0;
            if (d[k] >= 0) asm volatile("atom.relaxed.gpu.global.add.u32 %0, [%1], 1;" : "=r"(pos[k]) : "l"(pofs<int>(g_cnt, d[k] << 2)) : "memory");
            s[k] = (uint32_t)(uintptr_t)g_u + s[k] * 512;
            if (d[k] >= 0 && pos[k] < CAP) asm volatile("st.volatile.global.u32 [%0], %1;" :: "l"(pofs<int>(g_bin, (d[k] * CAPS + pos[k]) << 2)), "r"(s[k]) : "memory");
            ov |= (pos[k] >= CAP) << k;
          }
          if (__any_sync(0xffffffffu, ov != 0)) {
            uint32_t at;
            asm volatile("atom.relaxed.gpu.global.add.u32 %0, [%1], %2;" : "=r"(at) : "l"(ovf_cnt), "r"(__popc(ov)) : "memory");
#pragma unroll
            for (int k = 0; k < 7; k++) if ((ov >> k) & 1) g_ovf[at++] = make_int2(d[k], s[k]);
          }
        }
        flag_wait_w(F_RC, ep1 * NHSIG);
        const uint32_t ush = max(62 - (int)(__shfl_sync(0xffffffffu, ld_relaxed(g_flag + F_RHO), 0) & 63), 0) << 23;
        const float us = __uint_as_float(__float_as_uint(US) + ush);
#pragma unroll 1
        for (int n0 = gw; n0 < NN; n0 += 4 * NGW) {
          uint4 xv[4]; float2 st[4];
#pragma unroll
          for (int k = 0; k < 4; k++) {
            const int n = n0 + k * NGW < NN ? n0 + k * NGW : n0;
            xv[k] = ldcs_v(pofs<const uint4>(P.x, n * 512 + lane * 16));
            st[k] = __ldcg(pofs<const float2>(g_stat, n * 8));
          }
#pragma unroll
          for (int k = 3; k >= 0; k--) {
            const int n = n0 + k * NGW;
            const float a = st[k].x * us, c = fmaf(st[k].y, us, UB + 8388608.0f);
#define FIX(w) __byte_perm(__float_as_uint(fmaf(bf_lo(w), a, c)), __float_as_uint(fmaf(bf_hi(w), a, c)), 0x5410)
            if (n < NN) {
              *pofs<uint4>(P.out, n * 512 + lane * 16) = xv[k];
              *pofs<uint4>(g_u, n * 512 + lane * 16) = make_uint4(FIX(xv[k].x), FIX(xv[k].y), FIX(xv[k].z), FIX(xv[k].w));
            }
          }
        }
        flag_release_w(F_BIN);
        STAMP(lane == 0 && warp == 1, 2, 9);
        flag_wait_w(F_BIN, ep1 * NGW);
        STAMP(lane == 0 && warp == 1, 2, 10);
        const int myn = gw + lane * NGW < NN ? gw + lane * NGW : gw;
        int cnts = __ldcg(g_cnt + myn);
        cnts = gw + lane * NGW < NN ? (cnts > CAP ? CAP + 1 : cnts) | ((int)__ldg((const unsigned short*)P.dinv + myn) << 16) : 0;
        __syncwarp();
        g_cnt[myn] = 0;
        const uint32_t uhi = (uintptr_t)g_u >> 32, lx = lane * 16;
        uint32_t obin = gw * CAPS * 4;
        auto bin = [&](uint32_t ofs, int r, int first) {
          uint32_t en;
          asm volatile("{\n.reg .pred p;\nsetp.lt.u32 p, %2, %3;\nmov.u32 %0, 0;\n@p ld.global.cg.u32 %0, [%1];\n}\n"
                       : "=&r"(en) : "l"(pofs<const uint32_t>(g_bin, ofs + first * 4 + lx / 4)), "r"(lx + first * 16), "r"((__shfl_sync(0xffffffffu, cnts, r) & 0xffff) * 16) : "memory");
          return en;
        };
        uint32_t ent = bin(obin, 0, 0), entn = bin(obin + NGW * CAPS * 4, 1, 0);
        int cd = __shfl_sync(0xffffffffu, cnts, 0), cb = min(cd & 0xffff, CAP), e = 0;
        uint32_t sa[4] = {0, 0, 0, 0}, sh[4] = {0, 0, 0, 0};
        auto add = [&](uint32_t x, uint32_t y, uint32_t z, uint32_t w) {
          sa[0] += x; sa[1] += y; sa[2] += z; sa[3] += w;
          sh[0] += x >> 16; sh[1] += y >> 16; sh[2] += z >> 16; sh[3] += w >> 16;
        };
        int rnd = -1, rows = -1, cdo = 0;
#pragma unroll 1
        for (;;) {
          const bool hold = rows >= 0 && rnd == 8;
          const int m = hold ? 0 : cb - e;
          uint4 v[8];
          if (m >= 8) {
#pragma unroll
            for (int k = 0; k < 8; k++) v[k] = ldcg_v(addr64(__shfl_sync(0xffffffffu, ent, k) + lx, uhi));
          } else {
#pragma unroll
            for (int k = 0; k < 8; k++) {
              v[k] = make_uint4(0, 0, 0, 0);
              if (k < 7) ldcg_if(v[k], addr64(__shfl_sync(0xffffffffu, ent, k) + lx, uhi), k < m);
            }
          }
          if (rows >= 0) {
            const int n = gw + rnd * NGW;
            if (n < NN) {
              const float di = __uint_as_float(cdo & 0xffff0000u) * __uint_as_float(__float_as_uint(1.0f / US) - ush), nl = -di * UB * (float)rows;
#define AGG(k) pack_bf16(fmaf((float)(sa[k] - (sh[k] << 16)), di, nl), fmaf((float)sh[k], di, nl))
              *pofs<uint4>(g_agg, ((n >> 3) * 4096 + (n & 7) * 144) ^ ((lx & 0x70) | ((lx & 0x180) << 3))) = make_uint4(AGG(0), AGG(1), AGG(2), AGG(3));
            }
#pragma unroll
            for (int k = 0; k < 4; k++) sa[k] = sh[k] = 0;
            rows = -1;
            if (rnd == 0 || rnd == 3 || rnd == 8 || rnd == NRND - 1) flag_release_w(F_AGG + ((rnd > 0) + (rnd > 3) + (rnd > 8)) * LN_);
            if (rnd == NRND - 1) break;
            if (hold) {
              if (fin && W.slotB >= 0) {
#pragma unroll 1
                for (int k = 0; k < 2; k++) flag_wait_w(F_PART + (k ? W.slotB : W.slotA) * LN_, ep1);
#pragma unroll 1
                for (int b = warp - 1; b < 8; b += 3) {
                  float2* ma = g_ml + W.slotA * 128 + b * 16 + g;
                  const float2* mb = g_ml + W.slotB * 128 + b * 16 + g;
                  const float2 a0 = __ldcg(ma), a1 = __ldcg(ma + 8), b0 = __ldcg(mb), b1 = __ldcg(mb + 8);
                  const float x0 = fmaxf(a0.x, b0.x), x1 = fmaxf(a1.x, b1.x);
                  const float fa0 = ex2(a0.x - x0), fa1 = ex2(a1.x - x1), fb0 = ex2(b0.x - x0), fb1 = ex2(b1.x - x1);
                  __syncwarp();
                  if (t == 0) { ma[0] = make_float2(x0, a0.y * fa0 + b0.y * fb0); ma[8] = make_float2(x1, a1.y * fa1 + b1.y * fb1); }
                  const uint32_t ofs = ((b >> 2) * 2048 + (b & 3) * 32 + lane) * 16;
#pragma unroll 1
                  for (int u = 0; u < 16; u += 4) {
                    uint4* pa = pofs<uint4>(g_part, W.slotA * 65536 + ofs + u * 2048);
                    const uint4* pb = pofs<const uint4>(g_part, W.slotB * 65536 + ofs + u * 2048);
                    uint4 va[4], vb[4];
#pragma unroll
                    for (int k = 0; k < 4; k++) { va[k] = ldcg_v(pa + k * 128); vb[k] = ldcs_v(pb + k * 128); }
#define FOLD(w, fa, fb) pack_bf16(bf_lo(va[k].w) * fa + bf_lo(vb[k].w) * fb, bf_hi(va[k].w) * fa + bf_hi(vb[k].w) * fb)
#pragma unroll
                    for (int k = 3; k >= 0; k--) pa[k * 128] = make_uint4(FOLD(x, fa0, fb0), FOLD(y, fa1, fb1), FOLD(z, fa0, fb0), FOLD(w, fa1, fb1));
                  }
                }
                bar_sync(3, 96);
                if (warp == 1) asm volatile("fence.acq_rel.gpu;" ::: "memory");
              }
              if (fin && warp == 1 && lane == 0) mbar_arrive(sb + B_BG);
              while (__any_sync(0xffffffffu, clk() - c0 < GPAUSE)) __nanosleep(500);
              continue;
            }
          }
#define SUM8(f) (v[7].f + v[6].f + v[5].f + v[4].f + v[3].f + v[2].f + v[1].f + v[0].f)
          add(SUM8(x), SUM8(y), SUM8(z), SUM8(w));
          e += 8;
          if (e < cb) {
            ent = __shfl_down_sync(0xffffffffu, ent, 8);
            if (e == 32) ent = bin(obin, rnd + 1, 32);
            continue;
          }
          rnd++; rows = cb; cdo = cd;
          if ((cd & 0xffff) > CAP) {
            const int no = __shfl_sync(0xffffffffu, (int)ld_relaxed(ovf_cnt), 0);
#pragma unroll 1
            for (int i0 = 0; i0 < no; i0 += 32) {
              int2 en = __ldcg(g_ovf + min(i0 + lane, no - 1));
              uint32_t mk = __ballot_sync(0xffffffffu, en.x == gw + rnd * NGW && i0 + lane < no);
              rows += __popc(mk);
#pragma unroll 1
              while (mk) {
                const int bit = __ffs(mk) - 1; mk &= mk - 1;
                const uint4 r = ldcg_v(addr64((uint32_t)__shfl_sync(0xffffffffu, en.y, bit) + lx, uhi));
                add(r.x, r.y, r.z, r.w);
              }
            }
          }
          obin += NGW * CAPS * 4;
          ent = entn; entn = bin(obin + NGW * CAPS * 4, rnd + 2, 0);
          cd = __shfl_sync(0xffffffffu, cnts, rnd + 1); cb = min(cd & 0xffff, CAP); e = 0;
        }
      }
      STAMP(lane == 0 && warp == 1, 2, 11);
      if (warp == 2 && fin && lane == 0) prefetch_l2(pofs<uint8_t>(P.out, W.q0 * 65536), tail ? 8192 : 65536);
      DUMP(warp == 1 && lane == 0, 2, 8, 14);
    }
}

}

extern "C" void kernel_launch(void* const* d_in, const int* in_sizes, int n_in, void* d_out, int out_size) {
  Params P;
  P.x = (const __nv_bfloat16*)d_in[0];
  P.src = (const int*)d_in[1];
  P.dst = (const int*)d_in[2];
  P.dinv = (const __nv_bfloat16*)d_in[3];
  P.wmsg = (const __nv_bfloat16*)d_in[4];
  P.wq = (const __nv_bfloat16*)d_in[5];
  P.wk = (const __nv_bfloat16*)d_in[6];
  P.wv = (const __nv_bfloat16*)d_in[7];
  P.wout = (const __nv_bfloat16*)d_in[8];
  P.out = (__nv_bfloat16*)d_out;
  P.zero = 0;
  for (int c = 0; c < NCTA; c++) P.w[c] = make_work(c);
  static void* scr = nullptr;
  if (!scr) {
    cudaFuncSetAttribute(gps_kernel, cudaFuncAttributeMaxDynamicSharedMemorySize, SMEM_BYTES);
    cudaGetSymbolAddress(&scr, g_scr);
  }
  P.s = (Scratch*)((((uintptr_t)scr + SCR_ALIGN - 1) & ~(uintptr_t)(SCR_ALIGN - 1)) + SCR_OFS);
  P.u = (uint4*)(((uintptr_t)P.s->u + 511) & ~(uintptr_t)511);
  if (((uintptr_t)P.u >> 32) != (((uintptr_t)(P.u + NN * 32) - 1) >> 32)) P.u += NN * 32;
  gps_kernel<<<NCTA, 384, SMEM_BYTES>>>(P);
}
```

```cpp
#include <cuda_runtime.h>
#include <cuda_bf16.h>
#include <stdint.h>
#include <stddef.h>
#include <type_traits>
#define FB 5
#define MB 5
#define GSTART 40000
#define XD 3
#define NTAIL 5
#define ALN 1200
#define PACE 64
#define GPAUSE 112000
#define CREG 224
#define BACKOFF 1000

namespace {

constexpr int NN = 10000;
constexpr int NE = 160000;
constexpr int NQT = 79;
constexpr int NCTA = 132;
constexpr int CAP = 64;
constexpr int CAPS = 64;
constexpr int NHSIG = 105;
constexpr uint32_t WCH_B = 32768;
constexpr int NGW = (NCTA - 1) * 3;
constexpr float TAU = 16.0f;
constexpr float SAFE_N2 = 31.0f, SAFE_C = 0.6f;
#define KOFF 3
#define PSH -8.0f
constexpr float US = 256.0f, UB = 4095.0f;
constexpr float KS = 0.25f, KC = KOFF * KS;
constexpr uint32_t KC2 = KOFF == 2 ? 0x3f003f00u : (KOFF == 1 ? 0x3e803e80u : 0x3f403f40u);

constexpr int NAGG = 4;
constexpr int NRND = (NN + NGW - 1) / NGW;
constexpr int NSLOT = 105;
constexpr int F_EPOCH = 0, F_GE = 1, F_H = 2, F_M = 4  , F_H1 = 8  , F_RHO = 11, F_RC = 12, LN_ = 32;
constexpr int F_BIN = LN_, F_W = 2 * LN_, F_OVF = 3 * LN_  , F_QP = 5 * LN_, F_AGG = F_QP + NQT * LN_,
              F_PART = F_AGG + NAGG * LN_, F_TM = F_PART + NSLOT * LN_, F_END = F_TM + LN_;

struct Scratch {
  uint32_t flag[F_END];
  alignas(4096) uint4 M[8192];
  uint4 Wvo[8192], Wmo[8192];
  float2 ml[NSLOT * 128];
  uint32_t unsafe[96];
  int cnt[NN + 32];
  float2 stat[NQT * 128];
  alignas(4096) uint4 h[NQT * 4096];
  uint4 u[2 * NN * 32 + 32];
  uint4 qp[NQT * 4096];
  uint4 agg[NQT * 4096];
  uint4 part[NSLOT * 4096];
  int bin[NN * CAPS];
  int2 ovf[NE];
};
static_assert(offsetof(Scratch, h) % 128 == 0, "alignment");
#define SCR_ALIGN (2u << 20)
#define SCR_OFS 0
__device__ uint4 g_scr[(sizeof(Scratch) + SCR_ALIGN + SCR_OFS) / 16];
struct alignas(16) Work { short k0, k1; signed char q0, hp, nb0, na0, nb1, na1, slotA, slotB, loc0, nloc, own, role; };
constexpr int R_FIN = 1, R_PUB = 2, R_TAIL = 4, R_SIG = 8  ;
struct Params {
  const __nv_bfloat16 *x, *wq, *wk;
  Scratch* s;
  uint4* u;
  __nv_bfloat16* out;
  const __nv_bfloat16 *wout, *wmsg, *wv, *dinv;
  const int *src, *dst;
  long long zero;
  Work w[NCTA];
};
constexpr int first_cnt(int k) { return 2 * ((k + 6) / 8 - k / 8 + 1); }
constexpr int NH1_0 = 2, NH1_1 = first_cnt(48 * 8 - MB), NH1_2 = first_cnt(48 * 8 - MB + 16 * 8 - (15 - MB) / 2);
constexpr int NSERV = NQT - 52;
inline Work make_work(int c) {
  Work w;
  const int gi = c / 5, r = c % 5, q = gi * 3;
  const bool helper = r & 1, mid = r == 2;
  w.q0 = helper ? q + 1 : q + (r >> 1);
  const int hb1 = (15 - MB) / 2, hb3 = 15 - MB - hb1;
  w.nb0 = helper ? (r == 1 ? hb1 : hb3) : (mid ? MB : FB);
  w.na0 = (helper ? 16 : 48) - w.nb0;
  w.k0 = helper ? (48 * 8 - MB) + (r >> 1) * (16 * 8 - hb1) : 0;
  w.k1 = 48 * 8 - FB;
  w.nb1 = helper ? (FB < 7 ? 7 : 15) - FB : 0;
  w.na1 = helper ? (FB < 7 ? 31 : 32) - w.nb1 : 0;
  w.slotA = 4 * gi + (helper ? r - 1 : (mid ? 0 : (r >> 1) + 1));
  w.slotB = helper ? 4 * gi + r : (mid ? 4 * gi + 2 : -1);
  w.loc0 = NSERV + gi * 2 + (r >> 1);
  w.nloc = helper;
  w.own = helper ? (r + 1) >> 1 : (mid ? 0 : 3);
  w.role = helper ? 0 : (mid ? R_FIN : R_FIN | R_PUB);
  const int k1st[3] = {0, 48 * 8 - MB, 48 * 8 - MB + 16 * 8 - hb1};
  int pos[NQT], sig[NQT];
  for (int i = 0; i < NQT; i++) { pos[i] = i; sig[i] = 0; }
  for (int i = 0; i < 3; i++)
    for (int p = k1st[i] / 8; p <= (k1st[i] + 6) / 8; p++) {
      int m = 1, at = 0;
      while (sig[m]) m += 3;
      while (pos[at] != p) at++;
      pos[at] = pos[m]; pos[m] = p; sig[m] = 1 + i;
    }
  w.hp = c < 131 ? pos[w.q0] : 0;
  if (helper && c < 130) w.role |= sig[w.q0] * R_SIG;
  if (c == 130) { w.nb0 = 15; w.na0 = 65; w.slotA = NSLOT - 1; w.own = 1; w.role = R_FIN | R_TAIL; w.loc0 = NSERV - NTAIL; w.nloc = NTAIL; }
  if (c == 131) { w.nb0 = w.na0 = w.nb1 = w.na1 = 0; w.loc0 = 0; w.nloc = NSERV - NTAIL; w.own = 0; }
  return w;
}
#define g_flag P.s->flag
#define g_M P.s->M
#define g_Wvo P.s->Wvo
#define g_Wmo P.s->Wmo
#define g_ml P.s->ml
#define g_unsafe P.s->unsafe
#define g_cnt P.s->cnt
#define g_h P.s->h
#define g_u P.u
#define g_stat P.s->stat
#define g_qp P.s->qp
#define g_agg P.s->agg
#define g_part P.s->part
#define g_bin P.s->bin
#define g_ovf P.s->ovf

__device__ __forceinline__ uint32_t smem_u32(const void* p) { return (uint32_t)__cvta_generic_to_shared(p); }
__device__ __forceinline__ void mbar_init(uint32_t bar, uint32_t cnt) { asm volatile("mbarrier.init.shared::cta.b64 [%0], %1;" :: "r"(bar), "r"(cnt) : "memory"); }
__device__ __forceinline__ void mbar_arrive(uint32_t bar) { asm volatile("mbarrier.arrive.shared::cta.b64 _, [%0];" :: "r"(bar) : "memory"); }
__device__ __forceinline__ void mbar_expect_tx(uint32_t bar, uint32_t bytes) { asm volatile("mbarrier.arrive.expect_tx.shared::cta.b64 _, [%0], %1;" :: "r"(bar), "r"(bytes) : "memory"); }
__device__ __forceinline__ bool mbar_try_wait(uint32_t bar, uint32_t parity) {
  uint32_t ok;
  asm volatile("{\n.reg .pred p;\nmbarrier.try_wait.parity.shared::cta.b64 p, [%1], %2;\nselp.b32 %0, 1, 0, p;\n}\n" : "=r"(ok) : "r"(bar), "r"(parity) : "memory");
  return ok;
}
__device__ __forceinline__ bool mbar_try_wait_nb(uint32_t bar, uint32_t parity) {
  uint32_t ok;
  asm volatile("{\n.reg .pred p;\nmbarrier.test_wait.parity.shared::cta.b64 p, [%1], %2;\nselp.b32 %0, 1, 0, p;\n}\n" : "=r"(ok) : "r"(bar), "r"(parity) : "memory");
  return ok;
}
__device__ __forceinline__ void mbar_wait(uint32_t bar, uint32_t parity) {
#pragma unroll 1
  for (uint32_t it = 0; it < (1u << 25); it++) if (mbar_try_wait(bar, parity)) break;
}
__device__ __forceinline__ void bulk_s2g(void* dst, uint32_t src, uint32_t bytes) {
  asm volatile("cp.async.bulk.global.shared::cta.bulk_group [%0], [%1], %2;" :: "l"(dst), "r"(src), "r"(bytes) : "memory");
}
__device__ __forceinline__ void bulk_commit() { asm volatile("cp.async.bulk.commit_group;" ::: "memory"); }
__device__ __forceinline__ void bulk_wait_read() { asm volatile("cp.async.bulk.wait_group.read 0;" ::: "memory"); }
__device__ __forceinline__ void bulk_wait_all() { asm volatile("cp.async.bulk.wait_group 0;" ::: "memory"); }
__device__ __forceinline__ bool bar_red_or(int id, int cnt, bool c) {
  uint32_t r;
  asm volatile("{\n.reg .pred p, q;\nsetp.ne.b32 q, %3, 0;\nbar.red.or.pred p, %1, %2, q;\nselp.b32 %0, 1, 0, p;\n}\n"
               : "=r"(r) : "r"(id), "r"(cnt), "r"((uint32_t)c) : "memory");
  return r != 0;
}
template <class T> __device__ __forceinline__ T* pofs(const void* base, uint32_t off) {
  asm volatile("" : "+r"(off));
  return (T*)((uint8_t*)base + off);
}
__device__ __forceinline__ const void* addr64(uint32_t lo, uint32_t hi) { uint64_t a; asm("mov.b64 %0, {%1, %2};" : "=l"(a) : "r"(lo), "r"(hi)); return (const void*)a; }
__device__ __forceinline__ uint4 ldcg_v(const void* a) {
  uint4 v;
  asm volatile("ld.volatile.global.v4.u32 {%0,%1,%2,%3}, [%4];" : "=r"(v.x), "=r"(v.y), "=r"(v.z), "=r"(v.w) : "l"(a) : "memory");
  return v;
}
__device__ __forceinline__ uint4 ldcs_v(const void* a) {
  uint4 v;
  asm volatile("ld.global.cs.v4.u32 {%0,%1,%2,%3}, [%4];" : "=r"(v.x), "=r"(v.y), "=r"(v.z), "=r"(v.w) : "l"(a) : "memory");
  return v;
}
__device__ __forceinline__ void prefetch_l2(const void* a, uint32_t bytes) { asm volatile("cp.async.bulk.prefetch.L2.global [%0], %1;" :: "l"(a), "r"(bytes) : "memory"); }
__device__ __forceinline__ void ldcg_if(uint4& v, const void* a, bool c) {
  asm volatile("{\n.reg .pred p;\nsetp.ne.b32 p, %5, 0;\n@p ld.volatile.global.v4.u32 {%0,%1,%2,%3}, [%4];\n}\n"
               : "+r"(v.x), "+r"(v.y), "+r"(v.z), "+r"(v.w) : "l"(a), "r"((uint32_t)c) : "memory");
}
__device__ __forceinline__ void cp_async16(uint32_t dst, const void* src) {
  asm volatile("cp.async.cg.shared.global [%0], [%1], 16;" :: "r"(dst), "l"(src) : "memory");
}
__device__ __forceinline__ void red_bf16x8(void* a, uint4 v) {
  asm volatile("red.global.add.noftz.v4.bf16x2 [%0], {%1,%2,%3,%4};" :: "l"(a), "r"(v.x), "r"(v.y), "r"(v.z), "r"(v.w) : "memory");
}
__device__ __forceinline__ uint32_t clk() { uint32_t c; asm volatile("mov.u32 %0, %%clock;" : "=r"(c) :: "memory"); return c; }
__device__ __forceinline__ uint32_t gtime() { uint32_t t; asm volatile("mov.u32 %0, %%globaltimer_lo;" : "=r"(t) :: "memory"); return t; }
__device__ __forceinline__ void stsm4(uint32_t a, uint32_t r0, uint32_t r1, uint32_t r2, uint32_t r3) {
  asm volatile("stmatrix.sync.aligned.m8n8.x4.shared.b16 [%0], {%1,%2,%3,%4};" :: "r"(a), "r"(r0), "r"(r1), "r"(r2), "r"(r3) : "memory");
}
__device__ __forceinline__ void ldsm4(uint32_t a, uint32_t& r0, uint32_t& r1, uint32_t& r2, uint32_t& r3) {
  asm volatile("ldmatrix.sync.aligned.m8n8.x4.shared.b16 {%0,%1,%2,%3}, [%4];" : "=r"(r0), "=r"(r1), "=r"(r2), "=r"(r3) : "r"(a) : "memory");
}
__device__ __forceinline__ void red_relaxed(uint32_t* p) { asm volatile("red.relaxed.gpu.global.add.u32 [%0], 1;" :: "l"(p) : "memory"); }
__device__ __forceinline__ uint32_t lds32(uint32_t a) { uint32_t v; asm volatile("ld.shared.u32 %0, [%1];" : "=r"(v) : "r"(a) : "memory"); return v; }
__device__ __forceinline__ void cp_commit() { asm volatile("cp.async.commit_group;" ::: "memory"); }
__device__ __forceinline__ uint32_t hmul2(uint32_t a, uint32_t b) { uint32_t d; asm("mul.rn.bf16x2 %0, %1, %2;" : "=r"(d) : "r"(a), "r"(b)); return d; }
__device__ __forceinline__ uint32_t hfma2(uint32_t a, uint32_t b, uint32_t c) { uint32_t d; asm("fma.rn.bf16x2 %0, %1, %2, %3;" : "=r"(d) : "r"(a), "r"(b), "r"(c)); return d; }
__device__ __forceinline__ uint32_t pow2_bf2(int n) { return (uint32_t)max(n + 127, 0) * 0x00800080u; }
__device__ __forceinline__ int fexp(float x) { return (int)(__float_as_uint(x) >> 23) - 127; }
__device__ __forceinline__ void bulk_g2s(uint32_t dst, const void* src, uint32_t bytes, uint32_t bar) {
  asm volatile("cp.async.bulk.shared::cta.global.mbarrier::complete_tx::bytes [%0], [%1], %2, [%3];"
    :: "r"(dst), "l"(src), "r"(bytes), "r"(bar) : "memory");
}
__device__ __forceinline__ void bulk_g2s_last(uint32_t dst, const void* src, uint32_t bytes, uint32_t bar) {
  asm volatile("{\n.reg .b64 p;\ncreatepolicy.fractional.L2::evict_first.b64 p;\n"
    "cp.async.bulk.shared::cta.global.mbarrier::complete_tx::bytes.L2::cache_hint [%0], [%1], %2, [%3], p;\n}\n"
    :: "r"(dst), "l"(src), "r"(bytes), "r"(bar) : "memory");
}
__device__ __forceinline__ void wg_fence() { asm volatile("wgmma.fence.sync.aligned;" ::: "memory"); }
__device__ __forceinline__ void wg_commit() { asm volatile("wgmma.commit_group.sync.aligned;" ::: "memory"); }
template<int N> __device__ __forceinline__ void wg_wait() { asm volatile("wgmma.wait_group.sync.aligned %0;" :: "n"(N) : "memory"); }
__device__ __forceinline__ void bar_sync(int id, int cnt) { asm volatile("bar.sync %0, %1;" :: "r"(id), "r"(cnt) : "memory"); }
__device__ __forceinline__ void fence_async_smem() { asm volatile("fence.proxy.async.shared::cta;" ::: "memory"); }
__device__ __forceinline__ void fence_async_gmem() { asm volatile("fence.proxy.async.global;" ::: "memory"); }
__device__ __forceinline__ void bar_arrive(int id, int cnt) { asm volatile("bar.arrive %0, %1;" :: "r"(id), "r"(cnt) : "memory"); }
__device__ __forceinline__ void red_release(uint32_t* p) { asm volatile("red.release.gpu.global.add.u32 [%0], 1;" :: "l"(p) : "memory"); }
__device__ __forceinline__ void red_release_w(uint32_t* p) {
  __syncwarp();
  asm volatile("{\n.reg .pred q;\n.reg .b32 l;\nmov.u32 l, %%laneid;\nsetp.eq.u32 q, l, 0;\n@q fence.release.gpu;\n@q red.relaxed.gpu.global.add.u32 [%0], 1;\n}\n" :: "l"(p) : "memory");
}
__device__ __forceinline__ void mbar_wait_w(uint32_t bar, uint32_t parity) {
#pragma unroll 1
  for (uint32_t it = 0; it < (1u << 25); it++) if (__all_sync(0xffffffffu, mbar_try_wait(bar, parity))) break;
}
#define flag_release_w(f) red_release_w(g_flag + (f))
#define flag_wait_w(f, target) poll_acquire_w(g_flag + (f), target)
#define flag_release(f) red_release(g_flag + (f))
__device__ __forceinline__ uint32_t ld_relaxed(const uint32_t* p) {
  uint32_t v; asm volatile("ld.relaxed.gpu.global.u32 %0, [%1];" : "=r"(v) : "l"(p) : "memory"); return v;
}
#define flag_wait(f, target) poll_acquire(g_flag + (f), target)
__device__ __forceinline__ void poll_acquire(const uint32_t* p, uint32_t target) {
#pragma unroll 1
  for (uint32_t it = 0; it < (1u << 23); it++) if ((int)(ld_relaxed(p) - target) >= 0) break;
  asm volatile("fence.acquire.gpu;" ::: "memory");
}
__device__ __forceinline__ void poll_acquire_w(const uint32_t* p, uint32_t target) {
#pragma unroll 1
  for (uint32_t it = 0; it < (1u << 23); it++) {
    if (__all_sync(0xffffffffu, (int)(ld_relaxed(p) - target) >= 0)) break;
    if (BACKOFF) __nanosleep(BACKOFF);
  }
  asm volatile("fence.acquire.gpu;" ::: "memory");
}
template<int N> __device__ __forceinline__ void reg_fence(float (&d)[N]) {
#pragma unroll
  for (int i = 0; i < N; i++) asm volatile("" : "+f"(d[i]) :: "memory");
}
template<int N> __device__ __forceinline__ void reg_fence(uint32_t (&d)[N]) {
#pragma unroll
  for (int i = 0; i < N; i++) asm volatile("" : "+r"(d[i]) :: "memory");
}
__device__ __forceinline__ float ex2(float x) { float y; asm("ex2.approx.ftz.f32 %0, %1;" : "=f"(y) : "f"(x)); return y; }
__device__ __forceinline__ uint32_t pack_bf16(float lo, float hi) { uint32_t r; asm("cvt.rn.bf16x2.f32 %0, %1, %2;" : "=r"(r) : "f"(hi), "f"(lo)); return r; }
__device__ __forceinline__ float bf_lo(uint32_t w) { return __uint_as_float(w << 16); }
__device__ __forceinline__ float bf_hi(uint32_t w) { return __uint_as_float(w & 0xffff0000u); }
__device__ __forceinline__ uint64_t desc_k(uint32_t addr, uint32_t add) { return (uint64_t)((((addr & 0x3FFFF) >> 4) | (1u << 16)) + add) | (0x40000100ull << 32); }
__device__ __forceinline__ uint64_t desc_mn(uint32_t addr, uint32_t add) { return (uint64_t)((((addr & 0x3FFFF) >> 4) | ((1024u >> 4) << 16)) + add) | (0x40000100ull << 32); }
__device__ __forceinline__ uint64_t desc_m(uint32_t addr, uint32_t add) { return (uint64_t)((((addr & 0x3FFFF) >> 4) | ((1024u >> 4) << 16)) + add) | (0x80000020ull << 32); }
__device__ __forceinline__ void sts128(uint32_t a, uint4 v) { asm volatile("st.shared.v4.u32 [%0], {%1,%2,%3,%4};" :: "r"(a), "r"(v.x), "r"(v.y), "r"(v.z), "r"(v.w) : "memory"); }
__device__ __forceinline__ uint4 lds128(uint32_t a) { uint4 v; asm volatile("ld.shared.v4.u32 {%0,%1,%2,%3}, [%4];" : "=r"(v.x), "=r"(v.y), "=r"(v.z), "=r"(v.w) : "r"(a) : "memory"); return v; }
__device__ __forceinline__ void mma16816(float (&c)[4], uint32_t a0, uint32_t a1, uint32_t a2, uint32_t a3, uint32_t b0, uint32_t b1) {
  asm volatile("mma.sync.aligned.m16n8k16.row.col.f32.bf16.bf16.f32 {%0,%1,%2,%3}, {%4,%5,%6,%7}, {%8,%9}, {%0,%1,%2,%3};"
    : "+f"(c[0]), "+f"(c[1]), "+f"(c[2]), "+f"(c[3]) : "r"(a0), "r"(a1), "r"(a2), "r"(a3), "r"(b0), "r"(b1));
}
__device__ __forceinline__ uint32_t sw_byte(int r, int c) {
  return (uint32_t)((r >> 3) * 4096 + (c >> 6) * 1024 + (r & 7) * 128 + ((((c >> 3) & 7) ^ (r & 7)) << 4) + (c & 7) * 2);
}
__device__ __forceinline__ int cta_id() { int c; asm volatile("mov.u32 %0, %%ctaid.x;" : "=r"(c)); return c; }
__device__ __forceinline__ bool tid_is(int v) { int t; asm volatile("mov.u32 %0, %%tid.x;" : "=r"(t)); return t == v; }
#define STAMP(cond, who, i)
#define CSTAMP(cond, who, i)
#define DUMP(cond, who, i0, i1)
#define XSTAMP(cond, i)
#define SSTAMP(i)

template <int OA, int OB> __device__ __forceinline__ void wgmma_ss_n256_tb(float (&d)[128], uint64_t da, uint64_t db, int scale_d) {
  asm volatile("{\n.reg .pred p;\n.reg .b64 a, b;\nsetp.ne.b32 p, %130, 0;\nadd.s64 a, %128, %131;\nadd.s64 b, %129, %132;\n"
    "wgmma.mma_async.sync.aligned.m64n256k16.f32.bf16.bf16 "
    "{%0, %1, %2, %3, %4, %5, %6, %7, %8, %9, %10, %11, %12, %13, %14, %15, %16, %17, %18, %19, %20, %21, %22, %23, %24, %25, %26, %27, %28, %29, %30, %31, %32, %33, %34, %35, %36, %37, %38, %39, %40, %41, %42, %43, %44, %45, %46, %47, %48, %49, %50, %51, %52, %53, %54, %55, %56, %57, %58, %59, %60, %61, %62, %63, %64, %65, %66, %67, %68, %69, %70, %71, %72, %73, %74, %75, %76, %77, %78, %79, %80, %81, %82, %83, %84, %85, %86, %87, %88, %89, %90, %91, %92, %93, %94, %95, %96, %97, %98, %99, %100, %101, %102, %103, %104, %105, %106, %107, %108, %109, %110, %111, %112, %113, %114, %115, %116, %117, %118, %119, %120, %121, %122, %123, %124, %125, %126, %127}, "
    "a, b, p, 1, 1, 0, 1;\n}\n"
    : "+f"(d[0]), "+f"(d[1]), "+f"(d[2]), "+f"(d[3]), "+f"(d[4]), "+f"(d[5]), "+f"(d[6]), "+f"(d[7]), "+f"(d[8]), "+f"(d[9]), "+f"(d[10]), "+f"(d[11]), "+f"(d[12]), "+f"(d[13]), "+f"(d[14]), "+f"(d[15]), "+f"(d[16]), "+f"(d[17]), "+f"(d[18]), "+f"(d[19]), "+f"(d[20]), "+f"(d[21]), "+f"(d[22]), "+f"(d[23]), "+f"(d[24]), "+f"(d[25]), "+f"(d[26]), "+f"(d[27]), "+f"(d[28]), "+f"(d[29]), "+f"(d[30]), "+f"(d[31]), "+f"(d[32]), "+f"(d[33]), "+f"(d[34]), "+f"(d[35]), "+f"(d[36]), "+f"(d[37]), "+f"(d[38]), "+f"(d[39]), "+f"(d[40]), "+f"(d[41]), "+f"(d[42]), "+f"(d[43]), "+f"(d[44]), "+f"(d[45]), "+f"(d[46]), "+f"(d[47]), "+f"(d[48]), "+f"(d[49]), "+f"(d[50]), "+f"(d[51]), "+f"(d[52]), "+f"(d[53]), "+f"(d[54]), "+f"(d[55]), "+f"(d[56]), "+f"(d[57]), "+f"(d[58]), "+f"(d[59]), "+f"(d[60]), "+f"(d[61]), "+f"(d[62]), "+f"(d[63]), "+f"(d[64]), "+f"(d[65]), "+f"(d[66]), "+f"(d[67]), "+f"(d[68]), "+f"(d[69]), "+f"(d[70]), "+f"(d[71]), "+f"(d[72]), "+f"(d[73]), "+f"(d[74]), "+f"(d[75]), "+f"(d[76]), "+f"(d[77]), "+f"(d[78]), "+f"(d[79]), "+f"(d[80]), "+f"(d[81]), "+f"(d[82]), "+f"(d[83]), "+f"(d[84]), "+f"(d[85]), "+f"(d[86]), "+f"(d[87]), "+f"(d[88]), "+f"(d[89]), "+f"(d[90]), "+f"(d[91]), "+f"(d[92]), "+f"(d[93]), "+f"(d[94]), "+f"(d[95]), "+f"(d[96]), "+f"(d[97]), "+f"(d[98]), "+f"(d[99]), "+f"(d[100]), "+f"(d[101]), "+f"(d[102]), "+f"(d[103]), "+f"(d[104]), "+f"(d[105]), "+f"(d[106]), "+f"(d[107]), "+f"(d[108]), "+f"(d[109]), "+f"(d[110]), "+f"(d[111]), "+f"(d[112]), "+f"(d[113]), "+f"(d[114]), "+f"(d[115]), "+f"(d[116]), "+f"(d[117]), "+f"(d[118]), "+f"(d[119]), "+f"(d[120]), "+f"(d[121]), "+f"(d[122]), "+f"(d[123]), "+f"(d[124]), "+f"(d[125]), "+f"(d[126]), "+f"(d[127])
    : "l"(da), "l"(db), "r"(scale_d), "n"(OA), "n"(OB));
}
template <int OA, int OB> __device__ __forceinline__ void wgmma_qk(float (&d)[64], uint64_t da, uint64_t db, int scale_d) {
  asm volatile("{\n.reg .pred p;\n.reg .b64 a, b;\nsetp.ne.b32 p, %66, 0;\nadd.s64 a, %64, %67;\nadd.s64 b, %65, %68;\n"
    "wgmma.mma_async.sync.aligned.m64n128k16.f32.bf16.bf16 "
    "{%0, %1, %2, %3, %4, %5, %6, %7, %8, %9, %10, %11, %12, %13, %14, %15, %16, %17, %18, %19, %20, %21, %22, %23, %24, %25, %26, %27, %28, %29, %30, %31, %32, %33, %34, %35, %36, %37, %38, %39, %40, %41, %42, %43, %44, %45, %46, %47, %48, %49, %50, %51, %52, %53, %54, %55, %56, %57, %58, %59, %60, %61, %62, %63}, "
    "a, b, p, 1, 1, 0, 0;\n}\n"
    : "+f"(d[0]), "+f"(d[1]), "+f"(d[2]), "+f"(d[3]), "+f"(d[4]), "+f"(d[5]), "+f"(d[6]), "+f"(d[7]), "+f"(d[8]), "+f"(d[9]), "+f"(d[10]), "+f"(d[11]), "+f"(d[12]), "+f"(d[13]), "+f"(d[14]), "+f"(d[15]), "+f"(d[16]), "+f"(d[17]), "+f"(d[18]), "+f"(d[19]), "+f"(d[20]), "+f"(d[21]), "+f"(d[22]), "+f"(d[23]), "+f"(d[24]), "+f"(d[25]), "+f"(d[26]), "+f"(d[27]), "+f"(d[28]), "+f"(d[29]), "+f"(d[30]), "+f"(d[31]), "+f"(d[32]), "+f"(d[33]), "+f"(d[34]), "+f"(d[35]), "+f"(d[36]), "+f"(d[37]), "+f"(d[38]), "+f"(d[39]), "+f"(d[40]), "+f"(d[41]), "+f"(d[42]), "+f"(d[43]), "+f"(d[44]), "+f"(d[45]), "+f"(d[46]), "+f"(d[47]), "+f"(d[48]), "+f"(d[49]), "+f"(d[50]), "+f"(d[51]), "+f"(d[52]), "+f"(d[53]), "+f"(d[54]), "+f"(d[55]), "+f"(d[56]), "+f"(d[57]), "+f"(d[58]), "+f"(d[59]), "+f"(d[60]), "+f"(d[61]), "+f"(d[62]), "+f"(d[63])
    : "l"(da), "l"(db), "r"(scale_d), "n"(OA), "n"(OB));
}
template <int OA, int OB> __device__ __forceinline__ void wgmma_qk(float (&d)[56], uint64_t da, uint64_t db, int scale_d) {
  asm volatile("{\n.reg .pred p;\n.reg .b64 a, b;\nsetp.ne.b32 p, %58, 0;\nadd.s64 a, %56, %59;\nadd.s64 b, %57, %60;\n"
    "wgmma.mma_async.sync.aligned.m64n112k16.f32.bf16.bf16 "
    "{%0, %1, %2, %3, %4, %5, %6, %7, %8, %9, %10, %11, %12, %13, %14, %15, %16, %17, %18, %19, %20, %21, %22, %23, %24, %25, %26, %27, %28, %29, %30, %31, %32, %33, %34, %35, %36, %37, %38, %39, %40, %41, %42, %43, %44, %45, %46, %47, %48, %49, %50, %51, %52, %53, %54, %55}, "
    "a, b, p, 1, 1, 0, 0;\n}\n"
    : "+f"(d[0]), "+f"(d[1]), "+f"(d[2]), "+f"(d[3]), "+f"(d[4]), "+f"(d[5]), "+f"(d[6]), "+f"(d[7]), "+f"(d[8]), "+f"(d[9]), "+f"(d[10]), "+f"(d[11]), "+f"(d[12]), "+f"(d[13]), "+f"(d[14]), "+f"(d[15]), "+f"(d[16]), "+f"(d[17]), "+f"(d[18]), "+f"(d[19]), "+f"(d[20]), "+f"(d[21]), "+f"(d[22]), "+f"(d[23]), "+f"(d[24]), "+f"(d[25]), "+f"(d[26]), "+f"(d[27]), "+f"(d[28]), "+f"(d[29]), "+f"(d[30]), "+f"(d[31]), "+f"(d[32]), "+f"(d[33]), "+f"(d[34]), "+f"(d[35]), "+f"(d[36]), "+f"(d[37]), "+f"(d[38]), "+f"(d[39]), "+f"(d[40]), "+f"(d[41]), "+f"(d[42]), "+f"(d[43]), "+f"(d[44]), "+f"(d[45]), "+f"(d[46]), "+f"(d[47]), "+f"(d[48]), "+f"(d[49]), "+f"(d[50]), "+f"(d[51]), "+f"(d[52]), "+f"(d[53]), "+f"(d[54]), "+f"(d[55])
    : "l"(da), "l"(db), "r"(scale_d), "n"(OA), "n"(OB));
}
template <int OB> __device__ __forceinline__ void wgmma_rs_n256_tb(float (&d)[128], uint32_t a0, uint32_t a1, uint32_t a2, uint32_t a3, uint64_t db, int scale_d) {
  asm volatile("{\n.reg .pred p;\n.reg .b64 b;\nsetp.ne.b32 p, %133, 0;\nadd.s64 b, %132, %134;\n"
    "wgmma.mma_async.sync.aligned.m64n256k16.f32.bf16.bf16 "
    "{%0, %1, %2, %3, %4, %5, %6, %7, %8, %9, %10, %11, %12, %13, %14, %15, %16, %17, %18, %19, %20, %21, %22, %23, %24, %25, %26, %27, %28, %29, %30, %31, %32, %33, %34, %35, %36, %37, %38, %39, %40, %41, %42, %43, %44, %45, %46, %47, %48, %49, %50, %51, %52, %53, %54, %55, %56, %57, %58, %59, %60, %61, %62, %63, %64, %65, %66, %67, %68, %69, %70, %71, %72, %73, %74, %75, %76, %77, %78, %79, %80, %81, %82, %83, %84, %85, %86, %87, %88, %89, %90, %91, %92, %93, %94, %95, %96, %97, %98, %99, %100, %101, %102, %103, %104, %105, %106, %107, %108, %109, %110, %111, %112, %113, %114, %115, %116, %117, %118, %119, %120, %121, %122, %123, %124, %125, %126, %127}, "
    "{%128, %129, %130, %131}, b, p, 1, 1, 1;\n}\n"
    : "+f"(d[0]), "+f"(d[1]), "+f"(d[2]), "+f"(d[3]), "+f"(d[4]), "+f"(d[5]), "+f"(d[6]), "+f"(d[7]), "+f"(d[8]), "+f"(d[9]), "+f"(d[10]), "+f"(d[11]), "+f"(d[12]), "+f"(d[13]), "+f"(d[14]), "+f"(d[15]), "+f"(d[16]), "+f"(d[17]), "+f"(d[18]), "+f"(d[19]), "+f"(d[20]), "+f"(d[21]), "+f"(d[22]), "+f"(d[23]), "+f"(d[24]), "+f"(d[25]), "+f"(d[26]), "+f"(d[27]), "+f"(d[28]), "+f"(d[29]), "+f"(d[30]), "+f"(d[31]), "+f"(d[32]), "+f"(d[33]), "+f"(d[34]), "+f"(d[35]), "+f"(d[36]), "+f"(d[37]), "+f"(d[38]), "+f"(d[39]), "+f"(d[40]), "+f"(d[41]), "+f"(d[42]), "+f"(d[43]), "+f"(d[44]), "+f"(d[45]), "+f"(d[46]), "+f"(d[47]), "+f"(d[48]), "+f"(d[49]), "+f"(d[50]), "+f"(d[51]), "+f"(d[52]), "+f"(d[53]), "+f"(d[54]), "+f"(d[55]), "+f"(d[56]), "+f"(d[57]), "+f"(d[58]), "+f"(d[59]), "+f"(d[60]), "+f"(d[61]), "+f"(d[62]), "+f"(d[63]), "+f"(d[64]), "+f"(d[65]), "+f"(d[66]), "+f"(d[67]), "+f"(d[68]), "+f"(d[69]), "+f"(d[70]), "+f"(d[71]), "+f"(d[72]), "+f"(d[73]), "+f"(d[74]), "+f"(d[75]), "+f"(d[76]), "+f"(d[77]), "+f"(d[78]), "+f"(d[79]), "+f"(d[80]), "+f"(d[81]), "+f"(d[82]), "+f"(d[83]), "+f"(d[84]), "+f"(d[85]), "+f"(d[86]), "+f"(d[87]), "+f"(d[88]), "+f"(d[89]), "+f"(d[90]), "+f"(d[91]), "+f"(d[92]), "+f"(d[93]), "+f"(d[94]), "+f"(d[95]), "+f"(d[96]), "+f"(d[97]), "+f"(d[98]), "+f"(d[99]), "+f"(d[100]), "+f"(d[101]), "+f"(d[102]), "+f"(d[103]), "+f"(d[104]), "+f"(d[105]), "+f"(d[106]), "+f"(d[107]), "+f"(d[108]), "+f"(d[109]), "+f"(d[110]), "+f"(d[111]), "+f"(d[112]), "+f"(d[113]), "+f"(d[114]), "+f"(d[115]), "+f"(d[116]), "+f"(d[117]), "+f"(d[118]), "+f"(d[119]), "+f"(d[120]), "+f"(d[121]), "+f"(d[122]), "+f"(d[123]), "+f"(d[124]), "+f"(d[125]), "+f"(d[126]), "+f"(d[127])
    : "r"(a0), "r"(a1), "r"(a2), "r"(a3), "l"(db), "r"(scale_d), "n"(OB));
}
template <int OB> __device__ __forceinline__ void wgmma_rs_n256_tb_first(float (&d)[128], uint32_t a0, uint32_t a1, uint32_t a2, uint32_t a3, uint64_t db) {
  asm volatile("{\n.reg .pred p;\n.reg .b64 b;\nsetp.ne.b32 p, 0, 0;\nadd.s64 b, %132, %133;\n"
    "wgmma.mma_async.sync.aligned.m64n256k16.f32.bf16.bf16 "
    "{%0, %1, %2, %3, %4, %5, %6, %7, %8, %9, %10, %11, %12, %13, %14, %15, %16, %17, %18, %19, %20, %21, %22, %23, %24, %25, %26, %27, %28, %29, %30, %31, %32, %33, %34, %35, %36, %37, %38, %39, %40, %41, %42, %43, %44, %45, %46, %47, %48, %49, %50, %51, %52, %53, %54, %55, %56, %57, %58, %59, %60, %61, %62, %63, %64, %65, %66, %67, %68, %69, %70, %71, %72, %73, %74, %75, %76, %77, %78, %79, %80, %81, %82, %83, %84, %85, %86, %87, %88, %89, %90, %91, %92, %93, %94, %95, %96, %97, %98, %99, %100, %101, %102, %103, %104, %105, %106, %107, %108, %109, %110, %111, %112, %113, %114, %115, %116, %117, %118, %119, %120, %121, %122, %123, %124, %125, %126, %127}, "
    "{%128, %129, %130, %131}, b, p, 1, 1, 1;\n}\n"
    : "=f"(d[0]), "=f"(d[1]), "=f"(d[2]), "=f"(d[3]), "=f"(d[4]), "=f"(d[5]), "=f"(d[6]), "=f"(d[7]), "=f"(d[8]), "=f"(d[9]), "=f"(d[10]), "=f"(d[11]), "=f"(d[12]), "=f"(d[13]), "=f"(d[14]), "=f"(d[15]), "=f"(d[16]), "=f"(d[17]), "=f"(d[18]), "=f"(d[19]), "=f"(d[20]), "=f"(d[21]), "=f"(d[22]), "=f"(d[23]), "=f"(d[24]), "=f"(d[25]), "=f"(d[26]), "=f"(d[27]), "=f"(d[28]), "=f"(d[29]), "=f"(d[30]), "=f"(d[31]), "=f"(d[32]), "=f"(d[33]), "=f"(d[34]), "=f"(d[35]), "=f"(d[36]), "=f"(d[37]), "=f"(d[38]), "=f"(d[39]), "=f"(d[40]), "=f"(d[41]), "=f"(d[42]), "=f"(d[43]), "=f"(d[44]), "=f"(d[45]), "=f"(d[46]), "=f"(d[47]), "=f"(d[48]), "=f"(d[49]), "=f"(d[50]), "=f"(d[51]), "=f"(d[52]), "=f"(d[53]), "=f"(d[54]), "=f"(d[55]), "=f"(d[56]), "=f"(d[57]), "=f"(d[58]), "=f"(d[59]), "=f"(d[60]), "=f"(d[61]), "=f"(d[62]), "=f"(d[63]), "=f"(d[64]), "=f"(d[65]), "=f"(d[66]), "=f"(d[67]), "=f"(d[68]), "=f"(d[69]), "=f"(d[70]), "=f"(d[71]), "=f"(d[72]), "=f"(d[73]), "=f"(d[74]), "=f"(d[75]), "=f"(d[76]), "=f"(d[77]), "=f"(d[78]), "=f"(d[79]), "=f"(d[80]), "=f"(d[81]), "=f"(d[82]), "=f"(d[83]), "=f"(d[84]), "=f"(d[85]), "=f"(d[86]), "=f"(d[87]), "=f"(d[88]), "=f"(d[89]), "=f"(d[90]), "=f"(d[91]), "=f"(d[92]), "=f"(d[93]), "=f"(d[94]), "=f"(d[95]), "=f"(d[96]), "=f"(d[97]), "=f"(d[98]), "=f"(d[99]), "=f"(d[100]), "=f"(d[101]), "=f"(d[102]), "=f"(d[103]), "=f"(d[104]), "=f"(d[105]), "=f"(d[106]), "=f"(d[107]), "=f"(d[108]), "=f"(d[109]), "=f"(d[110]), "=f"(d[111]), "=f"(d[112]), "=f"(d[113]), "=f"(d[114]), "=f"(d[115]), "=f"(d[116]), "=f"(d[117]), "=f"(d[118]), "=f"(d[119]), "=f"(d[120]), "=f"(d[121]), "=f"(d[122]), "=f"(d[123]), "=f"(d[124]), "=f"(d[125]), "=f"(d[126]), "=f"(d[127])
    : "r"(a0), "r"(a1), "r"(a2), "r"(a3), "l"(db), "n"(OB));
}
template <int OB> __device__ __forceinline__ void wgmma_rs_n128_tb(float (&d)[64], uint32_t a0, uint32_t a1, uint32_t a2, uint32_t a3, uint64_t db, int scale_d) {
  asm volatile("{\n.reg .pred p;\n.reg .b64 b;\nsetp.ne.b32 p, %69, 0;\nadd.s64 b, %68, %70;\n"
    "wgmma.mma_async.sync.aligned.m64n128k16.f32.bf16.bf16 "
    "{%0, %1, %2, %3, %4, %5, %6, %7, %8, %9, %10, %11, %12, %13, %14, %15, %16, %17, %18, %19, %20, %21, %22, %23, %24, %25, %26, %27, %28, %29, %30, %31, %32, %33, %34, %35, %36, %37, %38, %39, %40, %41, %42, %43, %44, %45, %46, %47, %48, %49, %50, %51, %52, %53, %54, %55, %56, %57, %58, %59, %60, %61, %62, %63}, "
    "{%64, %65, %66, %67}, b, p, 1, 1, 1;\n}\n"
    : "+f"(d[0]), "+f"(d[1]), "+f"(d[2]), "+f"(d[3]), "+f"(d[4]), "+f"(d[5]), "+f"(d[6]), "+f"(d[7]), "+f"(d[8]), "+f"(d[9]), "+f"(d[10]), "+f"(d[11]), "+f"(d[12]), "+f"(d[13]), "+f"(d[14]), "+f"(d[15]), "+f"(d[16]), "+f"(d[17]), "+f"(d[18]), "+f"(d[19]), "+f"(d[20]), "+f"(d[21]), "+f"(d[22]), "+f"(d[23]), "+f"(d[24]), "+f"(d[25]), "+f"(d[26]), "+f"(d[27]), "+f"(d[28]), "+f"(d[29]), "+f"(d[30]), "+f"(d[31]), "+f"(d[32]), "+f"(d[33]), "+f"(d[34]), "+f"(d[35]), "+f"(d[36]), "+f"(d[37]), "+f"(d[38]), "+f"(d[39]), "+f"(d[40]), "+f"(d[41]), "+f"(d[42]), "+f"(d[43]), "+f"(d[44]), "+f"(d[45]), "+f"(d[46]), "+f"(d[47]), "+f"(d[48]), "+f"(d[49]), "+f"(d[50]), "+f"(d[51]), "+f"(d[52]), "+f"(d[53]), "+f"(d[54]), "+f"(d[55]), "+f"(d[56]), "+f"(d[57]), "+f"(d[58]), "+f"(d[59]), "+f"(d[60]), "+f"(d[61]), "+f"(d[62]), "+f"(d[63])
    : "r"(a0), "r"(a1), "r"(a2), "r"(a3), "l"(db), "r"(scale_d), "n"(OB));
}
template <int V> using IC = std::integral_constant<int, V>;
template <int I, int N, class F> __device__ __forceinline__ void static_for(F&& f) {
  if constexpr (I < N) { f(std::integral_constant<int, I>{}); static_for<I + 1, N>(f); }
}

constexpr uint32_t SM_Q = 0, SM_BAR = 7 * 32768;
constexpr uint32_t B_FULL = SM_BAR, B_EMPTY = B_FULL + 24, B_WF = B_EMPTY + 24, B_QFULL = B_WF + 32, B_QEMPTY = B_QFULL + 16,
                   B_EVH = B_QEMPTY + 16, B_EVQ = B_EVH + 8, B_EVP0 = B_EVQ + 8, B_BG = B_EVP0 + 16, B_M0 = B_BG + 8, B_HALF = B_M0 + 8,
                   B_HRD = B_HALF + 8, SM_UNSAFE = B_HRD + 8, SM_TS = SM_UNSAFE + 8, SM_ML = (SM_TS + 192 + 15) / 16 * 16, SM_EPOCH = SM_ML + 1024, SM_GE = SM_EPOCH + 4, SM_END = SM_EPOCH + 16;
constexpr uint32_t POS_M = 0x5462;
constexpr int SMEM_BYTES = SM_END;

#define ROW0(u) make_uint4(pack_bf16(o[16 * u], o[16 * u + 1]), pack_bf16(o[16 * u + 4], o[16 * u + 5]), \
                           pack_bf16(o[16 * u + 8], o[16 * u + 9]), pack_bf16(o[16 * u + 12], o[16 * u + 13]))
#define ROW1(u) make_uint4(pack_bf16(o[16 * u + 2], o[16 * u + 3]), pack_bf16(o[16 * u + 6], o[16 * u + 7]), \
                           pack_bf16(o[16 * u + 10], o[16 * u + 11]), pack_bf16(o[16 * u + 14], o[16 * u + 15]))

__global__ void __launch_bounds__(384, 1) gps_kernel(const __grid_constant__ Params P) {
  extern __shared__ __align__(1024) uint8_t smem_raw[];
  constexpr uint32_t sb = 1024;
  if (smem_u32(smem_raw) != sb) return;
  const int cta = blockIdx.x;
  const int wg = __shfl_sync(0xffffffffu, (int)threadIdx.x >> 7, 0);
  const int warp = __shfl_sync(0xffffffffu, ((int)threadIdx.x >> 5) & 3, 0);
  const int lane = threadIdx.x & 31;
#define ROLE                                                                                       \
  const Work& W = P.w[cta_id()];                                                                   \
  [[maybe_unused]] const int n0 = W.nb0 + W.na0, n1 = W.nb1 + W.na1, total = n0 + n1;              \
  [[maybe_unused]] const bool fin = W.role & R_FIN, tail = W.role & R_TAIL;                        \
  [[maybe_unused]] const uint32_t posw = total == 0 || tail ? POS_M : ((total & 1) ? 0x2546 : 0x4326)
  const int g = lane >> 2, t = lane & 3;
  if (wg < 2) {
    const int tid = threadIdx.x & 127;
    ROLE;
    const uint32_t sQ = sb + SM_Q + wg * 32768;
#define st0 tid_is(wg * 128)
    STAMP(st0, wg, 0);
    const int rr = lane >> 3, j = lane & 7;
    const uint4* px[4];
#pragma unroll
    for (int i = 0; i < 4; i++) px[i] = (const uint4*)(P.x + (size_t)min(W.q0 * 128 + wg * 64 + warp * 16 + i * 4 + rr, NN - 1) * 256) + j;
    asm volatile("" : "+l"(px[0]), "+l"(px[1]), "+l"(px[2]), "+l"(px[3]));
    if (cta * 8 + wg * 4 + warp == 131 * 8) {
      const uint4 xs = __ldg((const uint4*)P.x + lane * 312 * 32);
      const uint32_t ep = ld_relaxed(g_flag + F_EPOCH);
      const float d0 = bf_lo(xs.x) - bf_hi(xs.x), d1 = bf_lo(xs.y) - bf_hi(xs.y), d2 = bf_lo(xs.z) - bf_hi(xs.z), d3 = bf_lo(xs.w) - bf_hi(xs.w);
      const int ge = __reduce_max_sync(0xffffffffu, __float_as_uint((d0 * d0 + d1 * d1 + d2 * d2 + d3 * d3) * (0.125f / 1e-5f)) >> 24);
      if (lane == 0) asm volatile("st.relaxed.gpu.global.u32 [%0], %1;" :: "l"(g_flag + F_GE), "r"((ep + 1) * 16 + min(max(63 - ge, 0), 12)) : "memory");
    }
    __syncwarp();
    auto x_load = [&](int c) {
      if (c < 4) {
#pragma unroll
        for (int i = 0; i < 4; i++)
          cp_async16(sQ + warp * 8192 + (i >> 1) * 4096 + c * 1024 + ((i & 1) * 4 + rr) * 128 + ((j ^ ((i & 1) * 4 + rr)) << 4), px[i] + c * 8);
      }
      cp_commit();
    };
    auto start = [&]() {
      bar_sync(4, 384);
      if (wg == 1) bar_arrive(5, 256);
    };

    const uint32_t sF = sQ + warp * 8192 + ((lane >> 3) & 1) * 4096 + (lane & 7) * 128;
    auto frag = [&](int k) { return sF + (k >> 2) * 1024 + ((((k & 3) * 2 + (lane >> 4)) ^ (lane & 7)) << 4); };
    uint32_t hq[64];
    const bool own = (W.own >> wg) & 1;
    auto layernorm = [&]() __attribute__((always_inline)) {
#pragma unroll
      for (int c = 0; c < XD; c++) x_load(c);
      start();
      float c1[4] = {0.f, 0.f, 0.f, 0.f}, ca[4] = {0.f, 0.f, 0.f, 0.f}, cb[4] = {0.f, 0.f, 0.f, 0.f};
#pragma unroll
      for (int k = 0; k < 16; k++) {
        if ((k & 3) == 0) {
          asm volatile("cp.async.wait_group %0;" :: "n"(XD - 1) : "memory");
          __syncwarp();
          x_load(k / 4 + XD);
        }
        ldsm4(frag(k), hq[4 * k], hq[4 * k + 1], hq[4 * k + 2], hq[4 * k + 3]);
        mma16816(c1, hq[4 * k], hq[4 * k + 1], hq[4 * k + 2], hq[4 * k + 3], 0x3f803f80u, 0x3f803f80u);
        mma16816(ca, hq[4 * k], hq[4 * k + 1], hq[4 * k + 2], hq[4 * k + 3], hq[4 * k], hq[4 * k + 2]);
        mma16816(cb, hq[4 * k], hq[4 * k + 1], hq[4 * k + 2], hq[4 * k + 3], hq[4 * k + 1], hq[4 * k + 3]);
      }
      const float mu0 = c1[0] * (1.0f / 256.0f), mu1 = c1[2] * (1.0f / 256.0f);
      const float v0 = fmaf(__shfl_sync(0xffffffffu, g & 1 ? ca[1] : ca[0], g * 4 + (g >> 1)), 1.0f / 256.0f, 1e-5f - mu0 * mu0);
      const float v1 = fmaf(__shfl_sync(0xffffffffu, g & 1 ? cb[3] : cb[2], g * 4 + (g >> 1)), 1.0f / 256.0f, 1e-5f - mu1 * mu1);
      float rs0, rs1;
      asm("rsqrt.approx.ftz.f32 %0, %1;" : "=f"(rs0) : "f"(v0)); asm("rsqrt.approx.ftz.f32 %0, %1;" : "=f"(rs1) : "f"(v1));
      float nb0 = -mu0 * rs0, nb1 = -mu1 * rs1;
      const uint32_t sS = sb + SM_ML + (wg * 64 + warp * 16) * 8;
      if (t == 0) {
        asm volatile("st.shared.v2.f32 [%0], {%1,%2};" :: "r"(sS + g * 8), "f"(rs0), "f"(nb0) : "memory");
        asm volatile("st.shared.v2.f32 [%0], {%1,%2};" :: "r"(sS + g * 8 + 64), "f"(rs1), "f"(nb1) : "memory");
      }
      if (__any_sync(0xffffffffu, !(4.f * mu0 * mu0 <= v0) || !(4.f * mu1 * mu1 <= v1))) {
#pragma unroll 1
        for (int r = 0; r < 16; r++) {
          const uint32_t ad = sQ + warp * 8192 + (r >> 3) * 4096 + rr * 1024 + (r & 7) * 128 + ((j ^ (r & 7)) << 4);
          const uint4 v = lds128(ad);
          float f[8] = {bf_lo(v.x), bf_hi(v.x), bf_lo(v.y), bf_hi(v.y), bf_lo(v.z), bf_hi(v.z), bf_lo(v.w), bf_hi(v.w)};
          float sum = 0.f, ss = 0.f, rs;
#pragma unroll
          for (int i = 0; i < 8; i++) sum += f[i];
#pragma unroll 1
          for (int k = 1; k < 32; k *= 2) sum += __shfl_xor_sync(0xffffffffu, sum, k);
          sum *= 1.0f / 256.0f;
#pragma unroll
          for (int i = 0; i < 8; i++) { f[i] -= sum; ss += f[i] * f[i]; }
#pragma unroll 1
          for (int k = 1; k < 32; k *= 2) ss += __shfl_xor_sync(0xffffffffu, ss, k);
          asm("rsqrt.approx.ftz.f32 %0, %1;" : "=f"(rs) : "f"(fmaf(ss, 1.0f / 256.0f, 1e-5f)));
          sts128(ad, make_uint4(pack_bf16(f[0] * rs, f[1] * rs), pack_bf16(f[2] * rs, f[3] * rs), pack_bf16(f[4] * rs, f[5] * rs), pack_bf16(f[6] * rs, f[7] * rs)));
          if (lane == 0) asm volatile("st.shared.v2.f32 [%0], {%1,%2};" :: "r"(sS + r * 8), "f"(rs), "f"(-sum * rs) : "memory");
        }
        __syncwarp();
#pragma unroll
        for (int k = 0; k < 16; k++) ldsm4(frag(k), hq[4 * k], hq[4 * k + 1], hq[4 * k + 2], hq[4 * k + 3]);
        rs0 = rs1 = 1.f; nb0 = nb1 = 0.f;
      }
      asm volatile("setmaxnreg.inc.sync.aligned.u32 %0;" :: "n"(CREG));
      const uint32_t ah0 = pack_bf16(rs0, rs0), ah1 = pack_bf16(rs1, rs1), n0_ = pack_bf16(nb0, nb0), n1_ = pack_bf16(nb1, nb1);
      const uint32_t al0 = pack_bf16(rs0 - bf_lo(ah0), rs0 - bf_lo(ah0)), al1 = pack_bf16(rs1 - bf_lo(ah1), rs1 - bf_lo(ah1));
#pragma unroll
      for (int i = 0; i < 32; i++) {
        hq[2 * i] = hfma2(hq[2 * i], ah0, hfma2(hq[2 * i], al0, n0_));
        hq[2 * i + 1] = hfma2(hq[2 * i + 1], ah1, hfma2(hq[2 * i + 1], al1, n1_));
      }
      bar_sync(8 + wg, 160);
      if (own) {
        const float ks = __uint_as_float(__float_as_uint(KS) + lds32(sb + SM_GE));
        const uint32_t ks2 = pack_bf16(ks, ks);
        const float e0 = fmaf(bf_hi(__shfl_sync(0xffffffffu, hq[62], lane | 3)), -0.5f * ks, KC), e1 = fmaf(bf_hi(__shfl_sync(0xffffffffu, hq[63], lane | 3)), -0.5f * ks, KC);
#pragma unroll
        for (int k = 0; k < 16; k++)
          stsm4(frag(k), hfma2(hq[4 * k], ks2, KC2), hfma2(hq[4 * k + 1], ks2, KC2),
                k < 15 ? hfma2(hq[4 * k + 2], ks2, KC2) : pack_bf16(fmaf(bf_lo(hq[62]), ks, e0), t == 3 ? KC : fmaf(bf_hi(hq[62]), ks, e0)),
                k < 15 ? hfma2(hq[4 * k + 3], ks2, KC2) : pack_bf16(fmaf(bf_lo(hq[63]), ks, e1), t == 3 ? KC : fmaf(bf_hi(hq[63]), ks, e1)));
      }
      __syncwarp();
      if (lane == 0) mbar_arrive(sb + B_EVH);
      STAMP(st0, wg, 1);
    };

    float o[128];
    int qph = 0, st = tail ? wg : 0, ph = 0;
    auto release = [&](int stg) { if (lane == 0) mbar_arrive(sb + B_EMPTY + 8 * stg); };
    int resume = total > 0 ? -1 : 0;
    auto fill = [&]() __attribute__((always_inline)) {
#pragma unroll
      for (int i = 0; i < 32; i++)
        asm volatile("ld.volatile.shared.v4.f32 {%0,%1,%2,%3}, [%4];" : "=f"(o[4 * i]), "=f"(o[4 * i + 1]), "=f"(o[4 * i + 2]), "=f"(o[4 * i + 3]) : "r"(sb) : "memory");
    };
    auto finish = [&]() __attribute__((always_inline)) {
      STAMP(st0, wg, 11);
      DUMP(st0, wg, 0, 16);
      if (!P.zero) { asm volatile("exit;"); __builtin_unreachable(); }
      fill();
    };
    auto run = [&](auto hot_) __attribute__((always_inline)) {
    constexpr bool HOT = hot_.value;
    const int nloc = P.w[cta_id()].nloc;
    if (!HOT && resume == 0) {
#pragma unroll 1
      for (int i = 0; i < 32; i++) {
        const int r = i * 8 + wg * 4 + warp;
        cp_async16(sb + ((POS_M >> (r >> 6) * 4) & 15) * 32768 + sw_byte(r & 63, lane * 8), (const uint4*)P.wout + r * 32 + lane);
      }
    }
    bool wide = false;
    if (HOT) {
      reg_fence(hq);
      auto qstep = [&](auto k_) {
        constexpr int k = k_.value;
        if (k < 2 || k % 4 == 0) { mbar_wait(k == 0 ? sb + B_M0 : sb + B_WF + 2 * (k & ~3), 0); if (k == 0 || k == 4) bar_sync(5 + wg, 256); wg_fence(); }
        if constexpr (k == 0) wgmma_rs_n256_tb_first<0>(o, hq[0], hq[1], hq[2], hq[3], desc_m(sb, (POS_M & 15) * 2048));
        else wgmma_rs_n256_tb<(k & 3) * 512>(o, hq[4 * k], hq[4 * k + 1], hq[4 * k + 2], hq[4 * k + 3], desc_m(sb, ((POS_M >> (k & ~3)) & 15) * 2048), 1);
      };
      static_for<0, 4>(qstep);
      wg_commit();
      bar_arrive(6 - wg, 256);
      wg_wait<0>();
      if (!tail) release(0);
      static_for<4, 16>(qstep);
      wg_commit();
      bar_arrive(6 - wg, 256);
      wg_wait<0>();
      reg_fence(o); reg_fence(hq);
      if (!tail) release(1);
      STAMP(st0, wg, 2);
      float c0 = (o[124] + (t == 3 ? 2.f : 1.f) * o[125]) * (-0.5f / 4.5f), c1 = (o[126] + (t == 3 ? 2.f : 1.f) * o[127]) * (-0.5f / 4.5f);
      c0 += __shfl_xor_sync(0xffffffffu, c0, 1); c1 += __shfl_xor_sync(0xffffffffu, c1, 1);
      c0 += __shfl_xor_sync(0xffffffffu, c0, 2); c1 += __shfl_xor_sync(0xffffffffu, c1, 2);
      float r0 = t == 3 ? 0.f : o[125], r1 = t == 3 ? 0.f : o[127], r2 = o[124], r3 = o[126];
#pragma unroll
      for (int i = 0; i < 31; i++) { r2 += o[4 * i]; r0 += o[4 * i + 1]; r3 += o[4 * i + 2]; r1 += o[4 * i + 3]; }
      r0 += r2; r1 += r3;
      r0 += __shfl_xor_sync(0xffffffffu, r0, 1); r1 += __shfl_xor_sync(0xffffffffu, r1, 1);
      r0 += __shfl_xor_sync(0xffffffffu, r0, 2); r1 += __shfl_xor_sync(0xffffffffu, r1, 2);
      wide = !(fabsf(c0) <= SAFE_C / KS) || !(fabsf(c1) <= SAFE_C / KS);
      const float ig = __uint_as_float(0x3f800000u - lds32(sb + SM_GE));
      c0 *= ig; c1 *= ig;
      r0 = fmaf(c0, -255.f, fmaf(r0, -ig, PSH / KC)); r1 = fmaf(c1, -255.f, fmaf(r1, -ig, PSH / KC));
      if (own) mbar_wait(sb + B_HRD, 0);
#pragma unroll
      for (int k = 0; k < 16; k++)
        stsm4(frag(k),
              pack_bf16(fmaf(o[8 * k], ig, c0), fmaf(o[8 * k + 1], ig, c0)), pack_bf16(fmaf(o[8 * k + 2], ig, c1), fmaf(o[8 * k + 3], ig, c1)),
              pack_bf16(fmaf(o[8 * k + 4], ig, c0), k == 15 && t == 3 ? r0 : fmaf(o[8 * k + 5], ig, c0)),
              pack_bf16(fmaf(o[8 * k + 6], ig, c1), k == 15 && t == 3 ? r1 : fmaf(o[8 * k + 7], ig, c1)));
      fence_async_smem();
      __syncwarp();
      STAMP(st0, wg, 3);
      if (tail) { bar_sync(7, 256); if (wg == 0) { release(0); release(1); release(2); } }
      }

    if (HOT || (resume && resume < 4)) {
      ROLE;
      float m0, m1;
      const int qh = tail ? 0 : wg, tl = tail;
      uint32_t qo = qh * 2048;
      const uint32_t ko = (2 - tl) * 2048, stop = 1 + tl + (uint32_t)P.zero;
      float l0, l1;
      auto row_sums = [&]() { l0 = __shfl_sync(0xffffffffu, o[125] + 0.f, lane | 3); l1 = __shfl_sync(0xffffffffu, o[127] + 0.f, lane | 3); };
#define PART(u) make_uint4(pack_bf16(o[8 * u] - l0, o[8 * u + 1] - l0), pack_bf16(o[8 * u + 2] - l1, o[8 * u + 3] - l1), \
                           pack_bf16(o[8 * u + 4] - l0, o[8 * u + 5] - l0), pack_bf16(o[8 * u + 6] - l1, o[8 * u + 7] - l1))
      bool unsafe = !HOT;
      m0 = m1 = 0.f;
#pragma unroll 1
      for (int seg = HOT ? 0 : resume - 1; seg < 2; seg++) {
        ROLE;
        const bool last = __any_sync(0xffffffffu, seg || n1 == 0);
        m0 = m1 = !HOT && unsafe ? -INFINITY : 0.f;
        int first = 1;
        auto tile = [&](auto n_, bool endseg) __attribute__((always_inline)) -> bool {
          constexpr int N = n_.value;
          float s[N / 2]; uint32_t p[N / 4];
          if (!mbar_try_wait(sb + B_FULL + 8 * st, ph)) mbar_wait(sb + B_FULL + 8 * st, ph);
          const bool again = !HOT && N == 112 && first && !seg;
          if (HOT || N == 128) bar_sync(5 + wg, 256);
          else asm volatile("{\n.reg .pred p;\nsetp.eq.u32 p, %1, 0;\n@p bar.sync %0, 256;\n}\n" :: "r"(5 + wg), "r"((uint32_t)again) : "memory");
          wg_fence();
          const uint64_t dQ = desc_k(sb + SM_Q, qo), dK = desc_k(sb, ko + st * 4096);
          qo += (uint32_t)P.zero;
          static_for<0, 16>([&](auto k) { constexpr int off = (k.value >> 2) * 64 + (k.value & 3) * 2; wgmma_qk<off, off>(s, dQ, dK, k.value > 0); });
          wg_commit();
          if (HOT || N == 128) bar_arrive(6 - wg, 256);
          else asm volatile("{\n.reg .pred p;\nsetp.eq.u32 p, %1, 0;\n@p bar.arrive %0, 256;\n}\n" :: "r"(6 - wg), "r"((uint32_t)again) : "memory");
          if (HOT && N == 112 && first && !seg) {
            float a0 = 0.f, a1 = 0.f, a2 = 0.f, a3 = 0.f;
#pragma unroll
            for (int i = 0; i < 32; i++) { a0 += o[4 * i] * o[4 * i]; a2 += o[4 * i + 1] * o[4 * i + 1]; a1 += o[4 * i + 2] * o[4 * i + 2]; a3 += o[4 * i + 3] * o[4 * i + 3]; }
            a0 += a2; a1 += a3;
            a0 += __shfl_xor_sync(0xffffffffu, a0, 1); a1 += __shfl_xor_sync(0xffffffffu, a1, 1);
            a0 += __shfl_xor_sync(0xffffffffu, a0, 2); a1 += __shfl_xor_sync(0xffffffffu, a1, 2);
            unsafe = __any_sync(0xffffffffu, bar_red_or(tail ? 7 : 1 + wg, tail ? 256 : 128, wide || !(a0 <= SAFE_N2 / (KS * KS)) || !(a1 <= SAFE_N2 / (KS * KS))));
            if (lane == 0) { asm volatile("st.shared.u8 [%0], %1;" :: "r"(sb + SM_UNSAFE + wg), "r"((uint32_t)unsafe) : "memory"); mbar_arrive(sb + B_EVQ); }
          }
          STAMP(N == 112 && first && !seg && st0, wg, 0);
          wg_wait<0>();
          reg_fence(s);
          if (HOT && N == 112 && unsafe) return true;
          if (endseg) { if (lane == 0) mbar_arrive(sb + B_QEMPTY + 8 * wg); }
          if (!HOT && unsafe) {
            float a0 = fmaxf(s[0], s[1]), a1 = fmaxf(s[2], s[3]);
#pragma unroll
            for (int i = 1; i < N / 8; i++) { a0 = fmaxf(a0, fmaxf(s[4 * i], s[4 * i + 1])); a1 = fmaxf(a1, fmaxf(s[4 * i + 2], s[4 * i + 3])); }
            if (__any_sync(0xffffffffu, (a0 > m0 + TAU) || (a1 > m1 + TAU))) {
              a0 = fmaxf(a0, __shfl_xor_sync(0xffffffffu, a0, 1)); a1 = fmaxf(a1, __shfl_xor_sync(0xffffffffu, a1, 1));
              a0 = fmaxf(a0, __shfl_xor_sync(0xffffffffu, a0, 2)); a1 = fmaxf(a1, __shfl_xor_sync(0xffffffffu, a1, 2));
              const float x0 = ceilf(fmaxf(m0, a0)), x1 = ceilf(fmaxf(m1, a1)), sc0 = ex2(m0 - x0), sc1 = ex2(m1 - x1);
              m0 = x0; m1 = x1;
#pragma unroll
              for (int i = 0; i < 32; i++) { o[4 * i] *= sc0; o[4 * i + 1] *= sc0; o[4 * i + 2] *= sc1; o[4 * i + 3] *= sc1; }
            }
#pragma unroll
            for (int i = 0; i < N / 8; i++) { s[4 * i] -= m0; s[4 * i + 1] -= m0; s[4 * i + 2] -= m1; s[4 * i + 3] -= m1; }
          }
          auto pv = [&](auto k) { wgmma_rs_n256_tb<k.value * 512 + (63 << 16)>(o, p[4 * k.value], p[4 * k.value + 1], p[4 * k.value + 2], p[4 * k.value + 3], dK, k.value > 0 || N == 128 ? 1 : !first); };
#pragma unroll
          for (int i = 0; i < 16; i++) { p[i] = pack_bf16(ex2(s[2 * i]), ex2(s[2 * i + 1])); asm volatile("" : "+r"(p[i]) :: "memory"); }
          reg_fence(o);
          do bar_sync(5 + wg, 256); while (P.zero);
          wg_fence();
          static_for<0, 4>(pv);
          wg_commit();
#pragma unroll
          for (int i = 16; i < N / 4; i++) { p[i] = pack_bf16(ex2(s[2 * i]), ex2(s[2 * i + 1])); asm volatile("" : "+r"(p[i]) :: "memory"); }
          wg_fence();
          static_for<4, N / 16>(pv);
          wg_commit();
          bar_arrive(6 - wg, 256);
          if (N == 128) { wg_wait<1>(); if (endseg && last) { if (lane == 0) mbar_arrive(sb + B_HALF); } }
          wg_wait<0>();
          reg_fence(o); reg_fence(p);
          release(st);
          if (st) { st--; ph ^= 1; } else st = stop;
          return false;
        };
#pragma unroll 1
        for (int left = tail ? 8 - wg : (seg ? W.nb1 : W.nb0); left > 0; left--) { if (tile(IC<112>{}, false)) { resume = 1; return; } STAMP(first && !seg && st0, wg, 4); first = 0; }
#pragma unroll 1
        for (int left = tail ? 32 + wg : (seg ? W.na1 : W.na0); left > 0; left--) tile(IC<128>{}, left == 1);
        STAMP(st0 && last, wg, 6);
        {
        ROLE;
        if (last && fin && !(tail && wg == 1)) break;
        row_sums();
        if (last) mbar_wait(sb + (tail ? B_QEMPTY : B_HALF), 0);
        const uint32_t sp = sb + (tail ? 0 : (last ? (posw >> 12) + wg : (wg ? 4 - 2 * st : 6))) * 32768, sm = sb + SM_ML + (tail ? 0 : wg) * 512;
#pragma unroll
        for (int u = 0; u < 16; u++) sts128(sp + (u * 128 + tid) * 16, PART(u));
        if (t == 0) {
          asm volatile("st.shared.v2.f32 [%0], {%1,%2};" :: "r"(sm + (warp * 16 + g) * 8), "f"(m0), "f"(l0) : "memory");
          asm volatile("st.shared.v2.f32 [%0], {%1,%2};" :: "r"(sm + (warp * 16 + g) * 8 + 64), "f"(m1), "f"(l1) : "memory");
        }
        __syncwarp();
        if (lane == 0) mbar_arrive(sb + B_EVP0 + 8 * wg);
        STAMP(st0 && last, wg, 7);
        if (last) break;
        mbar_wait(sb + B_QFULL + 8 * wg, qph); qph ^= 1;
        uint32_t u; asm volatile("ld.shared.u8 %0, [%1];" : "=r"(u) : "r"(sb + SM_UNSAFE + wg) : "memory");
        unsafe = __any_sync(0xffffffffu, u != 0);
        if (HOT && unsafe) { resume = 2; return; }
        }
      }

      if (P.w[cta_id()].role & R_FIN) {
        ROLE;
        if (!(tail && wg == 1)) {
        row_sums();
        const int rl = wg * 64 + warp * 16 + g;
        uint32_t a[64];
#pragma unroll
        for (int i = 0; i < 64; i++) a[i] = pack_bf16(o[2 * i] - (i & 1 ? l1 : l0), o[2 * i + 1] - (i & 1 ? l1 : l0));
        reg_fence(a);
        {
          float2 e0, e1;
          mbar_wait(sb + B_QFULL + 8 * wg, qph);
          asm volatile("ld.shared.v2.f32 {%0,%1}, [%2];" : "=f"(e0.x), "=f"(e0.y) : "r"(sb + SM_ML + rl * 8) : "memory");
          asm volatile("ld.shared.v2.f32 {%0,%1}, [%2];" : "=f"(e1.x), "=f"(e1.y) : "r"(sb + SM_ML + rl * 8 + 64) : "memory");
          STAMP(st0, wg, 7);
          uint32_t fb0 = 0x3f803f80u, fb1 = 0x3f803f80u;
          const float s0 = l0 + e0.y, s1 = l1 + e1.y;
          const bool odd = __any_sync(0xffffffffu, m0 != e0.x || m1 != e1.x || !(fmaxf(s0, s1) < 0x1p40f) || !(fminf(s0, s1) > 0x1p-40f));
          if (HOT && odd) { resume = 3; return; }
          uint4 v[16];
#pragma unroll
          for (int u = 0; u < 16; u++) v[u] = lds128(sQ + (u * 128 + tid) * 16);
          if (!HOT && odd) {
            const float x0 = fmaxf(m0, e0.x), x1 = fmaxf(m1, e1.x);
            const float d0 = fmaxf(m0 - x0, -1000.f), d1 = fmaxf(m1 - x1, -1000.f), f0 = fmaxf(e0.x - x0, -1000.f), f1 = fmaxf(e1.x - x1, -1000.f);
            l0 = l0 * ex2(d0) + e0.y * ex2(f0); l1 = l1 * ex2(d1) + e1.y * ex2(f1);
            const int E0 = fexp(l0), E1 = fexp(l1);
            const uint32_t fa0 = pow2_bf2((int)d0 - E0), fa1 = pow2_bf2((int)d1 - E1);
            fb0 = pow2_bf2((int)f0 - E0); fb1 = pow2_bf2((int)f1 - E1);
            l0 = __uint_as_float(__float_as_uint(l0) - (E0 << 23)); l1 = __uint_as_float(__float_as_uint(l1) - (E1 << 23));
#pragma unroll
            for (int i = 0; i < 32; i++) { a[2 * i] = hmul2(a[2 * i], fa0); a[2 * i + 1] = hmul2(a[2 * i + 1], fa1); }
          } else { l0 = s0; l1 = s1; }
#pragma unroll
          for (int u = 0; u < 16; u++) {
            a[4 * u] = hfma2(v[u].x, fb0, a[4 * u]); a[4 * u + 1] = hfma2(v[u].y, fb1, a[4 * u + 1]);
            a[4 * u + 2] = hfma2(v[u].z, fb0, a[4 * u + 2]); a[4 * u + 3] = hfma2(v[u].w, fb1, a[4 * u + 3]);
          }
        }
        float fs0, fs1;
        const float kl = __uint_as_float(__float_as_uint(KS / KC) + lds32(sb + SM_GE));
        asm("rcp.approx.ftz.f32 %0, %1;" : "=f"(fs0) : "f"(l0 * kl)); asm("rcp.approx.ftz.f32 %0, %1;" : "=f"(fs1) : "f"(l1 * kl));
        STAMP(st0, wg, 8);
        reg_fence(a);
        bar_sync(5 + wg, 256);
        uint64_t dW[4];
        float y0[64], y1[64];
        auto half0 = [&](auto u_) {
          constexpr int u = u_.value;
          if (u % 4 == 0) { mbar_wait(sb + B_WF + 2 * u, 1); wg_fence(); dW[u / 4] = desc_mn(sb, ((posw >> u) & 15) * 2048); }
          wgmma_rs_n128_tb<(u & 3) * 512>(y0, a[4 * u], a[4 * u + 1], a[4 * u + 2], a[4 * u + 3], dW[u / 4], u != 0);
        };
        auto half1 = [&](auto u_) {
          constexpr int u = u_.value;
          wgmma_rs_n128_tb<(u & 3) * 512 + 128>(y1, a[4 * u], a[4 * u + 1], a[4 * u + 2], a[4 * u + 3], dW[u / 4], u != 0);
        };
        const bool wr = W.q0 * 128 + wg * 64 + warp * 16 < NN;
        uint4* po = (uint4*)(P.out + (size_t)(W.q0 * 128 + rl) * 256) + t;
        auto emit = [&](const float* y, uint4* dst) {
          if (wr) {
            red_bf16x8(dst, make_uint4(pack_bf16(y[0] * fs0, y[1] * fs0), pack_bf16(y[4] * fs0, y[5] * fs0), pack_bf16(y[8] * fs0, y[9] * fs0), pack_bf16(y[12] * fs0, y[13] * fs0)));
            red_bf16x8(dst + 8 * 32, make_uint4(pack_bf16(y[2] * fs1, y[3] * fs1), pack_bf16(y[6] * fs1, y[7] * fs1), pack_bf16(y[10] * fs1, y[11] * fs1), pack_bf16(y[14] * fs1, y[15] * fs1)));
          }
          wg_fence();
        };
        static_for<0, 16>(half0);
        wg_commit();
        static_for<0, 4>(half1);
        wg_commit();
        wg_wait<1>();
        reg_fence(y0);
        emit(y0, po); static_for<4, 8>(half1);
        emit(y0 + 16, po + 4); static_for<8, 12>(half1);
        emit(y0 + 32, po + 8); static_for<12, 16>(half1);
        wg_commit();
        bar_arrive(6 - wg, 256);
        emit(y0 + 48, po + 12);
        wg_wait<0>();
        reg_fence(a); reg_fence(y1);
        STAMP(st0, wg, 9);
#pragma unroll
        for (int u = 0; u < 4; u++) emit(y1 + 16 * u, po + 16 + 4 * u);
        }
        if (!tail) { STAMP(st0, wg, 11); DUMP(st0, wg, 0, 16); asm volatile("exit;"); __builtin_unreachable(); }
        if (wg == 1) { bar_sync(6, 256); bar_arrive(5, 256); } else qph ^= 1;
        __syncwarp();
        if (lane == 0) mbar_arrive(sb + B_QEMPTY + 8 * wg);
        fill();
        resume = 4;
      }
        }
#pragma unroll 1
    for (int step = HOT || resume ? 0 : -4; step < (HOT && resume == 4 ? 0 : nloc); step++) {
      ROLE;
      const bool helper = HOT || (resume && resume < 4);
      const bool isw = !HOT && step < 0;
      if (isw) {
        const uint4* src = (const uint4*)(step < -2 ? P.wmsg : P.wv) + ((step & 1) * 128 + wg * 64 + warp) * 32 + lane;
        float cw[8] = {0.f, 0.f, 0.f, 0.f, 0.f, 0.f, 0.f, 0.f};
#pragma unroll 1
        for (int i = 0; i < 16; i++) cp_async16(sQ + sw_byte(i * 4 + warp, lane * 8), src + i * 128);
        cp_commit();
#pragma unroll
        for (int i = 0; i < 8; i++) {
          const uint4 v = __ldg((const uint4*)(step < -2 ? P.wmsg : P.wv) + (248 + i) * 32 + lane);
          const float k = step < -2 ? 0.f : (i == 7 ? -1.0f / 4.5f : -0.5f / 4.5f);
          cw[0] += bf_lo(v.x) * k; cw[1] += bf_hi(v.x) * k; cw[2] += bf_lo(v.y) * k; cw[3] += bf_hi(v.y) * k;
          cw[4] += bf_lo(v.z) * k; cw[5] += bf_hi(v.z) * k; cw[6] += bf_lo(v.w) * k; cw[7] += bf_hi(v.w) * k;
        }
        asm volatile("cp.async.wait_group 0;" ::: "memory");
#pragma unroll 1
        for (int i = 0; i < 16; i++) {
          const uint32_t ad = sQ + sw_byte(i * 4 + warp, lane * 8);
          const uint4 v = lds128(ad);
          uint4 w4 = make_uint4(pack_bf16(bf_lo(v.x) + cw[0], bf_hi(v.x) + cw[1]), pack_bf16(bf_lo(v.y) + cw[2], bf_hi(v.y) + cw[3]),
                                pack_bf16(bf_lo(v.z) + cw[4], bf_hi(v.z) + cw[5]), pack_bf16(bf_lo(v.w) + cw[6], bf_hi(v.w) + cw[7]));
          if (step == -1 && wg * 64 + i * 4 + warp == 127) w4 = make_uint4(0, 0, 0, 0);
          sts128(ad, w4);
        }
        fence_async_smem();
        bar_sync(7, 256);
      } else {
        SSTAMP(0);
        mbar_wait(sb + B_QFULL + 8 * wg, qph); qph ^= 1;
        STAMP(st0 && step == 0, wg, 8);
        SSTAMP(1);
        bar_sync(5 + wg, 256);
        SSTAMP(2);
      }
#pragma unroll 1
      for (int c = 0; c < 4; c++) {
        if (step == 0) mbar_wait(sb + B_WF + 8 * c, helper);
        const int turn2 = helper ? 3 : 4;
        if (c == turn2) bar_sync(5 + wg, 256);
        wg_fence();
        const uint64_t dA = desc_k(sb + SM_Q, wg * 2048 + c * 64), dW = desc_mn(sb, ((posw >> c * 4) & 15) * 2048);
        static_for<0, 4>([&](auto k) { wgmma_ss_n256_tb<k.value * 2, k.value * 512>(o, dA, dW, k.value > 0 ? 1 : c); });
        wg_commit();
        if ((c == 3 || c == turn2 - 1) && !isw) bar_arrive(6 - wg, 256);
        wg_wait<1>();
      }
      wg_wait<0>();
      reg_fence(o);
      {
        STAMP(st0 && step == 0, wg, 9);
        SSTAMP(3);
        if (isw) bar_sync(1 + wg, 128); else if (lane == 0) mbar_arrive(sb + B_QEMPTY + 8 * wg);
        uint8_t* dw = (uint8_t*)(step < -2 ? g_Wmo : g_Wvo) + ((step & 1) * 2 + wg) * 32768 + warp * 8192 + g * 128;
        const int row0 = (W.loc0 + step) * 128 + wg * 64 + warp * 16;
        uint4 r[16];
#pragma unroll
        for (int u = 0; u < 8; u++) { r[2 * u] = ROW0(u); r[2 * u + 1] = ROW1(u); }
        if (isw) {
#pragma unroll
          for (int u = 0; u < 16; u++) *(uint4*)(dw + (u >> 2) * 1024 + ((((u & 2) * 2 + t) ^ g) << 4) + (u & 1) * 4096) = r[u];
        } else if (row0 < NN) {
          uint4* po = (uint4*)(P.out + (size_t)(row0 + g) * 256) + t;
          uint32_t c1 = clk();
#pragma unroll
          for (int u = 0; u < 16; u++) {
            red_bf16x8(po + (u >> 1) * 4 + (u & 1) * 256, r[u]);
            if (!HOT) { c1 += PACE; while ((int)(clk() - c1) < 0) {} }
          }
        }
        if (!HOT && step == -1) { bar_sync(7, 256); if (tid_is(0)) flag_release(F_W); __syncwarp(); STAMP(st0, wg, 3); }
      }
    }
    if (HOT && resume == 4) return;
    finish();
    };
    if (total == 0) {
      start();
      asm volatile("setmaxnreg.inc.sync.aligned.u32 %0;" :: "n"(CREG));
      fill();
    } else {
      layernorm();
      run(std::true_type{});
    }
    run(std::false_type{});
    asm volatile("setmaxnreg.dec.sync.aligned.u32 %0;" :: "n"(504 - 2 * CREG));
  } else {
    STAMP(lane == 0 && warp == 0, 2, 0);
        const int mi = cta >> 3;
    const uint32_t sW = sb + 3 * 32768;
    uint4 wa[4], wb[8];
    {
      const uint4* pq = (const uint4*)(P.wq + ((mi & 15) * 16 + g) * 256) + warp * 8 + t;
      const uint4* pk = (const uint4*)(P.wk + ((cta & 7) * 32 + g) * 256) + warp * 8 + t;
#pragma unroll
      for (int i = 0; i < 4; i++) wa[i] = __ldg(pq + (i >> 1) * 256 + (i & 1) * 4);
#pragma unroll
      for (int i = 0; i < 8; i++) wb[i] = __ldg(pk + (i >> 1) * 256 + (i & 1) * 4);
    }
    if (threadIdx.x == 352) {
      for (int i = 0; i < 3; i++) { mbar_init(sb + B_FULL + 8 * i, 1); mbar_init(sb + B_EMPTY + 8 * i, cta == 130 ? 4 : 8); }
      for (int i = 0; i < 4; i++) mbar_init(sb + B_WF + 8 * i, 1);
      for (int i = 0; i < 2; i++) { mbar_init(sb + B_QFULL + 8 * i, 1); mbar_init(sb + B_QEMPTY + 8 * i, 4); mbar_init(sb + B_EVP0 + 8 * i, 4); }
      mbar_init(sb + B_EVH, 8); mbar_init(sb + B_EVQ, 8); mbar_init(sb + B_HALF, 8); mbar_init(sb + B_BG, 1); mbar_init(sb + B_M0, 1); mbar_init(sb + B_HRD, 1);
      asm volatile("fence.mbarrier_init.release.cluster;" ::: "memory");
    }
    __syncwarp();
    do bar_sync(4, 384); while (P.zero);
    {
#pragma unroll
      for (int n = 0; n < 4; n++) {
        float c[4] = {0.f, 0.f, 0.f, 0.f};
#pragma unroll
        for (int u = 0; u < 2; u++) {
          mma16816(c, wa[u].x, wa[2 + u].x, wa[u].y, wa[2 + u].y, wb[2 * n + u].x, wb[2 * n + u].y);
          mma16816(c, wa[u].z, wa[2 + u].z, wa[u].w, wa[2 + u].w, wb[2 * n + u].z, wb[2 * n + u].w);
        }
        asm volatile("st.shared.v2.f32 [%0], {%1,%2};" :: "r"(sW + ((warp * 16 + g) * 40 + n * 8 + 2 * t) * 4), "f"(c[0]), "f"(c[1]) : "memory");
        asm volatile("st.shared.v2.f32 [%0], {%1,%2};" :: "r"(sW + ((warp * 16 + g + 8) * 40 + n * 8 + 2 * t) * 4), "f"(c[2]), "f"(c[3]) : "memory");
      }
      STAMP(lane == 0 && warp == 0, 2, 7);
      bar_sync(3, 128);
      if (warp < 2) {
        float c[8] = {0.f, 0.f, 0.f, 0.f, 0.f, 0.f, 0.f, 0.f};
#pragma unroll
        for (int k = 0; k < 4; k++) {
          const uint4 v = lds128(sW + ((k * 16 + warp * 8 + g) * 40 + t * 8) * 4), w = lds128(sW + ((k * 16 + warp * 8 + g) * 40 + t * 8 + 4) * 4);
          c[0] += __uint_as_float(v.x); c[1] += __uint_as_float(v.y); c[2] += __uint_as_float(v.z); c[3] += __uint_as_float(v.w);
          c[4] += __uint_as_float(w.x); c[5] += __uint_as_float(w.y); c[6] += __uint_as_float(w.z); c[7] += __uint_as_float(w.w);
        }
        const float ms = 1.4426950408889634f / 16.0f / KS;
        const uint4 m4 = make_uint4(pack_bf16(c[0] * ms, c[1] * ms), pack_bf16(c[2] * ms, c[3] * ms), pack_bf16(c[4] * ms, c[5] * ms), pack_bf16(c[6] * ms, c[7] * ms));
        sts128(sW + 16384 + (warp * 8 + g) * 64 + ((t ^ (g >> 1)) << 4), m4);
      }
    }
    asm volatile("setmaxnreg.dec.sync.aligned.u32 %0;" :: "n"(504 - 2 * CREG));
    STAMP(lane == 0 && warp == 0, 2, 13);
    bar_sync(3, 128);
#define ep1 (lds32(sb + SM_EPOCH) + 1)
    if (threadIdx.x == 256 && cta < 128) {
      fence_async_smem();
      bulk_s2g(g_M + cta * 64, sW + 16384, 1024);
      bulk_commit();
      bulk_wait_all();
      red_relaxed(g_flag + F_M + (cta >> 5));
    }
    if (warp == 2 && cta < 131) {
      uint2 f;
#pragma unroll 1
      for (uint32_t it = 0; it < (1u << 23); it++) {
        __nanosleep(150);
        asm volatile("ld.relaxed.gpu.global.v2.u32 {%0,%1}, [%2];" : "=r"(f.x), "=r"(f.y) : "l"(g_flag + F_EPOCH) : "memory");
        if (__all_sync(0xffffffffu, f.y >> 4 == ((f.x + 1) & 0xfffffff))) break;
      }
      asm volatile("st.shared.u32 [%0], %1;" :: "r"(sb + SM_GE), "r"((f.y & 15) << 23) : "memory");
      bar_arrive(8, 160); bar_arrive(9, 160);
    }
    __syncwarp();
    ROLE;
    if (warp == 3 && W.own) {
      mbar_wait_w(sb + B_EVH, 0);
      if (W.role < R_SIG) mbar_wait_w(sb + B_WF + 8, 0);
      if (lane == 0) {
        fence_async_smem();
        const int h0 = W.own == 2, nh = W.own == 3 ? 2 : 1;
        bulk_s2g(g_h + W.hp * 4096 + h0 * 2048, sb + SM_Q + h0 * 32768, nh * 32768);
        bulk_s2g(g_stat + W.q0 * 128 + h0 * 64, sb + SM_ML + h0 * 512, nh * 512);
        bulk_commit();
        bulk_wait_read();
        mbar_arrive(sb + B_HRD);
        bulk_wait_all();
        if (W.role >= R_SIG) red_relaxed(g_flag + F_H1 - 1 + W.role / R_SIG);
        red_relaxed(g_flag + F_H);
      }
      __syncwarp();
      STAMP(lane == 0, 2, 6);
    }
    if (warp == 0) {
      if (lane == 0) {
        STAMP(true, 2, 1);
        const uint32_t epoch = ld_relaxed(g_flag + F_EPOCH);
        if (total > 0) {
#pragma unroll
          for (int c = 0; c < 3; c++) mbar_expect_tx(sb + B_WF + 8 * c, c == 0 ? WCH_B - 8192 : WCH_B);
          mbar_expect_tx(sb + B_M0, 8192);
          int c = 0;
#pragma unroll 1
          for (uint32_t it = 0; c < 4; it++) {
            uint4 f;
            asm volatile("ld.relaxed.gpu.global.v4.u32 {%0,%1,%2,%3}, [%4];" : "=r"(f.x), "=r"(f.y), "=r"(f.z), "=r"(f.w) : "l"(g_flag + F_M) : "memory");
            uint32_t tm;
            asm volatile("mad.lo.u32 %0, %1, 32, 32;" : "=r"(tm) : "r"(epoch));
            int ok = (int)(f.x - tm) < 0 ? 0 : (int)(f.y - tm) < 0 ? 1 : (int)(f.z - tm) < 0 ? 2 : (int)(f.w - tm) < 0 ? 3 : 4;
            if (it > (1u << 23)) ok = 4;
            if (ok > c) {
              asm volatile("fence.acquire.gpu;" ::: "memory"); fence_async_gmem();
              if (c == 0) bulk_g2s(sb + (POS_M & 15) * 32768, g_M, 8192, sb + B_M0);
            }
#pragma unroll 1
            for (; c < ok; c++) {
              const uint32_t skip = c == 0 ? 8192 : 0;
              bulk_g2s(sb + ((POS_M >> c * 4) & 15) * 32768 + skip, pofs<const uint8_t>(g_M, c * WCH_B + skip), WCH_B - skip, sb + B_WF + 8 * c);
              STAMP(c == 0, 2, 2);
            }
          }
        }
        asm volatile("st.shared.u32 [%0], %1;" :: "r"(sb + SM_EPOCH), "r"(epoch) : "memory");
        if (total > 0) mbar_expect_tx(sb + B_WF + 24, WCH_B);
        int st = 0, ph = 0, qph = 0;
        const int nsl = tail ? 3 : 2;
        auto next_slot = [&]() { mbar_wait(sb + B_EMPTY + 8 * st, ph); if (++st == nsl) { st = 0; ph ^= 1; } };
        const uint4* wsrc = fin ? g_Wvo : g_Wmo;
        auto w_load = [&](int c0, int c1) {
#pragma unroll 1
          for (int c = c0; c < c1; c++) {
            mbar_expect_tx(sb + B_WF + 8 * c, WCH_B);
            bulk_g2s(sb + ((posw >> c * 4) & 15) * 32768, pofs<const uint8_t>(wsrc, c * WCH_B), WCH_B, sb + B_WF + 8 * c);
          }
        };
        auto q_load = [&](const uint4* src, bool wait_empty) {
#pragma unroll 1
          for (int h = 0; h < 2; h++) {
            if (wait_empty) mbar_wait(sb + B_QEMPTY + 8 * h, qph);
            mbar_expect_tx(sb + B_QFULL + 8 * h, 32768);
            bulk_g2s_last(sb + SM_Q + h * 32768, src + h * 2048, 32768, sb + B_QFULL + 8 * h);
          }
          if (wait_empty) qph ^= 1;
        };
        auto part_out = [&](int slot, int h, uint32_t region, int parity) {
          mbar_wait(sb + B_EVP0 + 8 * h, parity);
          fence_async_smem();
          bulk_s2g(g_part + slot * 4096 + h * 2048, sb + region * 32768, 32768);
          bulk_s2g(g_ml + slot * 128 + h * 64, sb + SM_ML + h * 512, 512);
          bulk_commit();
        };
        auto announce = [&](int f) {
          red_relaxed(g_flag + f);
        };
        if (total > 0) {
          STAMP(true, 2, 3);
          const int q1 = W.q0 + 2 * W.own - 3;
          if (!tail) { flag_wait(F_H1 + (fin ? 0 : W.own), (epoch + 1) * (fin ? NH1_0 : (W.own == 1 ? NH1_1 : NH1_2))); fence_async_gmem(); }
          STAMP(true, 2, 4);
          uint32_t ko = W.k0 * 8192, t0 = 0, dly = 0;
#pragma unroll 1
          for (int j = 0; j < total; j++) {
            const int fw = j == (tail ? 0 : 1) ? F_H : (j == n0 ? F_QP + q1 * LN_ : (j == total - 1 ? F_W : -1));
            if (fw >= 0) { flag_wait(fw, (epoch + 1) * (fw == F_H ? NHSIG : 1)); fence_async_gmem(); }
            if (j == n0) {
              const uint32_t u = __ldcg(g_unsafe + q1);
              asm volatile("st.shared.u32 [%0], %1;" :: "r"(sb + SM_UNSAFE), "r"(u) : "memory");
              ko = W.k1 * 8192;
            }
            if (j == n0 + 1) q_load(g_qp + q1 * 4096, true);
            if (j == total - 1 && !tail) w_load(0, 1);
            const uint32_t bytes = (j < n0 ? j < W.nb0 : j - n0 < W.nb1) ? 112 * 512 : 128 * 512, s0 = st;
            const uint32_t region = (tail ? 1 : 2) + 2 * s0, skip = j == n0 + 1 ? 32768 : 0;
            if (skip) part_out(W.slotA, 0, 6, 0);
            const int js = tail ? 0 : (j < n0 ? j : j - n0);
            unsigned long long* tm = (unsigned long long*)(g_flag + F_TM) + (fin ? 0 : (j < n0 ? W.own : 3));
            if ((js & 15) == 5) {
              dly = min(ld_relaxed((const uint32_t*)tm) - t0, 4096u) * 7 / 4;
              while (dly > ALN) dly -= ALN - 200;
            }
            if (js == 0 || j == total - 1) dly = 0;
            next_slot();
            if ((js & 15) == 3) {
              t0 = gtime();
              asm volatile("red.relaxed.gpu.global.max.u64 [%0], %1;" :: "l"(tm), "l"((unsigned long long)(epoch + 1) << 32 | t0) : "memory");
            }
            const uint32_t c1 = clk() + dly;
            while ((int)(c1 - clk()) > 400) __nanosleep(100);
            while ((int)(c1 - clk()) > 0) {}
            mbar_expect_tx(sb + B_FULL + 8 * s0, bytes);
            bulk_g2s(sb + region * 32768 + skip, pofs<const uint8_t>(g_h, ko + skip), bytes - skip, sb + B_FULL + 8 * s0);
            if (skip) {
              part_out(W.slotA, 1, region, 0);
              bulk_wait_read();
              bulk_g2s(sb + region * 32768, pofs<const uint8_t>(g_h, ko), skip, sb + B_FULL + 8 * s0);
              bulk_wait_all();
              announce(F_PART + W.slotA * LN_);
            }
            ko += bytes;
          }
          next_slot();
          if (tail) { next_slot(); next_slot(); }
        } else { flag_wait(F_W, (epoch + 1)); fence_async_gmem(); }
        STAMP(true, 2, 5);
        const bool staged = total > 0 && !tail;
        w_load(staged, staged ? (fin ? 2 : 3) : 4);
        if (tail) {
          mbar_wait(sb + B_BG, 0); mbar_wait(sb + B_EVP0 + 8, 0); mbar_arrive(sb + B_QFULL);
          qph = 1; wsrc = g_Wmo;
          mbar_wait(sb + B_QEMPTY, 1);
          w_load(0, 4);
        }
#pragma unroll 1
        for (int i = 0; i < W.nloc; i++) {
          const int tl = W.loc0 + i, last = tl * 128 + 127 < NN ? tl * 128 + 127 : NN - 1;
          flag_wait(F_AGG + ((last >= NGW) + (last >= 4 * NGW) + (last >= 9 * NGW)) * LN_, (epoch + 1) * NGW); fence_async_gmem();
          if (total == 0) g_flag[F_EPOCH] = epoch + 1;
          q_load(g_agg + tl * 4096, total > 0 || i > 0);
        }
        if (fin && !tail) {
          int h = 0, c = 2, have = W.slotB >= 0 ? 2 : 0;
          mbar_wait(sb + B_BG, 0);
#pragma unroll 1
          for (uint32_t it = 0; (h < 2 || c < 4) && it < (1u << 23); it++) {
            if (have < 2) {
              uint2 f;
              asm volatile("ld.relaxed.gpu.global.v2.u32 {%0,%1}, [%2];" : "=r"(f.x), "=r"(f.y) : "l"(g_flag + F_PART + W.slotA * LN_) : "memory");
              have = (int)(f.x - (epoch + 1)) < 0 ? 0 : ((int)(f.y - (epoch + 1)) < 0 ? 1 : 2);
            }
            if (h < have && mbar_try_wait_nb(sb + B_QEMPTY + 8 * h, 0)) {
              asm volatile("fence.acquire.gpu;" ::: "memory"); fence_async_gmem();
              STAMP(true, 2, 14 + h);
              mbar_expect_tx(sb + B_QFULL + 8 * h, 32768 + 512);
              bulk_g2s(sb + SM_ML + h * 512, g_ml + W.slotA * 128 + h * 64, 512, sb + B_QFULL + 8 * h);
              bulk_g2s(sb + SM_Q + h * 32768, g_part + W.slotA * 4096 + h * 2048, 32768, sb + B_QFULL + 8 * h);
              h++;
            }
            const bool half = mbar_try_wait_nb(sb + B_HALF, 0);
            const int c1 = half ? 4 : (h > 0 ? 3 : 2);
            if (c < c1) { w_load(c, c1); c = c1; }
          }
        } else if (!fin && total > 0) {
#pragma unroll 1
          for (int h = 0; h < 2; h++) part_out(W.slotB, h, (posw >> 12) + h, 1);
          asm volatile("cp.async.bulk.wait_group.read 1;" ::: "memory");
          w_load(3, 4);
          asm volatile("cp.async.bulk.wait_group 1;" ::: "memory");
          announce(F_PART + W.slotB * LN_);
          STAMP(true, 2, 14);
          bulk_wait_all();
          announce(F_PART + W.slotB * LN_ + 1);
          STAMP(true, 2, 15);
        }
        DUMP(true, 2, 14, 16);
        DUMP(true, 2, 0, 8);
      }
      return;
    }
  }
    {
      const int gw = cta * 3 + warp - 1;
      ROLE;
      if (total > 0) {
        mbar_wait_w(sb + B_EVQ, 0);
        const uint32_t c0 = clk();
        if (warp == 3 && W.own) {
          const uint4 s0 = lds128(sb + SM_ML + (W.own == 2) * 512 + lane * 16), s1 = lds128(sb + SM_ML + (W.own >> 1) * 512 + lane * 16);
          const float rm = __uint_as_float(min(min(s0.x, s0.z), min(s1.x, s1.z)));
          const uint32_t ex = __reduce_max_sync(0xffffffffu, __float_as_uint(fmaf(-1e-5f * rm, rm, 1.000001f)) >> 24);
          if (lane == 0) asm volatile("red.relaxed.gpu.global.max.u32 [%0], %1;" :: "l"(g_flag + F_RHO), "r"(ep1 * 64 + ex) : "memory");
          flag_release_w(F_RC);
        }
        if (warp == 1 && (W.role & R_PUB)) {
          g_unsafe[W.q0] = lds32(sb + SM_UNSAFE);
#pragma unroll 1
          for (int k = 0; k < 4; k++) {
            __nanosleep(1000);
            if (lane == 0) bulk_s2g(pofs<uint4>(g_qp, W.q0 * 65536 + k * 16384), sb + SM_Q + k * 16384, 16384);
            bulk_commit();
          }
          bulk_wait_all();
          flag_release_w(F_QP + W.q0 * LN_);
        }
        while (__any_sync(0xffffffffu, clk() - c0 < GSTART)) __nanosleep(500);
        STAMP(lane == 0 && warp == 1, 2, 8);
#define ovf_cnt pofs<uint32_t>(g_flag, (F_OVF + (ep1 & 1) * LN_) * 4)
        if (gw == 0) g_flag[F_OVF + ((ep1 + 1) & 1) * LN_] = 0;
#pragma unroll 1
        for (int e0 = gw * 32; e0 < NE; e0 += NGW * 32 * 7) {
          int d[7], s[7], pos[7];
          const int* pd = pofs<const int>(P.dst, (e0 + lane) * 4);
          const int* ps = pofs<const int>(P.src, (e0 + lane) * 4);
#pragma unroll
          for (int k = 0; k < 7; k++) { const bool ok = e0 + k * NGW * 32 < NE; d[k] = ok ? __ldcs(pd + k * NGW * 32) : -1; s[k] = ok ? __ldcs(ps + k * NGW * 32) : 0; }
          uint32_t ov = 0;
#pragma unroll
          for (int k = 0; k < 7; k++) {
            pos[k] = 0;
            if (d[k] >= 0) asm volatile("atom.relaxed.gpu.global.add.u32 %0, [%1], 1;" : "=r"(pos[k]) : "l"(pofs<int>(g_cnt, d[k] << 2)) : "memory");
            s[k] = (uint32_t)(uintptr_t)g_u + s[k] * 512;
            if (d[k] >= 0 && pos[k] < CAP) asm volatile("st.volatile.global.u32 [%0], %1;" :: "l"(pofs<int>(g_bin, (d[k] * CAPS + pos[k]) << 2)), "r"(s[k]) : "memory");
            ov |= (pos[k] >= CAP) << k;
          }
          if (__any_sync(0xffffffffu, ov != 0)) {
            uint32_t at;
            asm volatile("atom.relaxed.gpu.global.add.u32 %0, [%1], %2;" : "=r"(at) : "l"(ovf_cnt), "r"(__popc(ov)) : "memory");
#pragma unroll
            for (int k = 0; k < 7; k++) if ((ov >> k) & 1) g_ovf[at++] = make_int2(d[k], s[k]);
          }
        }
        flag_wait_w(F_RC, ep1 * NHSIG);
        const uint32_t ush = max(62 - (int)(__shfl_sync(0xffffffffu, ld_relaxed(g_flag + F_RHO), 0) & 63), 0) << 23;
        const float us = __uint_as_float(__float_as_uint(US) + ush);
#pragma unroll 1
        for (int n0 = gw; n0 < NN; n0 += 4 * NGW) {
          uint4 xv[4]; float2 st[4];
#pragma unroll
          for (int k = 0; k < 4; k++) {
            const int n = n0 + k * NGW < NN ? n0 + k * NGW : n0;
            xv[k] = ldcs_v(pofs<const uint4>(P.x, n * 512 + lane * 16));
            st[k] = __ldcg(pofs<const float2>(g_stat, n * 8));
          }
#pragma unroll
          for (int k = 3; k >= 0; k--) {
            const int n = n0 + k * NGW;
            const float a = st[k].x * us, c = fmaf(st[k].y, us, UB + 8388608.0f);
#define FIX(w) __byte_perm(__float_as_uint(fmaf(bf_lo(w), a, c)), __float_as_uint(fmaf(bf_hi(w), a, c)), 0x5410)
            if (n < NN) {
              *pofs<uint4>(P.out, n * 512 + lane * 16) = xv[k];
              *pofs<uint4>(g_u, n * 512 + lane * 16) = make_uint4(FIX(xv[k].x), FIX(xv[k].y), FIX(xv[k].z), FIX(xv[k].w));
            }
          }
        }
        flag_release_w(F_BIN);
        STAMP(lane == 0 && warp == 1, 2, 9);
        flag_wait_w(F_BIN, ep1 * NGW);
        STAMP(lane == 0 && warp == 1, 2, 10);
        const int myn = gw + lane * NGW < NN ? gw + lane * NGW : gw;
        int cnts = __ldcg(g_cnt + myn);
        cnts = gw + lane * NGW < NN ? (cnts > CAP ? CAP + 1 : cnts) | ((int)__ldg((const unsigned short*)P.dinv + myn) << 16) : 0;
        __syncwarp();
        g_cnt[myn] = 0;
        const uint32_t uhi = (uintptr_t)g_u >> 32, lx = lane * 16;
        uint32_t obin = gw * CAPS * 4;
        auto bin = [&](uint32_t ofs, int r, int first) {
          uint32_t en;
          asm volatile("{\n.reg .pred p;\nsetp.lt.u32 p, %2, %3;\nmov.u32 %0, 0;\n@p ld.global.cg.u32 %0, [%1];\n}\n"
                       : "=&r"(en) : "l"(pofs<const uint32_t>(g_bin, ofs + first * 4 + lx / 4)), "r"(lx + first * 16), "r"((__shfl_sync(0xffffffffu, cnts, r) & 0xffff) * 16) : "memory");
          return en;
        };
        uint32_t ent = bin(obin, 0, 0), entn = bin(obin + NGW * CAPS * 4, 1, 0);
        int cd = __shfl_sync(0xffffffffu, cnts, 0), cb = min(cd & 0xffff, CAP), e = 0;
        uint32_t sa[4] = {0, 0, 0, 0}, sh[4] = {0, 0, 0, 0};
        auto add = [&](uint32_t x, uint32_t y, uint32_t z, uint32_t w) {
          sa[0] += x; sa[1] += y; sa[2] += z; sa[3] += w;
          sh[0] += x >> 16; sh[1] += y >> 16; sh[2] += z >> 16; sh[3] += w >> 16;
        };
        int rnd = -1, rows = -1, cdo = 0;
#pragma unroll 1
        for (;;) {
          const bool hold = rows >= 0 && rnd == 8;
          const int m = hold ? 0 : cb - e;
          uint4 v[8];
          if (m >= 8) {
#pragma unroll
            for (int k = 0; k < 8; k++) v[k] = ldcg_v(addr64(__shfl_sync(0xffffffffu, ent, k) + lx, uhi));
          } else {
#pragma unroll
            for (int k = 0; k < 8; k++) {
              v[k] = make_uint4(0, 0, 0, 0);
              if (k < 7) ldcg_if(v[k], addr64(__shfl_sync(0xffffffffu, ent, k) + lx, uhi), k < m);
            }
          }
          if (rows >= 0) {
            const int n = gw + rnd * NGW;
            if (n < NN) {
              const float di = __uint_as_float(cdo & 0xffff0000u) * __uint_as_float(__float_as_uint(1.0f / US) - ush), nl = -di * UB * (float)rows;
#define AGG(k) pack_bf16(fmaf((float)(sa[k] - (sh[k] << 16)), di, nl), fmaf((float)sh[k], di, nl))
              *pofs<uint4>(g_agg, ((n >> 3) * 4096 + (n & 7) * 144) ^ ((lx & 0x70) | ((lx & 0x180) << 3))) = make_uint4(AGG(0), AGG(1), AGG(2), AGG(3));
            }
#pragma unroll
            for (int k = 0; k < 4; k++) sa[k] = sh[k] = 0;
            rows = -1;
            if (rnd == 0 || rnd == 3 || rnd == 8 || rnd == NRND - 1) flag_release_w(F_AGG + ((rnd > 0) + (rnd > 3) + (rnd > 8)) * LN_);
            if (rnd == NRND - 1) break;
            if (hold) {
              if (fin && W.slotB >= 0) {
#pragma unroll 1
                for (int k = 0; k < 2; k++) flag_wait_w(F_PART + (k ? W.slotB : W.slotA) * LN_, ep1);
#pragma unroll 1
                for (int b = warp - 1; b < 8; b += 3) {
                  float2* ma = g_ml + W.slotA * 128 + b * 16 + g;
                  const float2* mb = g_ml + W.slotB * 128 + b * 16 + g;
                  const float2 a0 = __ldcg(ma), a1 = __ldcg(ma + 8), b0 = __ldcg(mb), b1 = __ldcg(mb + 8);
                  const float x0 = fmaxf(a0.x, b0.x), x1 = fmaxf(a1.x, b1.x);
                  const float fa0 = ex2(a0.x - x0), fa1 = ex2(a1.x - x1), fb0 = ex2(b0.x - x0), fb1 = ex2(b1.x - x1);
                  __syncwarp();
                  if (t == 0) { ma[0] = make_float2(x0, a0.y * fa0 + b0.y * fb0); ma[8] = make_float2(x1, a1.y * fa1 + b1.y * fb1); }
                  const uint32_t ofs = ((b >> 2) * 2048 + (b & 3) * 32 + lane) * 16;
#pragma unroll 1
                  for (int u = 0; u < 16; u += 4) {
                    uint4* pa = pofs<uint4>(g_part, W.slotA * 65536 + ofs + u * 2048);
                    const uint4* pb = pofs<const uint4>(g_part, W.slotB * 65536 + ofs + u * 2048);
                    uint4 va[4], vb[4];
#pragma unroll
                    for (int k = 0; k < 4; k++) { va[k] = ldcg_v(pa + k * 128); vb[k] = ldcs_v(pb + k * 128); }
#define FOLD(w, fa, fb) pack_bf16(bf_lo(va[k].w) * fa + bf_lo(vb[k].w) * fb, bf_hi(va[k].w) * fa + bf_hi(vb[k].w) * fb)
#pragma unroll
                    for (int k = 3; k >= 0; k--) pa[k * 128] = make_uint4(FOLD(x, fa0, fb0), FOLD(y, fa1, fb1), FOLD(z, fa0, fb0), FOLD(w, fa1, fb1));
                  }
                }
                bar_sync(3, 96);
                if (warp == 1) asm volatile("fence.acq_rel.gpu;" ::: "memory");
              }
              if (fin && warp == 1 && lane == 0) mbar_arrive(sb + B_BG);
              while (__any_sync(0xffffffffu, clk() - c0 < GPAUSE)) __nanosleep(500);
              continue;
            }
          }
#define SUM8(f) (v[7].f + v[6].f + v[5].f + v[4].f + v[3].f + v[2].f + v[1].f + v[0].f)
          add(SUM8(x), SUM8(y), SUM8(z), SUM8(w));
          e += 8;
          if (e < cb) {
            ent = __shfl_down_sync(0xffffffffu, ent, 8);
            if (e == 32) ent = bin(obin, rnd + 1, 32);
            continue;
          }
          rnd++; rows = cb; cdo = cd;
          if ((cd & 0xffff) > CAP) {
            const int no = __shfl_sync(0xffffffffu, (int)ld_relaxed(ovf_cnt), 0);
#pragma unroll 1
            for (int i0 = 0; i0 < no; i0 += 32) {
              int2 en = __ldcg(g_ovf + min(i0 + lane, no - 1));
              uint32_t mk = __ballot_sync(0xffffffffu, en.x == gw + rnd * NGW && i0 + lane < no);
              rows += __popc(mk);
#pragma unroll 1
              while (mk) {
                const int bit = __ffs(mk) - 1; mk &= mk - 1;
                const uint4 r = ldcg_v(addr64((uint32_t)__shfl_sync(0xffffffffu, en.y, bit) + lx, uhi));
                add(r.x, r.y, r.z, r.w);
              }
            }
          }
          obin += NGW * CAPS * 4;
          ent = entn; entn = bin(obin + NGW * CAPS * 4, rnd + 2, 0);
          cd = __shfl_sync(0xffffffffu, cnts, rnd + 1); cb = min(cd & 0xffff, CAP); e = 0;
        }
      }
      STAMP(lane == 0 && warp == 1, 2, 11);
      if (warp == 2 && fin && lane == 0) prefetch_l2(pofs<uint8_t>(P.out, W.q0 * 65536), tail ? 8192 : 65536);
      DUMP(warp == 1 && lane == 0, 2, 8, 14);
    }
}

}

extern "C" void kernel_launch(void* const* d_in, const int* in_sizes, int n_in, void* d_out, int out_size) {
  Params P;
  P.x = (const __nv_bfloat16*)d_in[0];
  P.src = (const int*)d_in[1];
  P.dst = (const int*)d_in[2];
  P.dinv = (const __nv_bfloat16*)d_in[3];
  P.wmsg = (const __nv_bfloat16*)d_in[4];
  P.wq = (const __nv_bfloat16*)d_in[5];
  P.wk = (const __nv_bfloat16*)d_in[6];
  P.wv = (const __nv_bfloat16*)d_in[7];
  P.wout = (const __nv_bfloat16*)d_in[8];
  P.out = (__nv_bfloat16*)d_out;
  P.zero = 0;
  for (int c = 0; c < NCTA; c++) P.w[c] = make_work(c);
  static void* scr = nullptr;
  if (!scr) {
    cudaFuncSetAttribute(gps_kernel, cudaFuncAttributeMaxDynamicSharedMemorySize, SMEM_BYTES);
    cudaGetSymbolAddress(&scr, g_scr);
  }
  P.s = (Scratch*)((((uintptr_t)scr + SCR_ALIGN - 1) & ~(uintptr_t)(SCR_ALIGN - 1)) + SCR_OFS);
  P.u = (uint4*)(((uintptr_t)P.s->u + 511) & ~(uintptr_t)511);
  if (((uintptr_t)P.u >> 32) != (((uintptr_t)(P.u + NN * 32) - 1) >> 32)) P.u += NN * 32;
  gps_kernel<<<NCTA, 384, SMEM_BYTES>>>(P);
}
```
